```python
import torch

def _softmax(x, axis=-1):
    return torch.softmax(x, dim=axis)
def _gelu(x):
    return torch.nn.functional.gelu(x, approximate="tanh")
def _silu(x):
    return torch.nn.functional.silu(x)
def _sigmoid(x):
    return torch.sigmoid(x)
def _layernorm(x, axis=-1, eps=1e-5):
    m = x.mean(dim=axis, keepdim=True)
    v = x.var(dim=axis, keepdim=True, unbiased=False)
    return (x - m) / torch.sqrt(v + eps)
def _scatter_add(tgt, idx, src, axis=0):
    return tgt.clone().index_add_(axis, idx, src)
def _segment_sum(src, seg, n):
    out = torch.zeros((n,) + src.shape[1:], dtype=src.dtype)
    return out.index_add_(0, seg, src)
def _pad(x, pw):
    flat = tuple(v for pair in reversed(pw) for v in pair)
    return torch.nn.functional.pad(x, flat)

kernel_name = 'sequential_preLN__sliding_block_cached__glu_gated_swiglu__decode'

def setup_inputs():

    _w = (lambda a: (lambda t: t.to(torch.bfloat16) if t.is_floating_point() else t)(torch.as_tensor(a)))
    def _A_setup():
        B, Sq, D = 1, 1, 640
        Hq, Hkv, Sk, Dh = 32, 32, 32768, 192
        assert Hq % Hkv == 0, (Hq, Hkv)
        return {
            "x": _w((lambda *s: torch.randn(*s, dtype=torch.bfloat16) * 0.05)(B, Sq, D)),
            "k_cache": _w((lambda *s: torch.randn(*s, dtype=torch.bfloat16) * 1.6)(B, Hkv, Sk, Dh)),
            "v_cache": _w((lambda *s: torch.randn(*s, dtype=torch.bfloat16) * 0.8)(B, Hkv, Sk, Dh)),
            "wq": _w((lambda *s: torch.randn(*s, dtype=torch.bfloat16) * 1.6)(D, Hq * Dh) * (D ** -0.5)),
            "wo": _w((lambda *s: torch.randn(*s, dtype=torch.bfloat16) * 0.8)(Hq * Dh, D) * ((Hq * Dh) ** -0.5)),
        }
    _A_in = _A_setup()

    def _B_setup():
        B, S, D, F = 1, 1, 640, 1536
        return {
            "x": _w((lambda *s: torch.randn(*s, dtype=torch.bfloat16) * 0.05)(B, S, D)),
            "w1": _w((lambda *s: torch.randn(*s, dtype=torch.bfloat16) * 0.4)(D, F) * (2.0 / D) ** 0.5),
            "w3": _w((lambda *s: torch.randn(*s, dtype=torch.bfloat16) * 0.4)(D, F) * (2.0 / D) ** 0.5),
            "w2": _w((lambda *s: torch.randn(*s, dtype=torch.bfloat16) * 0.4)(F, D) * (2.0 / F) ** 0.5),
        }
    _B_in = _B_setup()

    return {
        "A_x": _A_in["x"],
        "A_k_cache": _A_in["k_cache"],
        "A_v_cache": _A_in["v_cache"],
        "A_wq": _A_in["wq"],
        "A_wo": _A_in["wo"],
        "B_x": _B_in["x"],
        "B_w1": _B_in["w1"],
        "B_w3": _B_in["w3"],
        "B_w2": _B_in["w2"],
    }

def reference(A_x, A_k_cache, A_v_cache, A_wq, A_wo, B_x, B_w1, B_w3, B_w2):
    def _A_ref(x, k_cache, v_cache, wq, wo):
        B, Sq, D = x.shape
        Hq, Dh = 32, 192
        Hkv, Sk = k_cache.shape[1], k_cache.shape[2]
        W = min(4096, max(256, Sk // 4))
        rep = Hq // Hkv
        q = (lambda x, *d: x.permute(*d))((x @ wq).reshape(B, Sq, Hq, Dh), 0, 2, 1, 3)
        k = (lambda x, n, axis: torch.repeat_interleave(x, n, dim=axis))(k_cache[:, :, Sk - W:, :], rep, axis=1)
        v = (lambda x, n, axis: torch.repeat_interleave(x, n, dim=axis))(v_cache[:, :, Sk - W:, :], rep, axis=1)
        scores = torch.einsum("bhqd,bhkd->bhqk", q, k) * (Dh ** -0.5)
        p = _softmax(scores, axis=-1)
        o = torch.einsum("bhqk,bhkd->bhqd", p, v)
        return (lambda x, *d: x.permute(*d))(o, 0, 2, 1, 3).reshape(B, Sq, Hq * Dh) @ wo

    def _B_ref(x, w1, w3, w2):
        gate = torch.einsum("bsd,df->bsf", x, w1)
        up = torch.einsum("bsd,df->bsf", x, w3)
        h = _silu(gate) * up
        out = torch.einsum("bsf,fd->bsd", h, w2)
        return out

    x = A_x
    h = x + _A_ref(_layernorm(x, axis=-1), A_k_cache, A_v_cache, A_wq, A_wo)
    h2 = h + _B_ref(_layernorm(h, axis=-1), B_w1, B_w3, B_w2)
    return h2
```

```cpp
#include <cuda_runtime.h>
#include <cuda_bf16.h>
#include <cuda.h>
#include <stdint.h>

namespace {

constexpr int D_MODEL = 640;
constexpr int NHEAD = 32;
constexpr int DH = 192;
constexpr int SK = 32768;
constexpr int WIN = 4096;
constexpr int FF = 1536;

constexpr int NCTA = 128;
constexpr int NCONS = 256;
constexpr int NTHREADS = NCONS + 96;
constexpr int ROW_BYTES = DH * 2;
constexpr int TILE_BYTES = 32 * ROW_BYTES;
constexpr int NSLOT = 16;
constexpr int NKT = 32;
constexpr int NQT = 5;
constexpr int QSLOT = NSLOT - NQT;
constexpr int NFFN = 96;
constexpr int NRED = 80;
constexpr int NWO = 120;
constexpr int NG = 6;
constexpr int NWP = 8;
constexpr int WPIECE = 8192;
constexpr int NUP = 5;
constexpr int PIECE = 10240;
constexpr int NTAIL = NWP + NUP + 2;
constexpr int N_TAIL0 = 2 * NKT;

#define CFG_NPROBE 4
#define CFG_REDSLEEP 600
#define CFG_GATHER_AT 40
#define CFG_OGATE 2
#define CFG_OSLEEP 100
#define CFG_PROMO_WO 1
#define CFG_PROMO_W13 2
#define CFG_PROMO_W2 2
#define CFG_PROBE_AT 4
#define CFG_QDELAY 1500
#define CFG_QSLEEP 400
#define CFG_BOUNDED_MBAR 0
#define CFG_T 1908
#define CFG_OFF0 2000
#define CFG_TWO 305
#define CFG_TFF 244
#define CFG_TW2 305
#define CFG_HGATE 2
#define CFG_DEP4 mean_b
#define CFG_DEPW2 dep2
#define ABL_NOH 0
#define ABL_NOD 0
#define CFG_HCOPY 2
#define CFG_MA 16
#define CFG_MB 42
#define CFG_ADAPT 58
#define CFG_LAT 1440
#define CFG_SMAX 1964
#define CFG_PSLEEP 1000
#define CFG_PMIN 112
#define CFG_GAPWO 0
#define CFG_GAPFF 0
#define CFG_CAP 8

constexpr int SM_RING = 0;
constexpr int SM_W1 = NWP * WPIECE, SM_W2 = SM_W1 + NUP * WPIECE;
constexpr int SM_SC = SM_RING + NSLOT * TILE_BYTES;
constexpr int SM_RED = SM_SC + 8 * 128 * 4;
constexpr int SM_Q = SM_RED + 8 * DH * 4;
constexpr int SM_OB = SM_Q + DH * 4;
constexpr int SM_HN = SM_OB + 1024 * 2;
constexpr int SM_MISC = SM_HN + D_MODEL * 2;
constexpr int SM_BAR = SM_MISC + 128;
constexpr int SM_TOTAL = SM_BAR + 512;
static_assert(SM_TOTAL <= 232448, "shared memory");

struct __align__(128) Scratch {
    uint64_t qbuf[NHEAD * 4 * DH];
    uint4 mbuf[NHEAD * 32];
    uint64_t sel[NCTA];
    uint32_t epoch;
    uint32_t pad[31];
    unsigned long long pace[2];
};
__device__ Scratch g_scratch;
constexpr int XA_ALIGN = 1 << 20;
constexpr uint32_t SENT = 0xffffffffu;
constexpr int L_GATHER = 0;
constexpr int HCOPY_BYTES = NG * D_MODEL * 2;
constexpr int L_PROBE = 8 * 4096;
constexpr int L_O = 9 * 4096;
constexpr int L_D = 30 * 4096;
static_assert(2 * (L_D + NRED * 4096) <= XA_ALIGN, "");
__device__ unsigned char g_xarea[2 * XA_ALIGN];
__device__ __forceinline__ uint32_t xa_off(uint32_t l, uint32_t side) {
    const uint32_t k = l >> 12;
    return (2 * k + ((side ^ k ^ (k >> 3) ^ (k >> 4) ^ (k >> 6)) & 1)) * 4096 + (l & 4095);
}

#define LST(i) do { } while (0)
#define LSC(i) do { } while (0)
#define LSCD(i, v) do { } while (0)
constexpr uint32_t SPIN_LIMIT = 1u << 24;

__device__ __forceinline__ uint32_t now_q() { uint32_t t; asm volatile("mov.u32 %0, %globaltimer_lo;" : "=r"(t)); return t * 4; }
__device__ __forceinline__ void wait_until(uint32_t due) {
    for (int n = 0; n < 4096 && (int)(now_q() - due) < 0; n++) { }
}
__device__ __forceinline__ void sleep_until(uint32_t due) {
    for (int n = 0; n < 4096 && (int)(now_q() - due) < 0; n++) __nanosleep(200);
}
__device__ __forceinline__ uint32_t smem_u32(const void* p) { return (uint32_t)__cvta_generic_to_shared(p); }
__device__ __forceinline__ void mbar_init(uint32_t bar, uint32_t cnt) {
    asm volatile("mbarrier.init.shared::cta.b64 [%0], %1;" ::"r"(bar), "r"(cnt) : "memory");
}
__device__ __forceinline__ void mbar_expect_tx(uint32_t bar, uint32_t bytes) {
    asm volatile("mbarrier.arrive.expect_tx.shared::cta.b64 _, [%0], %1;" ::"r"(bar), "r"(bytes) : "memory");
}
__device__ __forceinline__ void mbar_arrive(uint32_t bar) {
    asm volatile("mbarrier.arrive.shared::cta.b64 _, [%0];" ::"r"(bar) : "memory");
}
__device__ __forceinline__ bool mbar_test(uint32_t bar, uint32_t parity) {
    uint32_t ok;
    asm volatile("{\n.reg .pred p;\nmbarrier.test_wait.parity.shared::cta.b64 p, [%1], %2;\nselp.u32 %0, 1, 0, p;\n}"
                 : "=r"(ok) : "r"(bar), "r"(parity) : "memory");
    return ok;
}
__device__ __forceinline__ void mbar_wait(uint32_t bar, uint32_t parity) {
    asm volatile("{\n.reg .pred p;\nW_%=:\nmbarrier.try_wait.parity.shared::cta.b64 p, [%0], %1;\n@!p bra W_%=;\n}" ::"r"(bar), "r"(parity) : "memory");
}
__device__ __forceinline__ void bulk_load(uint32_t dst, const void* src, uint32_t bytes, uint32_t bar, uint64_t pol) {
    asm volatile("cp.async.bulk.shared::cluster.global.mbarrier::complete_tx::bytes.L2::cache_hint [%0], [%1], %2, [%3], %4;"
                 ::"r"(dst), "l"(src), "r"(bytes), "r"(bar), "l"(pol) : "memory");
}
__device__ __forceinline__ void tma_5d(uint32_t dst, const CUtensorMap* tm, int c0, int c1, int c2, int c4, uint32_t bar) {
    asm volatile("cp.async.bulk.tensor.5d.shared::cluster.global.mbarrier::complete_tx::bytes [%0], [%1, {%3, %4, %5, %7, %6}], [%2];"
                 ::"r"(dst), "l"(reinterpret_cast<uint64_t>(tm)), "r"(bar), "r"(c0), "r"(c1), "r"(c2), "r"(c4), "r"(0) : "memory");
}
__device__ __forceinline__ void pin(uint32_t& v) { asm volatile("" : "+r"(v)); }
__device__ __forceinline__ uint32_t after(uint32_t bar, uint32_t v, uint32_t zero) { return bar | (v & zero); }
__device__ __forceinline__ void pinf(float& v) { asm volatile("" : "+f"(v)); }
template <class T> __device__ __forceinline__ void pin(T*& v) { asm volatile("" : "+l"(v)); }
__device__ __forceinline__ void sts32(uint32_t a, float v) { asm volatile("st.shared.f32 [%0], %1;" ::"r"(a), "f"(v) : "memory"); }
__device__ __forceinline__ void sts64(uint32_t a, uint32_t x, uint32_t y) { asm volatile("st.shared.v2.u32 [%0], {%1, %2};" ::"r"(a), "r"(x), "r"(y) : "memory"); }
__device__ __forceinline__ void cons_sync() { asm volatile("bar.sync 1, 256;" ::: "memory"); }

__device__ __forceinline__ uint4 lds128(uint32_t a) {
    uint4 v;
    asm volatile("ld.shared.v4.u32 {%0,%1,%2,%3}, [%4];" : "=r"(v.x), "=r"(v.y), "=r"(v.z), "=r"(v.w) : "r"(a));
    return v;
}
__device__ __forceinline__ float4 lds128f(uint32_t a) {
    float4 v;
    asm volatile("ld.shared.v4.f32 {%0,%1,%2,%3}, [%4];" : "=f"(v.x), "=f"(v.y), "=f"(v.z), "=f"(v.w) : "r"(a) : "memory");
    return v;
}
__device__ __forceinline__ float2 lds64f(uint32_t a) {
    float2 v;
    asm volatile("ld.shared.v2.f32 {%0,%1}, [%2];" : "=f"(v.x), "=f"(v.y) : "r"(a) : "memory");
    return v;
}
__device__ __forceinline__ float lds32f(uint32_t a) {
    float v;
    asm volatile("ld.shared.f32 %0, [%1];" : "=f"(v) : "r"(a) : "memory");
    return v;
}
__device__ __forceinline__ uint32_t lds32(uint32_t a) {
    uint32_t v;
    asm volatile("ld.shared.u32 %0, [%1];" : "=r"(v) : "r"(a));
    return v;
}
__device__ __forceinline__ void ldsm_x2_t(uint32_t* r, uint32_t a) {
    asm volatile("ldmatrix.sync.aligned.m8n8.x2.trans.shared.b16 {%0,%1}, [%2];" : "=r"(r[0]), "=r"(r[1]) : "r"(a));
}
__device__ __forceinline__ void ldsm_x4_t(uint32_t* r, uint32_t a) {
    asm volatile("ldmatrix.sync.aligned.m8n8.x4.trans.shared.b16 {%0,%1,%2,%3}, [%4];"
                 : "=r"(r[0]), "=r"(r[1]), "=r"(r[2]), "=r"(r[3]) : "r"(a));
}
__device__ __forceinline__ void mma_bf16(float* c, const uint32_t* a, uint32_t b0, uint32_t b1) {
    asm volatile("mma.sync.aligned.m16n8k16.row.col.f32.bf16.bf16.f32 {%0,%1,%2,%3}, {%4,%5,%6,%7}, {%8,%9}, {%0,%1,%2,%3};"
                 : "+f"(c[0]), "+f"(c[1]), "+f"(c[2]), "+f"(c[3]) : "r"(a[0]), "r"(a[1]), "r"(a[2]), "r"(a[3]), "r"(b0), "r"(b1));
}
__device__ __forceinline__ float bf_lo(uint32_t u) { return __uint_as_float(u << 16); }
__device__ __forceinline__ float bf_hi(uint32_t u) { return __uint_as_float(u & 0xffff0000u); }
__device__ __forceinline__ uint32_t pack_bf(float hi, float lo) { uint32_t r; asm("cvt.rn.bf16x2.f32 %0, %1, %2;" : "=r"(r) : "f"(hi), "f"(lo)); return r; }
__device__ __forceinline__ float bfr(float x) { return __uint_as_float(pack_bf(x, 0.f)); }

__device__ __forceinline__ uint64_t pk(float v, uint32_t tag) { return ((uint64_t)tag << 32) | (uint64_t)__float_as_uint(v); }
__device__ __forceinline__ void ll_st1(uint64_t* p, float a, uint32_t tag) {
    asm volatile("st.relaxed.gpu.global.b64 [%0], %1;" ::"l"(p), "l"(pk(a, tag)) : "memory");
}
__device__ __forceinline__ uint64_t ll_ld1(const uint64_t* p) {
    uint64_t v;
    asm volatile("ld.relaxed.gpu.global.b64 %0, [%1];" : "=l"(v) : "l"(p) : "memory");
    return v;
}
__device__ __forceinline__ uint32_t in_word(float v) {
    uint32_t r;
    asm("min.u32 %0, %1, 0xfffffffe;" : "=r"(r) : "r"(__float_as_uint(v)));
    return r;
}
__device__ __forceinline__ void in_st1(void* p, float v) {
    asm volatile("st.relaxed.gpu.global.u32 [%0], %1;" ::"l"(p), "r"(in_word(v)) : "memory");
}
__device__ __forceinline__ void in_st4(void* p, uint32_t a, uint32_t b, uint32_t c, uint32_t d) {
    asm volatile("st.relaxed.gpu.global.v4.u32 [%0], {%1, %2, %3, %4};" ::"l"(p), "r"(a), "r"(b), "r"(c), "r"(d) : "memory");
}
__device__ __forceinline__ uint32_t in_ld1(const void* p) {
    uint32_t v;
    asm volatile("ld.relaxed.gpu.global.u32 %0, [%1];" : "=r"(v) : "l"(p) : "memory");
    return v;
}
__device__ __forceinline__ uint4 in_ld4(const void* p) {
    uint4 v;
    asm volatile("ld.relaxed.gpu.global.v4.u32 {%0, %1, %2, %3}, [%4];" : "=r"(v.x), "=r"(v.y), "=r"(v.z), "=r"(v.w) : "l"(p) : "memory");
    return v;
}
__device__ __forceinline__ void in_st2(void* p, uint32_t a, uint32_t b) {
    asm volatile("st.relaxed.gpu.global.v2.u32 [%0], {%1, %2};" ::"l"(p), "r"(min(a, SENT - 1)), "r"(min(b, SENT - 1)) : "memory");
}
__device__ __forceinline__ void in_ld2p(const void* p, uint2& v, bool on) {
    asm volatile("{\n.reg .pred q;\nsetp.ne.u32 q, %3, 0;\n@q ld.relaxed.gpu.global.v2.u32 {%0, %1}, [%2];\n}"
                 : "+r"(v.x), "+r"(v.y) : "l"(p), "r"((uint32_t)on) : "memory");
}
__device__ __forceinline__ bool in_ok(const uint2& v) { return max(v.x, v.y) != SENT; }
__device__ __forceinline__ void in_ld4p(const void* p, uint4& v, bool on) {
    asm volatile("{\n.reg .pred q;\nsetp.ne.u32 q, %5, 0;\n@q ld.relaxed.gpu.global.v4.u32 {%0, %1, %2, %3}, [%4];\n}"
                 : "+r"(v.x), "+r"(v.y), "+r"(v.z), "+r"(v.w) : "l"(p), "r"((uint32_t)on) : "memory");
}
__device__ __forceinline__ bool in_ok(const uint4& v) { return max(max(v.x, v.y), max(v.z, v.w)) != SENT; }
__device__ __forceinline__ bool tag_ok(uint64_t v, uint32_t tag) { return (uint32_t)(v >> 32) == tag; }
__device__ __forceinline__ float val_of(uint64_t v) { return __uint_as_float((uint32_t)v); }
__device__ __forceinline__ void pkt_st(uint4* p, uint64_t lo, uint64_t hi) {
    asm volatile("{\n.reg .b128 t;\nmov.b128 t, {%1, %2};\nst.relaxed.gpu.global.b128 [%0], t;\n}" ::"l"(p), "l"(lo), "l"(hi) : "memory");
}
__device__ __forceinline__ void pkt_ld(const uint4* p, uint64_t& lo, uint64_t& hi) {
    asm volatile("{\n.reg .b128 t;\nld.relaxed.gpu.global.b128 t, [%2];\nmov.b128 {%0, %1}, t;\n}" : "=l"(lo), "=l"(hi) : "l"(p) : "memory");
}

__device__ __forceinline__ float warp_sum(float v) {
#pragma unroll
    for (int o = 16; o > 0; o >>= 1) v += __shfl_xor_sync(0xffffffffu, v, o);
    return v;
}
__device__ __forceinline__ float warp_max(float v) {
#pragma unroll
    for (int o = 16; o > 0; o >>= 1) v = fmaxf(v, __shfl_xor_sync(0xffffffffu, v, o));
    return v;
}
__device__ __forceinline__ void fma8(float* acc, const uint4& u, float w) {
    acc[0] = fmaf(w, bf_lo(u.x), acc[0]); acc[1] = fmaf(w, bf_hi(u.x), acc[1]);
    acc[2] = fmaf(w, bf_lo(u.y), acc[2]); acc[3] = fmaf(w, bf_hi(u.y), acc[3]);
    acc[4] = fmaf(w, bf_lo(u.z), acc[4]); acc[5] = fmaf(w, bf_hi(u.z), acc[5]);
    acc[6] = fmaf(w, bf_lo(u.w), acc[6]); acc[7] = fmaf(w, bf_hi(u.w), acc[7]);
}
__device__ __forceinline__ void dot8(float& s0, float& s1, const uint4& u, const float* q) {
    s0 = fmaf(q[0], bf_lo(u.x), s0); s1 = fmaf(q[1], bf_hi(u.x), s1);
    s0 = fmaf(q[2], bf_lo(u.y), s0); s1 = fmaf(q[3], bf_hi(u.y), s1);
    s0 = fmaf(q[4], bf_lo(u.z), s0); s1 = fmaf(q[5], bf_hi(u.z), s1);
    s0 = fmaf(q[6], bf_lo(u.w), s0); s1 = fmaf(q[7], bf_hi(u.w), s1);
}
__device__ __forceinline__ float sqrt_fast(float x) { float r; asm("sqrt.approx.ftz.f32 %0, %1;" : "=f"(r) : "f"(x)); return r; }
__device__ __forceinline__ float rcp_fast(float x) { float r; asm("rcp.approx.ftz.f32 %0, %1;" : "=f"(r) : "f"(x)); return r; }
__device__ __forceinline__ float ex2(float x) { float r; asm("ex2.approx.ftz.f32 %0, %1;" : "=f"(r) : "f"(x)); return r; }
constexpr float L2E = 1.4426950408889634f;
__device__ __forceinline__ void ln_finish(float s1, float s2, float& mean_b, float& inv_den) {
    const float mean = s1 * (1.0f / D_MODEL);
    const float var = fmaxf(fmaf(-mean, mean, s2 * (1.0f / D_MODEL)), 0.f);
    mean_b = bfr(mean);
    inv_den = rcp_fast(bfr(sqrt_fast(bfr(bfr(var) + 1e-5f))));
}
__device__ __forceinline__ float ln_apply(float v, float mean_b, float inv_den) { return bfr(bfr(v - mean_b) * inv_den); }

struct KParams {
    const __nv_bfloat16* x;
    const __nv_bfloat16* k;
    const __nv_bfloat16* v;
    const __nv_bfloat16* wq;
    __nv_bfloat16* out;
    Scratch* sc;
    unsigned char* xa;
    uint32_t zero;
    uint32_t t_first;
    uint32_t t_step;
    uint32_t t_smax;
    uint32_t t_lat;
};
struct TMaps { CUtensorMap wo, w1, w3, w2; };

__global__ void __launch_bounds__(NTHREADS, 1)
fused_decode_kernel(const KParams p, const __grid_constant__ TMaps tm) {
    extern __shared__ __align__(1024) unsigned char smem[];
    const uint32_t sbase = smem_u32(smem);
    const int tid = threadIdx.x;
    const int b = blockIdx.x;
    const int head = b >> 2, sp = b & 3;
    {
        if (tid < 240) {
            const int rg = tid / 24, ch = tid - rg * 24;
            const char* src = reinterpret_cast<const char*>(p.wq) + (size_t)(sp * 160 + rg) * (NHEAD * DH * 2) + head * ROW_BYTES + ch * 16;
            uint32_t dst = sbase + SM_RING + QSLOT * TILE_BYTES + tid * 16;
#pragma unroll 1
            for (int i = 0; i < 16; i++) {
                asm volatile("cp.async.cg.shared.global [%0], [%1], 16;" ::"r"(dst), "l"(src) : "memory");
                dst += 10 * ROW_BYTES;
                src += (size_t)10 * (NHEAD * DH * 2);
            }
        }
    }
    const int warp = __shfl_sync(0xffffffffu, tid >> 5, 0), lane = tid & 31;
    const int kg = b / 20, ng = b - kg * 20;
    const uint32_t bar_full = sbase + SM_BAR;
    const uint32_t bar_empty = sbase + SM_BAR + 128;
    const uint32_t bar_tail = sbase + SM_BAR + 256;
    const uint32_t bar_h = bar_tail + 8 * NTAIL;
    const uint32_t bar_topo = bar_h + 8;
    const uint32_t bar_red = bar_h + 16;
    const uint32_t bar_pace = bar_h + 24;
    volatile uint32_t* s_sel = reinterpret_cast<volatile uint32_t*>(smem + SM_MISC + 64);
    volatile uint32_t* s_pace = reinterpret_cast<volatile uint32_t*>(smem + SM_MISC + 96);
    volatile uint32_t* s_dummy = reinterpret_cast<volatile uint32_t*>(smem + SM_MISC + 112);

    if (warp == 8) {
        const uint32_t c_start = now_q();
        uint64_t pol_stream;
        asm volatile("createpolicy.fractional.L2::evict_first.b64 %0, 1.0;" : "=l"(pol_stream));
        const size_t kv_off = ((size_t)head * SK + (SK - WIN)) * ROW_BYTES + (size_t)sp * TILE_BYTES;
        const char* kp = reinterpret_cast<const char*>(p.k) + kv_off;
        if (lane == 0) {
#pragma unroll 1
            for (int i = 0; i < NSLOT; i++) { mbar_init(bar_full + 8 * i, 1); mbar_init(bar_empty + 8 * i, 8); }
#pragma unroll 1
            for (int i = 0; i < NTAIL + 4; i++) mbar_init(bar_tail + 8 * i, (i < NTAIL || (i - NTAIL) & 1) ? 1 : 8);
            asm volatile("fence.mbarrier_init.release.cluster;" ::: "memory");
        }
        __syncwarp();
        asm volatile("bar.arrive 2, 288;" ::: "memory");
        asm volatile("bar.arrive 3, 64;" ::: "memory");
        asm volatile("bar.arrive 4, 64;" ::: "memory");
        if (lane >= 1 && lane <= 4) asm volatile("prefetch.tensormap [%0];" ::"l"(reinterpret_cast<uint64_t>(&tm.wo + (lane - 1))) : "memory");
        if (lane == 0) {
            const char* vp = reinterpret_cast<const char*>(p.v) + kv_off;
            uint32_t due = c_start + p.t_first, step = p.t_step;
            const char* src = kp;
#pragma unroll 1
            for (int n = 0; n < N_TAIL0; n++) {
                const int slot = n & (NSLOT - 1);
                const int use = (n >> 4) + (slot >= QSLOT);
                if (n >= CFG_CAP) mbar_wait(bar_full + 8 * ((n - CFG_CAP) & (NSLOT - 1)), ((n - CFG_CAP) >> 4) & 1);
                if (use >= 1) mbar_wait(bar_empty + 8 * slot, (use - 1) & 1);
                if (n == CFG_ADAPT) { mbar_wait(bar_pace, 0); due = s_pace[0]; step = s_pace[1]; }
                const uint32_t full = bar_full + 8 * slot;
                mbar_expect_tx(full, TILE_BYTES);
                wait_until(due);
                LST(128 + n);
                bulk_load(sbase + SM_RING + slot * TILE_BYTES, src, TILE_BYTES, full, pol_stream);
                due += step;
                src = n == NKT - 1 ? vp : src + 4 * TILE_BYTES;
            }
            const int ntail = b < NFFN ? NTAIL : b < NWO ? NWP : 0;
            due += 4 * CFG_GAPWO;
#pragma unroll 1
            for (int j = 0; j < ntail; j++) {
                const int off = j <= NWP + NUP ? j * WPIECE : SM_W2 + PIECE, len = j < NWP + NUP ? WPIECE : PIECE;
                mbar_wait(bar_empty + 8 * ((off + len - 1) / TILE_BYTES), 1);
                const uint32_t full = bar_tail + 8 * j, dst = sbase + off;
                mbar_expect_tx(full, len);
                wait_until(due);
                LST(128 + N_TAIL0 + j);
                if (j < NWP) {
                    tma_5d(dst, &tm.wo, ng * 32, kg * 1024 + j * 128, 0, 0, full);
                } else if (j < NWP + NUP) {
                    tma_5d(dst, &tm.w1, b * 16, 0, (j - NWP) * 4, 0, full);
                    tma_5d(dst + WPIECE / 2, &tm.w3, b * 16, 0, (j - NWP) * 4, 0, full);
                } else {
                    tma_5d(dst, &tm.w2, 0, (j - NWP - NUP) * 5, b * 16, 0, full);
                }
                due += step * ((j < NWP - 1 ? CFG_TWO : j == NWP - 1 ? CFG_TWO + CFG_GAPFF : j < NWP + NUP ? CFG_TFF : CFG_TW2) * 4096 / 478) >> 12;
            }
        }
    } else if (warp == 10) {
        asm volatile("bar.sync 4, 64;" ::: "memory");
        if (lane == 0) {
            uint32_t epoch0;
            asm volatile("ld.relaxed.gpu.global.u32 %0, [%1];" : "=r"(epoch0) : "l"(&p.sc->epoch) : "memory");
            constexpr int MN = 8;
            const uint32_t t0 = now_q();
            uint32_t sa = 0, sb = 0;
#pragma unroll 1
            for (int n = 0; n < CFG_MB + MN; n++) {
                mbar_wait(bar_full + 8 * (n & (NSLOT - 1)), (n >> 4) & 1);
                const uint32_t t = now_q() - t0;
                LST(n);
                if ((uint32_t)(n - CFG_MA) < MN) sa += t;
                if (n >= CFG_MB) sb += t;
            }
            const uint32_t mb = t0 + sb / MN;
            unsigned long long* pace = p.sc->pace + ((epoch0 + 1) & 1);
            asm volatile("red.relaxed.gpu.global.add.u64 [%0], %1;" ::"l"(pace), "l"((unsigned long long)mb << 32 | min((sb - sa) / (4 * MN), 0xffffu) << 8 | 1) : "memory");
            if (b == 0) p.sc->pace[epoch0 & 1] = 0;
            unsigned long long v;
            uint32_t n = 0, cnt;
#pragma unroll 1
            do {
                __nanosleep(n ? 200 : CFG_PSLEEP);
                asm volatile("ld.relaxed.gpu.global.u64 %0, [%1];" : "=l"(v) : "l"(pace) : "memory");
                cnt = (uint32_t)v & 0xff;
                if (++n > SPIN_LIMIT) __trap();
            } while (cnt < CFG_PMIN);
            const float inv = rcp_fast((float)cnt);
            const uint32_t step = min(max((uint32_t)((float)((uint32_t)v >> 8) * inv * (4.0f / (CFG_MB - CFG_MA))), p.t_step), p.t_smax);
            s_pace[0] = mb + (int)((float)(int)((uint32_t)(v >> 32) - cnt * mb) * inv) + step * (2 * (CFG_ADAPT - CFG_MB) - (MN - 1)) / 2 - p.t_lat;
            s_pace[1] = step;
            mbar_arrive(bar_pace);
            LST(89);
        }
    } else if (warp == 9) {
        const uint32_t c_start = now_q();
        uint32_t epoch0;
        asm volatile("ld.relaxed.gpu.global.u32 %0, [%1];" : "=r"(epoch0) : "l"(&p.sc->epoch) : "memory");
        if (lane < 4) in_st4(p.xa + xa_off(L_PROBE + b * 32 + (lane & 1) * 16, lane >> 1), SENT, SENT, SENT, SENT);
        int vote = 0;
        uint32_t lat[2] = {0, 0};
        sleep_until(c_start + p.t_first + (CFG_PROBE_AT + 8) * p.t_step);
#pragma unroll 1
        for (int r = 0; r < CFG_NPROBE; r++) {
            uint32_t d[2];
#pragma unroll
            for (int i = 0; i < 2; i++) {
                const unsigned char* a = p.xa + xa_off(L_PROBE + (lane & 15) * 256, i);
                const uint32_t c0 = (uint32_t)clock();
                uint32_t v;
                asm volatile("ld.relaxed.gpu.global.u32 %0, [%1];" : "=r"(v) : "l"(a) : "memory");
                if (__any_sync(0xffffffffu, v == 0x7ff00123u)) s_dummy[0] = v;
                d[i] = (uint32_t)clock() - c0;
                lat[i] += min(d[i], 1500u);
            }
            vote += (d[1] < d[0]) - (d[0] < d[1]);
        }
        const uint32_t sel = vote ? vote > 0 : lat[1] < lat[0];
        const uint32_t tag = epoch0 + 1;
        {
            unsigned char* slot[9];
#pragma unroll
            for (int i = 0; i < 2; i++) slot[i] = p.xa + xa_off(L_O + (head * 4 + sp) * DH * 2 + min(lane, 23) * 16, i);
            slot[2] = p.xa + xa_off(L_GATHER + (lane >> 3) * HCOPY_BYTES + (min(kg, NG - 1) * D_MODEL + ng * 32 + (lane & 3) * 8) * 2, lane >> 2 & 1);
#pragma unroll
            for (int i = 0; i < 6; i++) slot[3 + i] = p.xa + xa_off(L_D + min(b, NRED - 1) * 4096 + i * 512 + lane * 16, sel);
            uint32_t acc = SENT;
#pragma unroll
            for (int i = 0; i < 9; i++) if (i < 2 ? lane < 24 : i == 2 ? lane < 8 * CFG_HCOPY && b < NWO : b < NRED) in_st4(slot[i], SENT, SENT, SENT, SENT);
#pragma unroll
            for (int i = 0; i < 9; i++) if (i < 2 ? lane < 24 : i == 2 ? lane < 8 * CFG_HCOPY && b < NWO : b < NRED) acc &= in_ld1(slot[i]);
            if (__any_sync(0xffffffffu, acc != SENT)) __trap();
        }
        asm volatile("bar.sync 3, 64;" ::: "memory");
        if (lane == 0) ll_st1(p.sc->sel + b, __uint_as_float(sel), tag);
        {
            uint32_t n = 0;
            sleep_until(c_start + p.t_first + (CFG_GATHER_AT + 8) * p.t_step);
            uint64_t e[4];
            bool ok;
            n = 0;
#pragma unroll 1
            do {
                if (n) __nanosleep(500);
#pragma unroll
                for (int i = 0; i < 4; i++) e[i] = ll_ld1(p.sc->sel + i * 32 + lane);
                ok = __all_sync(0xffffffffu, tag_ok(e[0], tag) && tag_ok(e[1], tag) && tag_ok(e[2], tag) && tag_ok(e[3], tag));
                if (++n > SPIN_LIMIT) __trap();
            } while (!ok);
#pragma unroll
            for (int i = 0; i < 4; i++) {
                const uint32_t m = __ballot_sync(0xffffffffu, (uint32_t)e[i] & 1);
                if (lane == 0) s_sel[i] = m;
            }
            __syncwarp();
            if (lane == 0) mbar_arrive(bar_topo);
        }
        if (b < NRED) {
            const unsigned char* src = p.xa + xa_off(L_D + b * 4096, sel) + lane * 16;
            while (!mbar_test(bar_tail, 0)) __nanosleep(CFG_REDSLEEP);
            mbar_wait(bar_h, 0);
            const uint2 res = *reinterpret_cast<const uint2*>(smem + SM_HN + b * 16 + (lane & 1) * 8);
            uint4 u[6];
#pragma unroll
            for (int i = 0; i < 6; i++) u[i] = make_uint4(0, 0, 0, 0);
            uint32_t pend = ABL_NOD ? 0 : 0x3f, n = 0;
            __nv_bfloat16* dst = p.out + b * 8 + (lane & 1) * 4;
#pragma unroll
            for (int i = 0; i < 6; i++) { pin(u[i].x); pin(u[i].y); pin(u[i].z); pin(u[i].w); }
            pin(src); pin(dst); pin(pend);
            mbar_wait(bar_red, 0);
#pragma unroll 1
            do {
#pragma unroll
                for (int i = 0; i < 6; i++) in_ld4p(src + i * 512, u[i], pend >> i & 1);
#pragma unroll
                for (int i = 0; i < 6; i++) if (in_ok(u[i])) pend &= ~(1u << i);
                if (++n > SPIN_LIMIT) __trap();
            } while (__any_sync(0xffffffffu, pend != 0));
            float a[4];
#define F_(i, c) __uint_as_float(u[i].c)
            a[0] = ((F_(0, x) + F_(1, x)) + (F_(2, x) + F_(3, x))) + (F_(4, x) + F_(5, x));
            a[1] = ((F_(0, y) + F_(1, y)) + (F_(2, y) + F_(3, y))) + (F_(4, y) + F_(5, y));
            a[2] = ((F_(0, z) + F_(1, z)) + (F_(2, z) + F_(3, z))) + (F_(4, z) + F_(5, z));
            a[3] = ((F_(0, w) + F_(1, w)) + (F_(2, w) + F_(3, w))) + (F_(4, w) + F_(5, w));
#undef F_
#pragma unroll
            for (int o = 2; o < 32; o <<= 1) {
#pragma unroll
                for (int i = 0; i < 4; i++) a[i] += __shfl_xor_sync(0xffffffffu, a[i], o);
            }
            if (lane < 2)
                *reinterpret_cast<uint2*>(dst) =
                    make_uint2(pack_bf(bf_hi(res.x) + bfr(a[1]), bf_lo(res.x) + bfr(a[0])), pack_bf(bf_hi(res.y) + bfr(a[3]), bf_lo(res.y) + bfr(a[2])));
            if (lane == 0) LST(96);
            if (b == 0 && lane == 0) p.sc->epoch = tag;
        }
    } else {
        float* s_red = reinterpret_cast<float*>(smem + SM_RED);
        float* s_q = reinterpret_cast<float*>(smem + SM_Q);
        float* sc = reinterpret_cast<float*>(smem + SM_SC) + warp * 128;
        const int g = lane >> 3, c = lane & 7;
        const int hcol = warp * 80 + min(lane, 4 * NUP - 1) * 4;
        uint32_t xr, epoch0;
        uint2 xu[5], xres;
        {
            const char* xb = reinterpret_cast<const char*>(p.x);
            asm volatile("ld.global.nc.u16 %0, [%1];" : "=r"(xr) : "l"(xb + (sp * 160 + min(lane >> 2, NQT - 1) * 32 + warp * 4 + (lane & 3)) * 2));
#pragma unroll
            for (int i = 0; i < 5; i++) asm volatile("ld.global.nc.v2.u32 {%0, %1}, [%2];" : "=r"(xu[i].x), "=r"(xu[i].y) : "l"(xb + i * 256 + lane * 8));
            asm volatile("ld.global.nc.v2.u32 {%0, %1}, [%2];" : "=r"(xres.x), "=r"(xres.y) : "l"(xb + hcol * 2));
            asm volatile("ld.relaxed.gpu.global.u32 %0, [%1];" : "=r"(epoch0) : "l"(&p.sc->epoch) : "memory");
        }
        if (tid < DH) ll_st1(p.sc->qbuf + (head * 4 + sp) * DH + tid, 0.f, 0);
        if (lane == 0) pkt_st(p.sc->mbuf + head * 32 + sp * 8 + warp, 0, 0);
        const uint32_t rowoff = sbase + SM_RING + (warp * 4 + g) * ROW_BYTES + c * 16;

        float mean_b, inv_den;
        uint32_t tag = 0;
        const int t4 = lane & 3;
        uint32_t aoff[5], goff[NG], odst = 0, osrc[4];
        const int wr = warp * 16 + (lane & 15);
        uint32_t wa = sbase + wr * 64 + (((lane >> 4) ^ (wr >> 1 & 3)) << 4), wa2 = wa ^ 32, oa = sbase + SM_OB + warp * 32 + t4 * 4;
        uint32_t pw = sbase + SM_RED + (warp * 32 + t4 * 2) * 4, pr = sbase + SM_RED + (lane & 15) * 8;
        uint32_t red_dst = sbase + SM_RED + 1024 + (warp * 32 + t4 * 8 + (lane >> 2)) * 8;
        uint32_t red_src = sbase + SM_RED + 1024 + lane * 8;
        uint32_t hdst = sbase + SM_HN + hcol * 2, stat = sbase + SM_MISC + warp * 8;
        uint32_t w13a = sbase + SM_W1 + (warp * 16 + (lane & 7) + ((lane >> 4) << 3)) * 32 + (((lane >> 3) ^ (lane >> 2)) & 1) * 16;
        uint32_t bar_w2 = bar_tail + 8 * (NWP + NUP + (warp >> 2));
        pin(bar_w2); pin(wa); pin(wa2); pin(oa); pin(pw); pin(pr); pin(red_dst); pin(red_src); pin(hdst); pin(stat); pin(w13a);
        unsigned char* dst[5];
        unsigned char* gdst = nullptr;

        {
            float s1 = 0.f, s2 = 0.f;
#pragma unroll
            for (int i = 0; i < 5; i++) {
                const float a0 = bf_lo(xu[i].x), a1 = bf_hi(xu[i].x), a2 = bf_lo(xu[i].y), a3 = bf_hi(xu[i].y);
                s1 += (a0 + a1) + (a2 + a3);
                s2 = fmaf(a0, a0, fmaf(a1, a1, fmaf(a2, a2, fmaf(a3, a3, s2))));
            }
#pragma unroll
            for (int o = 16; o > 0; o >>= 1) { s1 += __shfl_xor_sync(0xffffffffu, s1, o); s2 += __shfl_xor_sync(0xffffffffu, s2, o); }
            ln_finish(s1, s2, mean_b, inv_den);
            sc[lane] = ln_apply(bf_lo(xr), mean_b, inv_den);
            asm volatile("cp.async.wait_all;" ::: "memory");
            if (lane == 0) LST(80 + warp);
            asm volatile("bar.sync 2, 288;" ::: "memory");
            tag = epoch0 + 1;
        }

#pragma unroll 1
        for (int ph = 0; ph < 2; ph++) {
            float m_w = 0.f, fscale = 1.f;
            if (ph == 1) {
                float qv[24];
#pragma unroll
                for (int j = 0; j < 3; j++) {
                    const float4 a = *reinterpret_cast<const float4*>(s_q + j * 64 + c * 8);
                    const float4 bq = *reinterpret_cast<const float4*>(s_q + j * 64 + c * 8 + 4);
                    qv[j * 8 + 0] = a.x; qv[j * 8 + 1] = a.y; qv[j * 8 + 2] = a.z; qv[j * 8 + 3] = a.w;
                    qv[j * 8 + 4] = bq.x; qv[j * 8 + 5] = bq.y; qv[j * 8 + 6] = bq.z; qv[j * 8 + 7] = bq.w;
                }
                const float scale = 0.07216878364870322f;
#pragma unroll 1
                for (int t = 0; t < NKT; t++) {
                    const int slot = t & (NSLOT - 1);
                    mbar_wait(bar_full + 8 * slot, (t >> 4) & 1);
                    const uint32_t a = rowoff + slot * TILE_BYTES;
                    const uint4 u0 = lds128(a), u1 = lds128(a + 128), u2 = lds128(a + 256);
                    float s0 = 0.f, s1 = 0.f, s2 = 0.f, s3 = 0.f;
                    dot8(s0, s1, u0, qv); dot8(s2, s3, u1, qv + 8); dot8(s0, s1, u2, qv + 16);
                    s0 = (s0 + s1) + (s2 + s3);
#pragma unroll
                    for (int o = 1; o < 8; o <<= 1) s0 += __shfl_xor_sync(0xffffffffu, s0, o);
                    __syncwarp();
                    if (lane == 0) mbar_arrive(bar_empty + 8 * slot);
                    if (c == 0) sc[t * 4 + g] = bfr(bfr(s0) * scale);
                }
                __syncwarp();
                float4 sv = *reinterpret_cast<const float4*>(sc + lane * 4);
                m_w = warp_max(fmaxf(fmaxf(sv.x, sv.y), fmaxf(sv.z, sv.w)));
                sv.x = ex2((sv.x - m_w) * L2E); sv.y = ex2((sv.y - m_w) * L2E);
                sv.z = ex2((sv.z - m_w) * L2E); sv.w = ex2((sv.w - m_w) * L2E);
                const float l_w = warp_sum((sv.x + sv.y) + (sv.z + sv.w));
                if (lane == 0) pkt_st(p.sc->mbuf + head * 32 + sp * 8 + warp, ((uint64_t)__float_as_uint(l_w) << 32) | __float_as_uint(m_w), (uint64_t)tag << 32);
                *reinterpret_cast<float4*>(sc + lane * 4) = sv;
            }
            __syncwarp();
            float acc[24];
#pragma unroll
            for (int e = 0; e < 24; e++) acc[e] = 0.f;
            const int nt = ph ? NKT : NQT;
#pragma unroll 1
            for (int t = 0; t < nt; t++) {
                const int slot = ph ? (t & (NSLOT - 1)) : QSLOT + t;
                if (ph) mbar_wait(bar_full + 8 * slot, (t >> 4) & 1);
                const uint32_t a = rowoff + slot * TILE_BYTES;
                const uint4 u0 = lds128(a), u1 = lds128(a + 128), u2 = lds128(a + 256);
                const float p0 = sc[t * 4 + g];
                fma8(acc, u0, p0); fma8(acc + 8, u1, p0); fma8(acc + 16, u2, p0);
                __syncwarp();
                if (lane == 0) mbar_arrive(bar_empty + 8 * slot);
                if (t == NKT / 2) {
                    const uint4* q = p.sc->mbuf + head * 32 + lane;
                    uint64_t lo, hi;
                    uint32_t n = 0;
                    bool ok;
#pragma unroll 1
                    do {
                        pkt_ld(q, lo, hi);
                        ok = __all_sync(0xffffffffu, tag_ok(hi, tag));
                        if (++n > SPIN_LIMIT) __trap();
                    } while (!ok);
                    const float ms = val_of(lo), ls = __uint_as_float((uint32_t)(lo >> 32));
                    const float M = warp_max(ms);
                    fscale = ex2((m_w - M) * L2E) * __frcp_rn(warp_sum(ex2((ms - M) * L2E) * ls));
                }
                if (t == NKT - 4) {
                    mbar_wait(bar_topo, 0);
                    const uint32_t msel = s_sel[b >> 5] >> (b & 31) & 1;
                    const int r = (lane & 7) + ((lane >> 4) << 3), mi = (lane >> 3) & 1;
#pragma unroll
                    for (int i = 0; i < 5; i++) {
                        const int j = warp * 5 + i;
                        const int cb = j >> 2, half = cb >= 5;
                        const int unit = r * 5 + cb - 5 * half;
                        aoff[i] = sbase + SM_W2 + half * PIECE + unit * 128 + ((((j & 3) * 2 + mi) ^ (unit & 7)) << 4);
                        const int ch = warp * 10 + 2 * i + (lane & 1);
                        dst[i] = p.xa + xa_off(L_D + ch * 4096, s_sel[ch >> 5] >> (ch & 31) & 1) + b * 32 + (lane >> 2) * 4;
                        pin(aoff[i]); pin(dst[i]);
                    }
#pragma unroll
                    for (int i = 0; i < NG; i++) { goff[i] = xa_off(L_GATHER + (b >> 1) % CFG_HCOPY * HCOPY_BYTES + (i * D_MODEL + hcol) * 2, msel); pin(goff[i]); }
                    gdst = p.xa + xa_off(L_GATHER + warp % CFG_HCOPY * HCOPY_BYTES + (min(kg, NG - 1) * D_MODEL + ng * 32 + (lane & 15) * 2) * 2, lane >> 4);
                    odst = xa_off(L_O + ((head * 4 + sp) * DH + (tid % 48) * 4) * 2, tid / 48 & 1);
                    const int dim = min(kg, NG - 1) * 1024 + tid * 4, oh = dim / DH;
#pragma unroll
                    for (int i = 0; i < 4; i++) { osrc[i] = xa_off(L_O + ((oh * 4 + i) * DH + dim - oh * DH) * 2, msel); pin(osrc[i]); }
                    pin(odst);
                    pin(gdst);
                }
            }
            if (tid == 0) LST(ph ? 91 : 90);
            {
                const bool hi16 = lane & 16, hi8 = lane & 8;
                float r12[12], r6[6];
#pragma unroll
                for (int i = 0; i < 12; i++) {
                    const float send = hi16 ? acc[i] : acc[i + 12];
                    const float keep = hi16 ? acc[i + 12] : acc[i];
                    r12[i] = keep + __shfl_xor_sync(0xffffffffu, send, 16);
                }
#pragma unroll
                for (int i = 0; i < 6; i++) {
                    const float send = hi8 ? r12[i] : r12[i + 6];
                    const float keep = hi8 ? r12[i + 6] : r12[i];
                    r6[i] = (keep + __shfl_xor_sync(0xffffffffu, send, 8)) * fscale;
                }
                const int f0 = (hi16 ? 12 : 0) + (hi8 ? 6 : 0);
#pragma unroll
                for (int i = 0; i < 6; i++) {
                    const int f = f0 + i;
                    s_red[warp * DH + (f >> 3) * 64 + c * 8 + (f & 7)] = r6[i];
                }
            }
            cons_sync();
            if (ph == 0) {
                if (tid < DH) {
                    const float* r = s_red + tid;
                    ll_st1(p.sc->qbuf + (head * 4 + sp) * DH + tid,
                           ((r[0] + r[DH]) + (r[2 * DH] + r[3 * DH])) + ((r[4 * DH] + r[5 * DH]) + (r[6 * DH] + r[7 * DH])), tag);
                    const uint64_t* src = p.sc->qbuf + head * 4 * DH + tid;
                    uint64_t u0, u1, u2, u3;
                    uint32_t n = 0;
                    bool ok;
                    __nanosleep(CFG_QDELAY);
#pragma unroll 1
                    do {
                        if (n) __nanosleep(CFG_QSLEEP);
                        u0 = ll_ld1(src); u1 = ll_ld1(src + DH); u2 = ll_ld1(src + 2 * DH); u3 = ll_ld1(src + 3 * DH);
                        ok = __all_sync(0xffffffffu, tag_ok(u0, tag) && tag_ok(u1, tag) && tag_ok(u2, tag) && tag_ok(u3, tag));
                        if (++n > SPIN_LIMIT) __trap();
                    } while (!ok);
                    s_q[tid] = bfr((val_of(u0) + val_of(u1)) + (val_of(u2) + val_of(u3)));
                }
            } else {
                if (tid < 96) {
                    const float4* r = reinterpret_cast<const float4*>(s_red) + tid % 48;
                    const float4 r0 = r[0], r1 = r[48], r2 = r[96], r3 = r[144], r4 = r[192], r5 = r[240], r6 = r[288], r7 = r[336];
#define S_(c) (((r0.c + r1.c) + (r2.c + r3.c)) + ((r4.c + r5.c) + (r6.c + r7.c)))
                    in_st2(p.xa + odst, pack_bf(S_(y), S_(x)), pack_bf(S_(w), S_(z)));
#undef S_
                }
                if (b < NWO) {
                    uint2 u[4];
#pragma unroll
                    for (int i = 0; i < 4; i++) u[i] = make_uint2(0, 0);
                    uint32_t n = 0, pend = 0xf;
                    mbar_wait(bar_tail + 8 * CFG_OGATE, 0);
#pragma unroll 1
                    do {
                        if (n) __nanosleep(CFG_OSLEEP);
#pragma unroll
                        for (int i = 0; i < 4; i++) in_ld2p(p.xa + osrc[i], u[i], pend >> i & 1);
#pragma unroll
                        for (int i = 0; i < 4; i++) if (in_ok(u[i])) pend &= ~(1u << i);
                        if (++n > SPIN_LIMIT) __trap();
                    } while (__any_sync(0xffffffffu, pend != 0));
#define F_(f, c) ((f(u[0].c) + f(u[1].c)) + (f(u[2].c) + f(u[3].c)))
                    sts64(sbase + SM_OB + tid * 8, pack_bf(F_(bf_hi, x), F_(bf_lo, x)), pack_bf(F_(bf_hi, y), F_(bf_lo, y)));
#undef F_
                }
            }
            cons_sync();

            if (tid == 0) LST(ph ? 93 : 92);
        }
        const int t = t4;
        if (b < NWO) {
            float cw[4][4], cx[4][4];
#pragma unroll
            for (int i = 0; i < 4; i++) { cw[i][0] = cw[i][1] = cw[i][2] = cw[i][3] = 0.f; cx[i][0] = cx[i][1] = cx[i][2] = cx[i][3] = 0.f; }
            uint32_t av[NWP][2];
#pragma unroll
            for (int j = 0; j < NWP; j++) { av[j][0] = lds32(oa + j * 256); av[j][1] = lds32(oa + j * 256 + 16); }
#pragma unroll
            for (int j = 0; j < NWP; j++) {
                const uint32_t a[4] = {av[j][0], av[j][0], av[j][1], av[j][1]};
                mbar_wait(bar_tail + 8 * j, 0);
                uint32_t w01[4], w23[4];
                ldsm_x4_t(w01, wa + j * WPIECE); ldsm_x4_t(w23, wa2 + j * WPIECE);
                float (*c)[4] = (j & 1) ? cx : cw;
                mma_bf16(c[0], a, w01[0], w01[1]); mma_bf16(c[1], a, w01[2], w01[3]);
                mma_bf16(c[2], a, w23[0], w23[1]); mma_bf16(c[3], a, w23[2], w23[3]);
            }
            if (lane < 4) {
#pragma unroll
                for (int i = 0; i < 4; i++) sts64(pw + i * 32, __float_as_uint(cw[i][0] + cx[i][0]), __float_as_uint(cw[i][1] + cx[i][1]));
            }
            cons_sync();
            if (warp < CFG_HCOPY) {
                float2 r[8];
#pragma unroll
                for (int i = 0; i < 8; i++) r[i] = lds64f(pr + i * 128);
#define S_(c) (((r[0].c + r[1].c) + (r[2].c + r[3].c)) + ((r[4].c + r[5].c) + (r[6].c + r[7].c)))
                in_st1(gdst, __uint_as_float(pack_bf(S_(y), S_(x))));
#undef S_
            }
            if (tid == 0) LST(94);
        }
        if (b < NFFN) {
            uint32_t a1[NUP][4], a3[NUP][4];
            auto load_w13 = [&](int i, uint32_t bar) {
                mbar_wait(bar + 8 * (NWP + i), 0);
                ldsm_x4_t(a1[i], w13a + i * WPIECE); ldsm_x4_t(a3[i], w13a + i * WPIECE + WPIECE / 2);
            };
            uint32_t hp0, hp1;
            {
                const unsigned char* gsrc[NG];
                uint2 u[NG];
#pragma unroll
                for (int i = 0; i < NG; i++) { u[i] = make_uint2(0, 0); gsrc[i] = p.xa + goff[i]; }
#pragma unroll
                for (int i = 0; i < CFG_HGATE; i++) load_w13(i, bar_tail);
                LSC(0);
#pragma unroll
                for (int i = 0; i < NG; i++) in_ld2p(gsrc[i], u[i], lane < 4 * NUP && !ABL_NOH);
                load_w13(CFG_HGATE, bar_tail);
                LSCD(1, u[0].x ^ u[1].x ^ u[2].x ^ u[3].x ^ u[4].x ^ u[5].x);
                uint32_t n = 0;
#pragma unroll 1
                while (__any_sync(0xffffffffu, max(max(max(u[0].x, u[0].y), max(u[1].x, u[1].y)), max(max(max(u[2].x, u[2].y), max(u[3].x, u[3].y)),
                                                                                                    max(max(u[4].x, u[4].y), max(u[5].x, u[5].y)))) == SENT)) {
#pragma unroll
                    for (int i = 0; i < NG; i++) in_ld2p(gsrc[i], u[i], !in_ok(u[i]));
                    if (++n > SPIN_LIMIT) __trap();
                }
                if (tid == 96) LST(100);
                LSC(2);
#define F_(f, c) (f(xres.c) + bfr(((f(u[0].c) + f(u[1].c)) + (f(u[2].c) + f(u[3].c))) + (f(u[4].c) + f(u[5].c))))
                hp0 = pack_bf(F_(bf_hi, x), F_(bf_lo, x));
                hp1 = pack_bf(F_(bf_hi, y), F_(bf_lo, y));
#undef F_
            }
            auto ln_stats = [&]() {
                const float4 pa = lds128f(sbase + SM_MISC), pb = lds128f(sbase + SM_MISC + 16), pc = lds128f(sbase + SM_MISC + 32), pd = lds128f(sbase + SM_MISC + 48);
                ln_finish(((pa.y + pa.w) + (pb.y + pb.w)) + ((pc.y + pc.w) + (pd.y + pd.w)),
                          ((pa.x + pa.z) + (pb.x + pb.z)) + ((pc.x + pc.z) + (pd.x + pd.z)), mean_b, inv_den);
            };
            {
                uint32_t b0[NUP], b1[NUP];
                float cg[4], cu[4], cs[2][4];
#pragma unroll
                for (int e = 0; e < 4; e++) cg[e] = cu[e] = cs[0][e] = cs[1][e] = 0.f;
#pragma unroll
                for (int i = 0; i < NUP; i++) {
                    const uint32_t h0 = __shfl_sync(0xffffffffu, hp0, i * 4 + t), h1 = __shfl_sync(0xffffffffu, hp1, i * 4 + t);
                    b0[i] = (lane & 4) ? 0x3f803f80u : h0;
                    b1[i] = (lane & 4) ? 0x3f803f80u : h1;
                    const uint32_t sa[4] = {h0, h0, h1, h1};
                    mma_bf16(cs[i & 1], sa, b0[i], b1[i]);
                }
#pragma unroll
                for (int i = 0; i <= CFG_HGATE; i++) { mma_bf16(cg, a1[i], b0[i], b1[i]); mma_bf16(cu, a3[i], b0[i], b1[i]); }
                if (lane < 4 * NUP) sts64(hdst, hp0, hp1);
                if (lane == 0) sts64(stat, __float_as_uint(cs[0][0] + cs[1][0]), __float_as_uint(cs[0][1] + cs[1][1]));
                __syncwarp();
                if (lane == 0) mbar_arrive(bar_h);
                LSC(3);
#pragma unroll
                for (int i = CFG_HGATE + 1; i < NUP - 1; i++) { load_w13(i, bar_tail); mma_bf16(cg, a1[i], b0[i], b1[i]); mma_bf16(cu, a3[i], b0[i], b1[i]); }
                LSC(4);
                mbar_wait(bar_h, 0);
                ln_stats();
                LSC(5);
                load_w13(NUP - 1, after(bar_tail, __float_as_uint(CFG_DEP4), p.zero));
                LSC(6);
                mma_bf16(cg, a1[NUP - 1], b0[NUP - 1], b1[NUP - 1]); mma_bf16(cu, a3[NUP - 1], b0[NUP - 1], b1[NUP - 1]);
#define SEL_(e) ((t & 2) ? ((t & 1) ? cu[e + 2] : cu[e]) : ((t & 1) ? cg[e + 2] : cg[e]))
                sts64(red_dst, __float_as_uint(SEL_(0)), __float_as_uint(SEL_(1)));
#undef SEL_
            }
            LSC(7);
            cons_sync();
            uint32_t b0, b1, dep2;
            {
                float2 r[8];
#pragma unroll
                for (int i = 0; i < 8; i++) r[i] = lds64f(red_src + i * 256);
                const float raw = ((r[0].x + r[1].x) + (r[2].x + r[3].x)) + ((r[4].x + r[5].x) + (r[6].x + r[7].x));
                const float csum = ((r[0].y + r[1].y) + (r[2].y + r[3].y)) + ((r[4].y + r[5].y) + (r[6].y + r[7].y));
                const float tot = bfr(fmaf(-mean_b, csum, raw) * inv_den);
                LSCD(8, __float_as_uint(tot));
                const float up = __shfl_down_sync(0xffffffffu, tot, 16);
                const float act = bfr(__fdividef(tot, 1.0f + ex2(-tot * L2E)));
                const uint32_t hv1 = __float_as_uint(bfr(act * up));
                const uint32_t e0 = __shfl_sync(0xffffffffu, hv1, 2 * t), e1 = __shfl_sync(0xffffffffu, hv1, 2 * t + 1);
                const uint32_t e2 = __shfl_sync(0xffffffffu, hv1, 2 * t + 8), e3 = __shfl_sync(0xffffffffu, hv1, 2 * t + 9);
                dep2 = hv1;
                b0 = __byte_perm(e0, e1, 0x7632);
                b1 = __byte_perm(e2, e3, 0x7632);
            }
            LSCD(9, b0);
            uint32_t a[5][4];
            mbar_wait(after(bar_w2, CFG_DEPW2, p.zero), 0);
#pragma unroll
            for (int i = 0; i < 5; i++) ldsm_x4_t(a[i], aoff[i]);
            LSC(10);
            float cw[5][4];
#pragma unroll
            for (int i = 0; i < 5; i++) { cw[i][0] = cw[i][1] = cw[i][2] = cw[i][3] = 0.f; mma_bf16(cw[i], a[i], b0, b1); }
            if ((lane & 2) == 0) {
#pragma unroll
                for (int i = 0; i < 5; i++) in_st1(dst[i], (lane & 1) ? cw[i][2] : cw[i][0]);
            }
            __syncwarp();
            if (lane == 0) mbar_arrive(bar_red);
            LSC(11);
            if (lane == 0) LST(110 + warp);
        }
    }
}

typedef CUresult (*EncodeTiledFn)(CUtensorMap*, CUtensorMapDataType, cuuint32_t, void*, const cuuint64_t*, const cuuint64_t*,
                                  const cuuint32_t*, const cuuint32_t*, CUtensorMapInterleave, CUtensorMapSwizzle,
                                  CUtensorMapL2promotion, CUtensorMapFloatOOBfill);

void make_map(EncodeTiledFn fn, CUtensorMap* tm, const void* w, const int (&d)[5], const int (&st)[4], const int (&bx)[5],
              CUtensorMapSwizzle sw, int promo) {
    cuuint64_t dims[5], strides[4];
    cuuint32_t box[5], estr[5];
    for (int i = 0; i < 5; i++) { dims[i] = (cuuint64_t)d[i]; box[i] = (cuuint32_t)bx[i]; estr[i] = 1; }
    for (int i = 0; i < 4; i++) strides[i] = (cuuint64_t)st[i];
    fn(tm, CU_TENSOR_MAP_DATA_TYPE_BFLOAT16, 5, const_cast<void*>(w), dims, strides, box, estr, CU_TENSOR_MAP_INTERLEAVE_NONE, sw,
       (CUtensorMapL2promotion)promo, CU_TENSOR_MAP_FLOAT_OOB_FILL_NONE);
}

}

extern "C" void kernel_launch(void* const* d_in, const int* in_sizes, int n_in, void* d_out, int out_size) {
    (void)in_sizes; (void)n_in; (void)out_size;
    static EncodeTiledFn encode = nullptr;
    static Scratch* scratch = nullptr;
    static unsigned char* xarea = nullptr;
    static double tscale = 1.0;
    if (!encode) {
        void* sp = nullptr;
        cudaGetSymbolAddress(&sp, g_scratch);
        scratch = reinterpret_cast<Scratch*>(sp);
        cudaGetSymbolAddress(&sp, g_xarea);
        xarea = reinterpret_cast<unsigned char*>((reinterpret_cast<uintptr_t>(sp) + XA_ALIGN - 1) / XA_ALIGN * XA_ALIGN);
        void* fn = nullptr;
        cudaDriverEntryPointQueryResult st;
        cudaGetDriverEntryPoint("cuTensorMapEncodeTiled", &fn, cudaEnableDefault, &st);
        encode = reinterpret_cast<EncodeTiledFn>(fn);
        int dev = 0, khz = 0, bits = 0;
        cudaGetDevice(&dev);
        cudaDeviceGetAttribute(&khz, cudaDevAttrMemoryClockRate, dev);
        cudaDeviceGetAttribute(&bits, cudaDevAttrGlobalMemoryBusWidth, dev);
        if (khz > 0 && bits > 0) tscale = (2619000.0 * 5120.0) / ((double)khz * bits);
        cudaFuncSetAttribute(fused_decode_kernel, cudaFuncAttributeMaxDynamicSharedMemorySize, SM_TOTAL);
    }
    KParams p;
    p.x = (const __nv_bfloat16*)d_in[0];
    p.k = (const __nv_bfloat16*)d_in[1];
    p.v = (const __nv_bfloat16*)d_in[2];
    p.wq = (const __nv_bfloat16*)d_in[3];
    p.out = (__nv_bfloat16*)d_out;
    p.sc = scratch;
    p.xa = xarea;
    p.zero = 0;
    p.t_first = (uint32_t)(4 * CFG_OFF0 * tscale);
    p.t_step = (uint32_t)(CFG_T * tscale);
    p.t_smax = (uint32_t)(CFG_SMAX * tscale);
    p.t_lat = (uint32_t)(4 * (450 + (CFG_LAT - 450) * tscale));
    TMaps tm;
    constexpr int R1 = FF * 2, R2 = D_MODEL * 2;
    make_map(encode, &tm.wo, d_in[4], {D_MODEL, NHEAD * DH, 1, 1, 1}, {R2, R2, R2, R2}, {32, 128, 1, 1, 1}, CU_TENSOR_MAP_SWIZZLE_64B, CFG_PROMO_WO);
    make_map(encode, &tm.w1, d_in[6], {FF, 2, 20, 2, 8}, {R1, 4 * R1, 2 * R1, 80 * R1}, {16, 2, 4, 2, 8}, CU_TENSOR_MAP_SWIZZLE_32B, CFG_PROMO_W13);
    make_map(encode, &tm.w3, d_in[7], {FF, 2, 20, 2, 8}, {R1, 4 * R1, 2 * R1, 80 * R1}, {16, 2, 4, 2, 8}, CU_TENSOR_MAP_SWIZZLE_32B, CFG_PROMO_W13);
    make_map(encode, &tm.w2, d_in[8], {64, 10, FF, 1, 1}, {128, R2, R2, R2}, {64, 5, 16, 1, 1}, CU_TENSOR_MAP_SWIZZLE_128B, CFG_PROMO_W2);
    fused_decode_kernel<<<NCTA, NTHREADS, SM_TOTAL, cudaStreamPerThread>>>(p, tm);
}
```

```cpp
#include <cuda_runtime.h>
#include <cuda_bf16.h>
#include <cuda.h>
#include <stdint.h>

namespace {

constexpr int D_MODEL = 640;
constexpr int NHEAD = 32;
constexpr int DH = 192;
constexpr int SK = 32768;
constexpr int WIN = 4096;
constexpr int FF = 1536;

constexpr int NCTA = 128;
constexpr int NCONS = 256;
constexpr int NTHREADS = NCONS + 96;
constexpr int ROW_BYTES = DH * 2;
constexpr int TILE_BYTES = 32 * ROW_BYTES;
constexpr int NSLOT = 16;
constexpr int NKT = 32;
constexpr int NQT = 5;
constexpr int QSLOT = NSLOT - NQT;
constexpr int NWO = 60;
constexpr int NG = 6;
constexpr int NFFN = 48;
constexpr int NRED = 40;
constexpr int NWP = 8;
constexpr int NUP = 5;
constexpr int WPIECE = 16384;
constexpr int PIECE = 10240;
constexpr int NTAIL = 9;
constexpr int N_TAIL0 = 2 * NKT;

#define CFG_NPROBE 4
#define CFG_REDSLEEP 300
#define CFG_GATHER_AT 40
#define CFG_OGATE 2
#define CFG_OSLEEP 100
#define CFG_PROMO_WO 2
#define CFG_PROMO_W13 2
#define CFG_PROMO_W2 2
#define CFG_PROBE_AT 4
#define CFG_QDELAY 1500
#define CFG_QSLEEP 400
#define CFG_BOUNDED_MBAR 0
#define CFG_T 1908
#define CFG_OFF0 2000
#define CFG_TWO 305
#define CFG_TFF 244
#define CFG_TW2 305
#define CFG_HGATE 1
#define CFG_DEP4 mean_b
#define CFG_DEPW2 dep2
#define ABL_NOH 0
#define ABL_NOD 0
#define CFG_HCOPY 2
#define CFG_MA 16
#define CFG_MB 42
#define CFG_ADAPT 58
#define CFG_LAT 1440
#define CFG_SMAX 1964
#define CFG_PSLEEP 1000
#define CFG_PMIN 112
#define CFG_NRW 1
#define CFG_DSTAG 200
#define CFG_DDELAY 0
#define CFG_HSHADOW 0
#define CFG_T4 122
#define CFG_T5 122
#define CFG_T6 305
#define CFG_T7 152
#define CFG_HPOST 1
constexpr int HPRE = CFG_HGATE + CFG_HSHADOW + CFG_HPOST;
#define CFG_KEEP 150
#define CFG_KEEP_AT 7
#define CFG_KEEPWO 1
#define CFG_GAPWO 0
#define CFG_GAPFF 60
#define CFG_CAP 8

constexpr int SM_RING = 0;
constexpr int SM_W2 = NUP * WPIECE;
constexpr int SM_SC = SM_RING + NSLOT * TILE_BYTES;
constexpr int SM_RED = SM_SC + 8 * 128 * 4;
constexpr int SM_Q = SM_RED + 8 * DH * 4;
constexpr int SM_OB = SM_Q + DH * 4;
constexpr int SM_HN = SM_OB + 1024 * 2;
constexpr int SM_MISC = SM_HN + D_MODEL * 2;
constexpr int SM_BAR = SM_MISC + 128;
constexpr int SM_TOTAL = SM_BAR + 512;
static_assert(SM_TOTAL <= 232448, "shared memory");

struct __align__(128) Scratch {
    uint64_t qbuf[NHEAD * 4 * DH];
    uint4 mbuf[NHEAD * 32];
    uint64_t sel[NCTA];
    uint32_t epoch;
    uint32_t pad[31];
    unsigned long long pace[2];
};
__device__ Scratch g_scratch;
constexpr int XA_ALIGN = 1 << 20;
constexpr uint32_t SENT = 0xffffffffu;
constexpr int L_GATHER = 0;
constexpr int HCOPY_BYTES = NG * D_MODEL * 2;
constexpr int L_PROBE = 8 * 4096;
constexpr int L_O = 9 * 4096;
constexpr int L_D = 30 * 4096;
static_assert(2 * (L_D + NRED * 4096) <= XA_ALIGN, "");
__device__ unsigned char g_xarea[2 * XA_ALIGN];
__device__ __forceinline__ uint32_t xa_off(uint32_t l, uint32_t side) {
    const uint32_t k = l >> 12;
    return (2 * k + ((side ^ k ^ (k >> 3) ^ (k >> 4) ^ (k >> 6)) & 1)) * 4096 + (l & 4095);
}

#define LST(i) do { } while (0)
#define LSC(i) do { } while (0)
#define LSCD(i, v) do { } while (0)
constexpr uint32_t SPIN_LIMIT = 1u << 24;

__device__ __forceinline__ uint32_t now_q() { uint32_t t; asm volatile("mov.u32 %0, %globaltimer_lo;" : "=r"(t)); return t * 4; }
__device__ __forceinline__ void wait_until(uint32_t due) {
    for (int n = 0; n < 4096 && (int)(now_q() - due) < 0; n++) { }
}
__device__ __forceinline__ void sleep_until(uint32_t due) {
    for (int n = 0; n < 4096 && (int)(now_q() - due) < 0; n++) __nanosleep(200);
}
__device__ __forceinline__ uint32_t smem_u32(const void* p) { return (uint32_t)__cvta_generic_to_shared(p); }
__device__ __forceinline__ void mbar_init(uint32_t bar, uint32_t cnt) {
    asm volatile("mbarrier.init.shared::cta.b64 [%0], %1;" ::"r"(bar), "r"(cnt) : "memory");
}
__device__ __forceinline__ void mbar_expect_tx(uint32_t bar, uint32_t bytes) {
    asm volatile("mbarrier.arrive.expect_tx.shared::cta.b64 _, [%0], %1;" ::"r"(bar), "r"(bytes) : "memory");
}
__device__ __forceinline__ void mbar_arrive(uint32_t bar) {
    asm volatile("mbarrier.arrive.shared::cta.b64 _, [%0];" ::"r"(bar) : "memory");
}
__device__ __forceinline__ bool mbar_test(uint32_t bar, uint32_t parity) {
    uint32_t ok;
    asm volatile("{\n.reg .pred p;\nmbarrier.test_wait.parity.shared::cta.b64 p, [%1], %2;\nselp.u32 %0, 1, 0, p;\n}"
                 : "=r"(ok) : "r"(bar), "r"(parity) : "memory");
    return ok;
}
__device__ __forceinline__ void mbar_wait(uint32_t bar, uint32_t parity) {
    asm volatile("{\n.reg .pred p;\nW_%=:\nmbarrier.try_wait.parity.shared::cta.b64 p, [%0], %1;\n@!p bra W_%=;\n}" ::"r"(bar), "r"(parity) : "memory");
}
__device__ __forceinline__ void bulk_load(uint32_t dst, const void* src, uint32_t bytes, uint32_t bar, uint64_t pol) {
    asm volatile("cp.async.bulk.shared::cluster.global.mbarrier::complete_tx::bytes.L2::cache_hint [%0], [%1], %2, [%3], %4;"
                 ::"r"(dst), "l"(src), "r"(bytes), "r"(bar), "l"(pol) : "memory");
}
__device__ __forceinline__ void tma_5d(uint32_t dst, const CUtensorMap* tm, int c0, int c1, int c2, int c4, uint32_t bar) {
    asm volatile("cp.async.bulk.tensor.5d.shared::cluster.global.mbarrier::complete_tx::bytes [%0], [%1, {%3, %4, %5, %7, %6}], [%2];"
                 ::"r"(dst), "l"(reinterpret_cast<uint64_t>(tm)), "r"(bar), "r"(c0), "r"(c1), "r"(c2), "r"(c4), "r"(0) : "memory");
}
__device__ __forceinline__ void pin(uint32_t& v) { asm volatile("" : "+r"(v)); }
__device__ __forceinline__ uint32_t after(uint32_t bar, uint32_t v, uint32_t zero) { return bar | (v & zero); }
__device__ __forceinline__ void pinf(float& v) { asm volatile("" : "+f"(v)); }
template <class T> __device__ __forceinline__ void pin(T*& v) { asm volatile("" : "+l"(v)); }
__device__ __forceinline__ void sts32(uint32_t a, float v) { asm volatile("st.shared.f32 [%0], %1;" ::"r"(a), "f"(v) : "memory"); }
__device__ __forceinline__ void sts64(uint32_t a, uint32_t x, uint32_t y) { asm volatile("st.shared.v2.u32 [%0], {%1, %2};" ::"r"(a), "r"(x), "r"(y) : "memory"); }
__device__ __forceinline__ void cons_sync() { asm volatile("bar.sync 1, 256;" ::: "memory"); }

__device__ __forceinline__ uint4 lds128(uint32_t a) {
    uint4 v;
    asm volatile("ld.shared.v4.u32 {%0,%1,%2,%3}, [%4];" : "=r"(v.x), "=r"(v.y), "=r"(v.z), "=r"(v.w) : "r"(a));
    return v;
}
__device__ __forceinline__ float4 lds128f(uint32_t a) {
    float4 v;
    asm volatile("ld.shared.v4.f32 {%0,%1,%2,%3}, [%4];" : "=f"(v.x), "=f"(v.y), "=f"(v.z), "=f"(v.w) : "r"(a) : "memory");
    return v;
}
__device__ __forceinline__ float2 lds64f(uint32_t a) {
    float2 v;
    asm volatile("ld.shared.v2.f32 {%0,%1}, [%2];" : "=f"(v.x), "=f"(v.y) : "r"(a) : "memory");
    return v;
}
__device__ __forceinline__ float lds32f(uint32_t a) {
    float v;
    asm volatile("ld.shared.f32 %0, [%1];" : "=f"(v) : "r"(a) : "memory");
    return v;
}
__device__ __forceinline__ uint32_t lds32(uint32_t a) {
    uint32_t v;
    asm volatile("ld.shared.u32 %0, [%1];" : "=r"(v) : "r"(a));
    return v;
}
__device__ __forceinline__ void ldsm_x2_t(uint32_t* r, uint32_t a) {
    asm volatile("ldmatrix.sync.aligned.m8n8.x2.trans.shared.b16 {%0,%1}, [%2];" : "=r"(r[0]), "=r"(r[1]) : "r"(a));
}
__device__ __forceinline__ void ldsm_x4_t(uint32_t* r, uint32_t a) {
    asm volatile("ldmatrix.sync.aligned.m8n8.x4.trans.shared.b16 {%0,%1,%2,%3}, [%4];"
                 : "=r"(r[0]), "=r"(r[1]), "=r"(r[2]), "=r"(r[3]) : "r"(a));
}
__device__ __forceinline__ void mma_bf16(float* c, const uint32_t* a, uint32_t b0, uint32_t b1) {
    asm volatile("mma.sync.aligned.m16n8k16.row.col.f32.bf16.bf16.f32 {%0,%1,%2,%3}, {%4,%5,%6,%7}, {%8,%9}, {%0,%1,%2,%3};"
                 : "+f"(c[0]), "+f"(c[1]), "+f"(c[2]), "+f"(c[3]) : "r"(a[0]), "r"(a[1]), "r"(a[2]), "r"(a[3]), "r"(b0), "r"(b1));
}
__device__ __forceinline__ float bf_lo(uint32_t u) { return __uint_as_float(u << 16); }
__device__ __forceinline__ float bf_hi(uint32_t u) { return __uint_as_float(u & 0xffff0000u); }
__device__ __forceinline__ uint32_t pack_bf(float hi, float lo) { uint32_t r; asm("cvt.rn.bf16x2.f32 %0, %1, %2;" : "=r"(r) : "f"(hi), "f"(lo)); return r; }
__device__ __forceinline__ float bfr(float x) { return __uint_as_float(pack_bf(x, 0.f)); }

__device__ __forceinline__ uint64_t pk(float v, uint32_t tag) { return ((uint64_t)tag << 32) | (uint64_t)__float_as_uint(v); }
__device__ __forceinline__ void ll_st1(uint64_t* p, float a, uint32_t tag) {
    asm volatile("st.relaxed.gpu.global.b64 [%0], %1;" ::"l"(p), "l"(pk(a, tag)) : "memory");
}
__device__ __forceinline__ uint64_t ll_ld1(const uint64_t* p) {
    uint64_t v;
    asm volatile("ld.relaxed.gpu.global.b64 %0, [%1];" : "=l"(v) : "l"(p) : "memory");
    return v;
}
__device__ __forceinline__ uint32_t in_word(float v) {
    uint32_t r;
    asm("min.u32 %0, %1, 0xfffffffe;" : "=r"(r) : "r"(__float_as_uint(v)));
    return r;
}
__device__ __forceinline__ void in_st1(void* p, float v) {
    asm volatile("st.relaxed.gpu.global.u32 [%0], %1;" ::"l"(p), "r"(in_word(v)) : "memory");
}
__device__ __forceinline__ void in_st4(void* p, uint32_t a, uint32_t b, uint32_t c, uint32_t d) {
    asm volatile("st.relaxed.gpu.global.v4.u32 [%0], {%1, %2, %3, %4};" ::"l"(p), "r"(a), "r"(b), "r"(c), "r"(d) : "memory");
}
__device__ __forceinline__ uint32_t in_ld1(const void* p) {
    uint32_t v;
    asm volatile("ld.relaxed.gpu.global.u32 %0, [%1];" : "=r"(v) : "l"(p) : "memory");
    return v;
}
__device__ __forceinline__ uint4 in_ld4(const void* p) {
    uint4 v;
    asm volatile("ld.relaxed.gpu.global.v4.u32 {%0, %1, %2, %3}, [%4];" : "=r"(v.x), "=r"(v.y), "=r"(v.z), "=r"(v.w) : "l"(p) : "memory");
    return v;
}
__device__ __forceinline__ void in_st2(void* p, uint32_t a, uint32_t b) {
    asm volatile("st.relaxed.gpu.global.v2.u32 [%0], {%1, %2};" ::"l"(p), "r"(min(a, SENT - 1)), "r"(min(b, SENT - 1)) : "memory");
}
__device__ __forceinline__ void in_ld2p(const void* p, uint2& v, bool on) {
    asm volatile("{\n.reg .pred q;\nsetp.ne.u32 q, %3, 0;\n@q ld.relaxed.gpu.global.v2.u32 {%0, %1}, [%2];\n}"
                 : "+r"(v.x), "+r"(v.y) : "l"(p), "r"((uint32_t)on) : "memory");
}
__device__ __forceinline__ bool in_ok(const uint2& v) { return max(v.x, v.y) != SENT; }
__device__ __forceinline__ void in_ld4p(const void* p, uint4& v, bool on) {
    asm volatile("{\n.reg .pred q;\nsetp.ne.u32 q, %5, 0;\n@q ld.relaxed.gpu.global.v4.u32 {%0, %1, %2, %3}, [%4];\n}"
                 : "+r"(v.x), "+r"(v.y), "+r"(v.z), "+r"(v.w) : "l"(p), "r"((uint32_t)on) : "memory");
}
__device__ __forceinline__ bool in_ok(const uint4& v) { return max(max(v.x, v.y), max(v.z, v.w)) != SENT; }
__device__ __forceinline__ bool tag_ok(uint64_t v, uint32_t tag) { return (uint32_t)(v >> 32) == tag; }
__device__ __forceinline__ float val_of(uint64_t v) { return __uint_as_float((uint32_t)v); }
__device__ __forceinline__ void pkt_st(uint4* p, uint64_t lo, uint64_t hi) {
    asm volatile("{\n.reg .b128 t;\nmov.b128 t, {%1, %2};\nst.relaxed.gpu.global.b128 [%0], t;\n}" ::"l"(p), "l"(lo), "l"(hi) : "memory");
}
__device__ __forceinline__ void pkt_ld(const uint4* p, uint64_t& lo, uint64_t& hi) {
    asm volatile("{\n.reg .b128 t;\nld.relaxed.gpu.global.b128 t, [%2];\nmov.b128 {%0, %1}, t;\n}" : "=l"(lo), "=l"(hi) : "l"(p) : "memory");
}

__device__ __forceinline__ float warp_sum(float v) {
#pragma unroll
    for (int o = 16; o > 0; o >>= 1) v += __shfl_xor_sync(0xffffffffu, v, o);
    return v;
}
__device__ __forceinline__ float warp_max(float v) {
#pragma unroll
    for (int o = 16; o > 0; o >>= 1) v = fmaxf(v, __shfl_xor_sync(0xffffffffu, v, o));
    return v;
}
__device__ __forceinline__ void fma8(float* acc, const uint4& u, float w) {
    acc[0] = fmaf(w, bf_lo(u.x), acc[0]); acc[1] = fmaf(w, bf_hi(u.x), acc[1]);
    acc[2] = fmaf(w, bf_lo(u.y), acc[2]); acc[3] = fmaf(w, bf_hi(u.y), acc[3]);
    acc[4] = fmaf(w, bf_lo(u.z), acc[4]); acc[5] = fmaf(w, bf_hi(u.z), acc[5]);
    acc[6] = fmaf(w, bf_lo(u.w), acc[6]); acc[7] = fmaf(w, bf_hi(u.w), acc[7]);
}
__device__ __forceinline__ void dot8(float& s0, float& s1, const uint4& u, const float* q) {
    s0 = fmaf(q[0], bf_lo(u.x), s0); s1 = fmaf(q[1], bf_hi(u.x), s1);
    s0 = fmaf(q[2], bf_lo(u.y), s0); s1 = fmaf(q[3], bf_hi(u.y), s1);
    s0 = fmaf(q[4], bf_lo(u.z), s0); s1 = fmaf(q[5], bf_hi(u.z), s1);
    s0 = fmaf(q[6], bf_lo(u.w), s0); s1 = fmaf(q[7], bf_hi(u.w), s1);
}
__device__ __forceinline__ float sqrt_fast(float x) { float r; asm("sqrt.approx.ftz.f32 %0, %1;" : "=f"(r) : "f"(x)); return r; }
__device__ __forceinline__ float rcp_fast(float x) { float r; asm("rcp.approx.ftz.f32 %0, %1;" : "=f"(r) : "f"(x)); return r; }
__device__ __forceinline__ float ex2(float x) { float r; asm("ex2.approx.ftz.f32 %0, %1;" : "=f"(r) : "f"(x)); return r; }
constexpr float L2E = 1.4426950408889634f;
__device__ __forceinline__ void ln_finish(float s1, float s2, float& mean_b, float& inv_den) {
    const float mean = s1 * (1.0f / D_MODEL);
    const float var = fmaxf(fmaf(-mean, mean, s2 * (1.0f / D_MODEL)), 0.f);
    mean_b = bfr(mean);
    inv_den = rcp_fast(bfr(sqrt_fast(bfr(bfr(var) + 1e-5f))));
}
__device__ __forceinline__ float ln_apply(float v, float mean_b, float inv_den) { return bfr(bfr(v - mean_b) * inv_den); }

struct KParams {
    const __nv_bfloat16* wq;
    const __nv_bfloat16* k;
    uint32_t t_first;
    uint32_t t_step;
    const __nv_bfloat16* x;
    Scratch* sc;
    unsigned char* xa;
    const __nv_bfloat16* v;
    __nv_bfloat16* out;
    uint32_t t_smax;
    uint32_t t_lat;
    uint32_t zero;
};
struct TMaps { CUtensorMap wo, w1, w3, w2; };

__global__ void __launch_bounds__(NTHREADS, 1)
fused_decode_kernel(const KParams p, const __grid_constant__ TMaps tm) {
    extern __shared__ __align__(1024) unsigned char smem[];
    const uint32_t sbase = smem_u32(smem);
    const int tid = threadIdx.x;
    const int b = blockIdx.x;
    const int head = b >> 2, sp = b & 3;
    {
        if (tid < 240) {
            const int rg = tid / 24, ch = tid - rg * 24;
            const char* src = reinterpret_cast<const char*>(p.wq) + (size_t)(sp * 160 + rg) * (NHEAD * DH * 2) + head * ROW_BYTES + ch * 16;
            uint32_t dst = sbase + SM_RING + QSLOT * TILE_BYTES + tid * 16;
#pragma unroll 1
            for (int i = 0; i < 16; i++) {
                asm volatile("cp.async.cg.shared.global [%0], [%1], 16;" ::"r"(dst), "l"(src) : "memory");
                dst += 10 * ROW_BYTES;
                src += (size_t)10 * (NHEAD * DH * 2);
            }
        }
    }
    const int warp = __shfl_sync(0xffffffffu, tid >> 5, 0), lane = tid & 31;
    const int rr = b >> 1;
    const bool is_wo = !(b & 1) && rr < NWO, is_ffn = (b & 1) && rr < NFFN, is_red = (b & 1) && rr < NRED;
    const int kg = min(rr / 10, NG - 1), ng = rr % 10;
    const uint32_t bar_full = sbase + SM_BAR;
    const uint32_t bar_empty = sbase + SM_BAR + 128;
    const uint32_t bar_tail = sbase + SM_BAR + 256;
    const uint32_t bar_h = bar_tail + 8 * NTAIL;
    const uint32_t bar_topo = bar_h + 8;
    const uint32_t bar_red = bar_h + 16;
    const uint32_t bar_pace = bar_h + 24;
    volatile uint32_t* s_sel = reinterpret_cast<volatile uint32_t*>(smem + SM_MISC + 64);
    volatile uint32_t* s_pace = reinterpret_cast<volatile uint32_t*>(smem + SM_MISC + 96);
    volatile uint32_t* s_dummy = reinterpret_cast<volatile uint32_t*>(smem + SM_MISC + 112);

    if (warp == 8) {
        const uint32_t c_start = now_q();
        uint64_t pol_stream;
        asm volatile("createpolicy.fractional.L2::evict_first.b64 %0, 1.0;" : "=l"(pol_stream));
        const size_t kv_off = ((size_t)head * SK + (SK - WIN)) * ROW_BYTES + (size_t)sp * TILE_BYTES;
        const char* kp = reinterpret_cast<const char*>(p.k) + kv_off;
        if (lane == 0) {
#pragma unroll 1
            for (int i = 0; i < NSLOT; i++) { mbar_init(bar_full + 8 * i, 1); mbar_init(bar_empty + 8 * i, 8); }
#pragma unroll 1
            for (int i = 0; i < NTAIL + 4; i++) mbar_init(bar_tail + 8 * i, (i < NTAIL || (i - NTAIL) & 1) ? 1 : 8);
            asm volatile("fence.mbarrier_init.release.cluster;" ::: "memory");
        }
        __syncwarp();
        asm volatile("bar.arrive 2, 288;" ::: "memory");
        asm volatile("bar.arrive 3, 64;" ::: "memory");
        asm volatile("bar.arrive 4, 64;" ::: "memory");
        if (lane >= 1 && lane <= 4) asm volatile("prefetch.tensormap [%0];" ::"l"(reinterpret_cast<uint64_t>(&tm.wo + (lane - 1))) : "memory");
        if (lane == 0) {
            const char* vp = reinterpret_cast<const char*>(p.v) + kv_off;
            uint32_t due = c_start + p.t_first, step = p.t_step;
            const char* src = kp;
#pragma unroll 1
            for (int n = 0; n < N_TAIL0; n++) {
                const int slot = n & (NSLOT - 1);
                const int use = (n >> 4) + (slot >= QSLOT);
                if (n >= CFG_CAP) mbar_wait(bar_full + 8 * ((n - CFG_CAP) & (NSLOT - 1)), ((n - CFG_CAP) >> 4) & 1);
                if (use >= 1) mbar_wait(bar_empty + 8 * slot, (use - 1) & 1);
                if (n == CFG_ADAPT) { mbar_wait(bar_pace, 0); due = s_pace[0]; step = s_pace[1]; }
                const uint32_t full = bar_full + 8 * slot;
                mbar_expect_tx(full, TILE_BYTES);
                wait_until(due);
                LST(128 + n);
                bulk_load(sbase + SM_RING + slot * TILE_BYTES, src, TILE_BYTES, full, pol_stream);
                due += step;
                src = n == NKT - 1 ? vp : src + 4 * TILE_BYTES;
            }
            const uint32_t t_wo = step * (CFG_TWO * 4096 / 478) >> 12;
            due += 4 * CFG_GAPWO;
            if (is_wo) {
#pragma unroll 1
                for (int j = 0; j < NWP; j++) {
                    mbar_wait(bar_empty + 8 * (((j + 1) * WPIECE - 1) / TILE_BYTES), 1);
                    mbar_expect_tx(bar_tail + 8 * j, WPIECE);
                    wait_until(due);
                    LST(128 + N_TAIL0 + j);
                    tma_5d(sbase + j * WPIECE, &tm.wo, ng * 64, kg * 1024 + j * 128, 0, 0, bar_tail + 8 * j);
                    due += t_wo;
                }
            } else if (is_ffn) {
                due += NWP * t_wo + 4 * CFG_GAPFF;
                mbar_wait(bar_empty + 8 * ((SM_W2 + 4 * PIECE - 1) / TILE_BYTES), 1);
#pragma unroll
                for (int j = 0; j < NTAIL; j++) mbar_expect_tx(bar_tail + 8 * j, j < 4 ? WPIECE : j < 6 ? WPIECE / 2 : j == 6 ? 2 * PIECE : PIECE);
                sleep_until(due - 4 * 400);
                constexpr int gap[NTAIL] = {CFG_TFF, CFG_TFF, CFG_TFF, CFG_TFF, CFG_T4, CFG_T5, CFG_T6, CFG_T7, 0};
#pragma unroll
                for (int j = 0; j < NTAIL; j++) {
                    const uint32_t full = bar_tail + 8 * j;
                    const int i = min(j, NUP - 1);
                    wait_until(due);
                    if (j < 5) tma_5d(sbase + i * WPIECE, &tm.w1, rr * 32, 0, i * 4, 0, full);
                    if (j < 4 || j == 5) tma_5d(sbase + i * WPIECE + WPIECE / 2, &tm.w3, rr * 32, 0, i * 4, 0, full);
                    if (j == 6 || j == 7) tma_5d(sbase + SM_W2 + (j - 6) * 2 * PIECE, &tm.w2, 0, rr * 32 + (j - 6) * 16, 0, 0, full);
                    if (j == 6 || j == 8) tma_5d(sbase + SM_W2 + (j - 5) * PIECE, &tm.w2, 0, rr * 32 + (j - 6) * 8, 5, 0, full);
                    LST(128 + N_TAIL0 + 6 + j);
                    due += step * (gap[j] * 4096 / 478) >> 12;
                }
            }
        }
    } else if (warp == 10) {
        asm volatile("bar.sync 4, 64;" ::: "memory");
        if (lane == 0) {
            uint32_t epoch0;
            asm volatile("ld.relaxed.gpu.global.u32 %0, [%1];" : "=r"(epoch0) : "l"(&p.sc->epoch) : "memory");
            constexpr int MN = 8;
            const uint32_t t0 = now_q();
            uint32_t sa = 0, sb = 0;
#pragma unroll 1
            for (int n = 0; n < CFG_MB + MN; n++) {
                mbar_wait(bar_full + 8 * (n & (NSLOT - 1)), (n >> 4) & 1);
                const uint32_t t = now_q() - t0;
                LST(n);
                if ((uint32_t)(n - CFG_MA) < MN) sa += t;
                if (n >= CFG_MB) sb += t;
            }
            const uint32_t mb = t0 + sb / MN;
            unsigned long long* pace = p.sc->pace + ((epoch0 + 1) & 1);
            asm volatile("red.relaxed.gpu.global.add.u64 [%0], %1;" ::"l"(pace), "l"((unsigned long long)mb << 32 | min((sb - sa) / (4 * MN), 0xffffu) << 8 | 1) : "memory");
            if (b == 0) p.sc->pace[epoch0 & 1] = 0;
            unsigned long long v;
            uint32_t n = 0, cnt;
#pragma unroll 1
            do {
                __nanosleep(n ? 200 : CFG_PSLEEP);
                asm volatile("ld.relaxed.gpu.global.u64 %0, [%1];" : "=l"(v) : "l"(pace) : "memory");
                cnt = (uint32_t)v & 0xff;
                if (++n > SPIN_LIMIT) __trap();
            } while (cnt < CFG_PMIN);
            const float inv = rcp_fast((float)cnt);
            const uint32_t step = min(max((uint32_t)((float)((uint32_t)v >> 8) * inv * (4.0f / (CFG_MB - CFG_MA))), p.t_step), p.t_smax);
            s_pace[0] = mb + (int)((float)(int)((uint32_t)(v >> 32) - cnt * mb) * inv) + step * (2 * (CFG_ADAPT - CFG_MB) - (MN - 1)) / 2 - p.t_lat;
            s_pace[1] = step;
            mbar_arrive(bar_pace);
            LST(89);
        }
    } else if (warp == 9) {
        const uint32_t c_start = now_q();
        uint32_t epoch0;
        asm volatile("ld.relaxed.gpu.global.u32 %0, [%1];" : "=r"(epoch0) : "l"(&p.sc->epoch) : "memory");
        if (lane < 4) in_st4(p.xa + xa_off(L_PROBE + b * 32 + (lane & 1) * 16, lane >> 1), SENT, SENT, SENT, SENT);
        int vote = 0;
        uint32_t lat[2] = {0, 0};
        sleep_until(c_start + p.t_first + (CFG_PROBE_AT + 8) * p.t_step);
#pragma unroll 1
        for (int r = 0; r < CFG_NPROBE; r++) {
            uint32_t d[2];
#pragma unroll
            for (int i = 0; i < 2; i++) {
                const unsigned char* a = p.xa + xa_off(L_PROBE + (lane & 15) * 256, i);
                const uint32_t c0 = (uint32_t)clock();
                uint32_t v;
                asm volatile("ld.relaxed.gpu.global.u32 %0, [%1];" : "=r"(v) : "l"(a) : "memory");
                if (__any_sync(0xffffffffu, v == 0x7ff00123u)) s_dummy[0] = v;
                d[i] = (uint32_t)clock() - c0;
                lat[i] += min(d[i], 1500u);
            }
            vote += (d[1] < d[0]) - (d[0] < d[1]);
        }
        const uint32_t sel = vote ? vote > 0 : lat[1] < lat[0];
        const uint32_t tag = epoch0 + 1;
        {
            unsigned char* slot[9];
#pragma unroll
            for (int i = 0; i < 2; i++) slot[i] = p.xa + xa_off(L_O + (head * 4 + sp) * DH * 2 + min(lane, 23) * 16, i);
            slot[2] = p.xa + xa_off(L_GATHER + (lane >> 4) * HCOPY_BYTES + (kg * D_MODEL + ng * 64 + (lane & 7) * 8) * 2, lane >> 3 & 1);
#pragma unroll
            for (int i = 0; i < 6; i++) slot[3 + i] = p.xa + xa_off(L_D + min(rr, NRED - 1) * 4096 + i * 512 + lane * 16, sel);
            uint32_t acc = SENT;
#pragma unroll
            for (int i = 0; i < 9; i++) if (i < 2 ? lane < 24 : i == 2 ? lane < 16 * CFG_HCOPY && is_wo : is_red) in_st4(slot[i], SENT, SENT, SENT, SENT);
#pragma unroll
            for (int i = 0; i < 9; i++) if (i < 2 ? lane < 24 : i == 2 ? lane < 16 * CFG_HCOPY && is_wo : is_red) acc &= in_ld1(slot[i]);
            if (__any_sync(0xffffffffu, acc != SENT)) __trap();
        }
        asm volatile("bar.sync 3, 64;" ::: "memory");
        if (lane == 0) ll_st1(p.sc->sel + b, __uint_as_float(sel), tag);
        {
            uint32_t n = 0;
            sleep_until(c_start + p.t_first + (CFG_GATHER_AT + 8) * p.t_step);
            uint64_t e[4];
            bool ok;
            n = 0;
#pragma unroll 1
            do {
                if (n) __nanosleep(500);
#pragma unroll
                for (int i = 0; i < 4; i++) e[i] = ll_ld1(p.sc->sel + i * 32 + lane);
                ok = __all_sync(0xffffffffu, tag_ok(e[0], tag) && tag_ok(e[1], tag) && tag_ok(e[2], tag) && tag_ok(e[3], tag));
                if (++n > SPIN_LIMIT) __trap();
            } while (!ok);
#pragma unroll
            for (int i = 0; i < 4; i++) {
                const uint32_t m = __ballot_sync(0xffffffffu, (uint32_t)e[i] & 1);
                if (lane == 0) s_sel[i] = m;
            }
            __syncwarp();
            if (lane == 0) mbar_arrive(bar_topo);
        }
        if (CFG_KEEP && (is_ffn || (CFG_KEEPWO && is_wo))) {
            mbar_wait(bar_pace, 0);
            sleep_until(s_pace[0] + CFG_KEEP_AT * s_pace[1]);
            float c[4] = {0.f, 0.f, 0.f, 0.f};
            const uint32_t z[4] = {p.zero, p.zero, p.zero, p.zero};
            uint32_t n = 0;
#pragma unroll 1
            do {
                mma_bf16(c, z, p.zero, p.zero);
                __nanosleep(CFG_KEEP);
                n += 1 + __float_as_uint(c[0]);
            } while (!__all_sync(0xffffffffu, mbar_test(is_ffn ? bar_h : bar_tail + 8 * (NWP - 1), 0)) && n < SPIN_LIMIT);
        }
        if (is_red) {
            const unsigned char* src = p.xa + xa_off(L_D + rr * 4096, sel) + lane * 16;
            while (!mbar_test(bar_tail, 0)) __nanosleep(CFG_REDSLEEP);
            mbar_wait(bar_h, 0);
            if (b == 1 && lane == 0) p.sc->epoch = tag;
            const int col = rr * 16 + 4 * (lane & 3) + (lane >> 1 & 2) + (lane >> 3 & 1);
            float res = __bfloat162float(reinterpret_cast<const __nv_bfloat16*>(smem + SM_HN)[col]);
            __nv_bfloat16* dst = p.out + col;
            uint4 u[6];
#pragma unroll
            for (int i = 0; i < 6; i++) u[i] = make_uint4(SENT, SENT, SENT, SENT);
            uint32_t n = 0;
            auto missing = [&]() {
                uint32_t m[6];
#pragma unroll
                for (int i = 0; i < 6; i++) m[i] = max(max(u[i].x, u[i].y), max(u[i].z, u[i].w));
                return __any_sync(0xffffffffu, max(max(max(m[0], m[1]), m[2]), max(max(m[3], m[4]), m[5])) == SENT);
            };
            pin(src); pin(dst); pinf(res);
            mbar_wait(bar_red, 0);
#pragma unroll
            for (int i = 0; i < 6; i++) in_ld4p(src + i * 512, u[i], true);
#pragma unroll 1
            while (missing()) {
#pragma unroll
                for (int i = 0; i < 6; i++) in_ld4p(src + i * 512, u[i], !in_ok(u[i]));
                if (++n > SPIN_LIMIT) __trap();
            }
            float a[4];
#define F_(i, c) __uint_as_float(u[i].c)
            a[0] = ((F_(0, x) + F_(1, x)) + (F_(2, x) + F_(3, x))) + (F_(4, x) + F_(5, x));
            a[1] = ((F_(0, y) + F_(1, y)) + (F_(2, y) + F_(3, y))) + (F_(4, y) + F_(5, y));
            a[2] = ((F_(0, z) + F_(1, z)) + (F_(2, z) + F_(3, z))) + (F_(4, z) + F_(5, z));
            a[3] = ((F_(0, w) + F_(1, w)) + (F_(2, w) + F_(3, w))) + (F_(4, w) + F_(5, w));
#undef F_
            const bool h4 = lane & 4, h8 = lane & 8;
            const float e0 = (h4 ? a[2] : a[0]) + __shfl_xor_sync(0xffffffffu, h4 ? a[0] : a[2], 4);
            const float e1 = (h4 ? a[3] : a[1]) + __shfl_xor_sync(0xffffffffu, h4 ? a[1] : a[3], 4);
            float e = (h8 ? e1 : e0) + __shfl_xor_sync(0xffffffffu, h8 ? e0 : e1, 8);
            e += __shfl_xor_sync(0xffffffffu, e, 16);
            if (lane < 16) asm volatile("st.global.u16 [%0], %1;" ::"l"(dst), "h"((unsigned short)pack_bf(0.f, res + bfr(e))) : "memory");
            if (lane == 0) LST(96);
        }
    } else {
        float* s_red = reinterpret_cast<float*>(smem + SM_RED);
        float* s_q = reinterpret_cast<float*>(smem + SM_Q);
        float* sc = reinterpret_cast<float*>(smem + SM_SC) + warp * 128;
        const int g = lane >> 3, c = lane & 7;
        const int hcol = warp * 80 + min(lane, 4 * NUP - 1) * 4;
        uint32_t xr, epoch0;
        uint2 xu[5], xres;
        {
            const char* xb = reinterpret_cast<const char*>(p.x);
            asm volatile("ld.global.nc.u16 %0, [%1];" : "=r"(xr) : "l"(xb + (sp * 160 + min(lane >> 2, NQT - 1) * 32 + warp * 4 + (lane & 3)) * 2));
#pragma unroll
            for (int i = 0; i < 5; i++) asm volatile("ld.global.nc.v2.u32 {%0, %1}, [%2];" : "=r"(xu[i].x), "=r"(xu[i].y) : "l"(xb + i * 256 + lane * 8));
            asm volatile("ld.global.nc.v2.u32 {%0, %1}, [%2];" : "=r"(xres.x), "=r"(xres.y) : "l"(xb + hcol * 2));
            asm volatile("ld.relaxed.gpu.global.u32 %0, [%1];" : "=r"(epoch0) : "l"(&p.sc->epoch) : "memory");
        }
        if (tid < DH) ll_st1(p.sc->qbuf + (head * 4 + sp) * DH + tid, 0.f, 0);
        if (lane == 0) pkt_st(p.sc->mbuf + head * 32 + sp * 8 + warp, 0, 0);
        const uint32_t rowoff = sbase + SM_RING + (warp * 4 + g) * ROW_BYTES + c * 16;

        float mean_b, inv_den;
        uint32_t tag = 0;
        unsigned char* odst = p.xa + xa_off(L_O + ((head * 4 + sp) * DH + (tid % 48) * 4) * 2, tid / 48 & 1);
        pin(odst);

        {
            float s1 = 0.f, s2 = 0.f;
#pragma unroll
            for (int i = 0; i < 5; i++) {
                const float a0 = bf_lo(xu[i].x), a1 = bf_hi(xu[i].x), a2 = bf_lo(xu[i].y), a3 = bf_hi(xu[i].y);
                s1 += (a0 + a1) + (a2 + a3);
                s2 = fmaf(a0, a0, fmaf(a1, a1, fmaf(a2, a2, fmaf(a3, a3, s2))));
            }
#pragma unroll
            for (int o = 16; o > 0; o >>= 1) { s1 += __shfl_xor_sync(0xffffffffu, s1, o); s2 += __shfl_xor_sync(0xffffffffu, s2, o); }
            ln_finish(s1, s2, mean_b, inv_den);
            sc[lane] = ln_apply(bf_lo(xr), mean_b, inv_den);
            asm volatile("cp.async.wait_all;" ::: "memory");
            if (lane == 0) LST(80 + warp);
            asm volatile("bar.sync 2, 288;" ::: "memory");
            tag = epoch0 + 1;
        }

#pragma unroll 1
        for (int ph = 0; ph < 2; ph++) {
            float m_w = 0.f, fscale = 1.f;
            if (ph == 1) {
                float qv[24];
#pragma unroll
                for (int j = 0; j < 3; j++) {
                    const float4 a = *reinterpret_cast<const float4*>(s_q + j * 64 + c * 8);
                    const float4 bq = *reinterpret_cast<const float4*>(s_q + j * 64 + c * 8 + 4);
                    qv[j * 8 + 0] = a.x; qv[j * 8 + 1] = a.y; qv[j * 8 + 2] = a.z; qv[j * 8 + 3] = a.w;
                    qv[j * 8 + 4] = bq.x; qv[j * 8 + 5] = bq.y; qv[j * 8 + 6] = bq.z; qv[j * 8 + 7] = bq.w;
                }
                const float scale = 0.07216878364870322f;
#pragma unroll 1
                for (int t = 0; t < NKT; t++) {
                    const int slot = t & (NSLOT - 1);
                    mbar_wait(bar_full + 8 * slot, (t >> 4) & 1);
                    const uint32_t a = rowoff + slot * TILE_BYTES;
                    const uint4 u0 = lds128(a), u1 = lds128(a + 128), u2 = lds128(a + 256);
                    float s0 = 0.f, s1 = 0.f, s2 = 0.f, s3 = 0.f;
                    dot8(s0, s1, u0, qv); dot8(s2, s3, u1, qv + 8); dot8(s0, s1, u2, qv + 16);
                    s0 = (s0 + s1) + (s2 + s3);
#pragma unroll
                    for (int o = 1; o < 8; o <<= 1) s0 += __shfl_xor_sync(0xffffffffu, s0, o);
                    __syncwarp();
                    if (lane == 0) mbar_arrive(bar_empty + 8 * slot);
                    if (c == 0) sc[t * 4 + g] = bfr(bfr(s0) * scale);
                }
                __syncwarp();
                float4 sv = *reinterpret_cast<const float4*>(sc + lane * 4);
                m_w = warp_max(fmaxf(fmaxf(sv.x, sv.y), fmaxf(sv.z, sv.w)));
                sv.x = ex2((sv.x - m_w) * L2E); sv.y = ex2((sv.y - m_w) * L2E);
                sv.z = ex2((sv.z - m_w) * L2E); sv.w = ex2((sv.w - m_w) * L2E);
                const float l_w = warp_sum((sv.x + sv.y) + (sv.z + sv.w));
                if (lane == 0) pkt_st(p.sc->mbuf + head * 32 + sp * 8 + warp, ((uint64_t)__float_as_uint(l_w) << 32) | __float_as_uint(m_w), (uint64_t)tag << 32);
                *reinterpret_cast<float4*>(sc + lane * 4) = sv;
            }
            __syncwarp();
            float acc[24];
#pragma unroll
            for (int e = 0; e < 24; e++) acc[e] = 0.f;
            const int nt = ph ? NKT : NQT;
#pragma unroll 1
            for (int t = 0; t < nt; t++) {
                const int slot = ph ? (t & (NSLOT - 1)) : QSLOT + t;
                if (ph) mbar_wait(bar_full + 8 * slot, (t >> 4) & 1);
                const uint32_t a = rowoff + slot * TILE_BYTES;
                const uint4 u0 = lds128(a), u1 = lds128(a + 128), u2 = lds128(a + 256);
                const float p0 = sc[t * 4 + g];
                fma8(acc, u0, p0); fma8(acc + 8, u1, p0); fma8(acc + 16, u2, p0);
                __syncwarp();
                if (lane == 0) mbar_arrive(bar_empty + 8 * slot);
                if (t == NKT / 2) {
                    const uint4* q = p.sc->mbuf + head * 32 + lane;
                    uint64_t lo, hi;
                    uint32_t n = 0;
                    bool ok;
#pragma unroll 1
                    do {
                        pkt_ld(q, lo, hi);
                        ok = __all_sync(0xffffffffu, tag_ok(hi, tag));
                        if (++n > SPIN_LIMIT) __trap();
                    } while (!ok);
                    const float ms = val_of(lo), ls = __uint_as_float((uint32_t)(lo >> 32));
                    const float M = warp_max(ms);
                    fscale = ex2((m_w - M) * L2E) * __frcp_rn(warp_sum(ex2((ms - M) * L2E) * ls));
                }
                if (t == NKT - 4) mbar_wait(bar_topo, 0);
            }
            if (tid == 0) LST(ph ? 91 : 90);
            {
                const bool hi16 = lane & 16, hi8 = lane & 8;
                float r12[12], r6[6];
#pragma unroll
                for (int i = 0; i < 12; i++) {
                    const float send = hi16 ? acc[i] : acc[i + 12];
                    const float keep = hi16 ? acc[i + 12] : acc[i];
                    r12[i] = keep + __shfl_xor_sync(0xffffffffu, send, 16);
                }
#pragma unroll
                for (int i = 0; i < 6; i++) {
                    const float send = hi8 ? r12[i] : r12[i + 6];
                    const float keep = hi8 ? r12[i + 6] : r12[i];
                    r6[i] = (keep + __shfl_xor_sync(0xffffffffu, send, 8)) * fscale;
                }
                const int f0 = (hi16 ? 12 : 0) + (hi8 ? 6 : 0);
#pragma unroll
                for (int i = 0; i < 6; i++) {
                    const int f = f0 + i;
                    s_red[warp * DH + (f >> 3) * 64 + c * 8 + (f & 7)] = r6[i];
                }
            }
            cons_sync();
            if (ph == 0) {
                if (tid < DH) {
                    const float* r = s_red + tid;
                    ll_st1(p.sc->qbuf + (head * 4 + sp) * DH + tid,
                           ((r[0] + r[DH]) + (r[2 * DH] + r[3 * DH])) + ((r[4 * DH] + r[5 * DH]) + (r[6 * DH] + r[7 * DH])), tag);
                    const uint64_t* src = p.sc->qbuf + head * 4 * DH + tid;
                    uint64_t u0, u1, u2, u3;
                    uint32_t n = 0;
                    bool ok;
                    __nanosleep(CFG_QDELAY);
#pragma unroll 1
                    do {
                        if (n) __nanosleep(CFG_QSLEEP);
                        u0 = ll_ld1(src); u1 = ll_ld1(src + DH); u2 = ll_ld1(src + 2 * DH); u3 = ll_ld1(src + 3 * DH);
                        ok = __all_sync(0xffffffffu, tag_ok(u0, tag) && tag_ok(u1, tag) && tag_ok(u2, tag) && tag_ok(u3, tag));
                        if (++n > SPIN_LIMIT) __trap();
                    } while (!ok);
                    s_q[tid] = bfr((val_of(u0) + val_of(u1)) + (val_of(u2) + val_of(u3)));
                }
            } else {
                if (tid < 96) {
                    const float4* r = reinterpret_cast<const float4*>(s_red) + tid % 48;
                    const float4 r0 = r[0], r1 = r[48], r2 = r[96], r3 = r[144], r4 = r[192], r5 = r[240], r6 = r[288], r7 = r[336];
#define S_(c) (((r0.c + r1.c) + (r2.c + r3.c)) + ((r4.c + r5.c) + (r6.c + r7.c)))
                    in_st2(odst, pack_bf(S_(y), S_(x)), pack_bf(S_(w), S_(z)));
#undef S_
                }
                break;
            }
            cons_sync();
            if (tid == 0) LST(92);
        }
        const int t = lane & 3;
        const int arow = (lane & 7) + ((lane >> 4) << 3), ahalf = (lane >> 3) & 1;
        const uint32_t msel = s_sel[b >> 5] >> (b & 31) & 1;
        if (is_wo) {
            {
                const int dim = kg * 1024 + tid * 4, oh = dim / DH;
                const unsigned char* osrc[4];
                uint2 u[4];
#pragma unroll
                for (int i = 0; i < 4; i++) { osrc[i] = p.xa + xa_off(L_O + ((oh * 4 + i) * DH + dim - oh * DH) * 2, msel); u[i] = make_uint2(SENT, SENT); }
                mbar_wait(bar_tail + 8 * CFG_OGATE, 0);
                uint32_t n = 0;
#pragma unroll 1
                do {
                    if (n) __nanosleep(CFG_OSLEEP);
#pragma unroll
                    for (int i = 0; i < 4; i++) in_ld2p(osrc[i], u[i], !in_ok(u[i]));
                    if (++n > SPIN_LIMIT) __trap();
                } while (__any_sync(0xffffffffu, max(max(max(u[0].x, u[0].y), max(u[1].x, u[1].y)), max(max(u[2].x, u[2].y), max(u[3].x, u[3].y))) == SENT));
#define F_(f, c) ((f(u[0].c) + f(u[1].c)) + (f(u[2].c) + f(u[3].c)))
                sts64(sbase + SM_OB + tid * 8, pack_bf(F_(bf_hi, x), F_(bf_lo, x)), pack_bf(F_(bf_hi, y), F_(bf_lo, y)));
#undef F_
            }
            uint32_t wa = sbase + (warp * 16 + arow) * 128 + ((ahalf ^ (lane & 7)) << 4), oa = sbase + SM_OB + warp * 32 + t * 4;
            uint32_t pw = sbase + SM_RED + (warp * 64 + t * 16 + (lane >> 2)) * 4, pr = sbase + SM_RED + lane * 8;
            unsigned char* gdst = p.xa + xa_off(L_GATHER + (warp >> 1) % CFG_HCOPY * HCOPY_BYTES + (kg * D_MODEL + ng * 64 + lane * 2) * 2, warp & 1);
            pin(wa); pin(oa); pin(pw); pin(pr); pin(gdst);
            cons_sync();
            if (tid == 0) LST(93);
            float cw[4][4];
#pragma unroll
            for (int i = 0; i < 4; i++) cw[i][0] = cw[i][1] = cw[i][2] = cw[i][3] = 0.f;
            uint32_t ov[NWP][2];
#pragma unroll
            for (int j = 0; j < NWP; j++) { ov[j][0] = lds32(oa + j * 256); ov[j][1] = lds32(oa + j * 256 + 16); }
#pragma unroll
            for (int j = 0; j < NWP; j++) {
                mbar_wait(bar_tail + 8 * j, 0);
                uint32_t a[4][4];
#pragma unroll
                for (int i = 0; i < 4; i++) ldsm_x4_t(a[i], (wa ^ (i << 5)) + j * WPIECE);
#pragma unroll
                for (int i = 0; i < 4; i++) mma_bf16(cw[i], a[i], ov[j][0], ov[j][1]);
            }
#define SEL_(e) ((t & 2) ? ((t & 1) ? cw[3][e] : cw[2][e]) : ((t & 1) ? cw[1][e] : cw[0][e]))
            sts32(pw, SEL_(0)); sts32(pw + 32, SEL_(2));
#undef SEL_
            cons_sync();
            if (warp < 2 * CFG_HCOPY) {
                float2 r[8];
#pragma unroll
                for (int i = 0; i < 8; i++) r[i] = lds64f(pr + i * 256);
#define S_(c) (((r[0].c + r[1].c) + (r[2].c + r[3].c)) + ((r[4].c + r[5].c) + (r[6].c + r[7].c)))
                in_st1(gdst, __uint_as_float(pack_bf(S_(y), S_(x))));
#undef S_
            }
            if (tid == 0) LST(94);
        } else if (is_ffn) {
            uint32_t w13a = sbase + (warp * 16 + arow) * 64 + ((ahalf ^ (lane >> 1 & 3)) << 4);
            uint32_t red_dst = sbase + SM_RED + (warp * 32 + t * 8 + (lane >> 2)) * 8, red_src = sbase + SM_RED + lane * 8;
            uint32_t hdst = sbase + SM_HN + hcol * 2, stat = sbase + SM_MISC + warp * 8;
            uint32_t aoff[5];
            unsigned char* dst[5];
#pragma unroll
            for (int i = 0; i < 5; i++) {
                const int j = warp * 5 + i, rb = 2 * j + 1;
                aoff[i] = sbase + SM_W2 + ((j >> 2) * 16 + arow) * 128 + ((((j & 3) * 2 + ahalf) ^ (lane & 7)) << 4);
                dst[i] = p.xa + xa_off(L_D + j * 4096, s_sel[rb >> 5] >> (rb & 31) & 1) + rr * 64 + (lane & 1) * 32 + (lane >> 2) * 4;
                pin(aoff[i]); pin(dst[i]);
            }
            pin(w13a); pin(red_dst); pin(red_src); pin(hdst); pin(stat);
            uint32_t aw[NUP][4][4];
            auto load_w13 = [&](int i, uint32_t bar) {
                mbar_wait(bar + 8 * i, 0);
#pragma unroll
                for (int k = 0; k < 4; k++) ldsm_x4_t(aw[i][k], (w13a ^ (k << 5 & 32)) + i * WPIECE + (k >> 1) * (WPIECE / 2));
            };
            uint32_t hp0, hp1;
            {
                const unsigned char* gsrc[NG];
                uint2 u[NG];
#pragma unroll
                for (int i = 0; i < NG; i++) { u[i] = make_uint2(0, 0); gsrc[i] = p.xa + xa_off(L_GATHER + rr % CFG_HCOPY * HCOPY_BYTES + (i * D_MODEL + hcol) * 2, msel); pin(gsrc[i]); }
#pragma unroll
                for (int i = 0; i < CFG_HGATE; i++) load_w13(i, bar_tail);
                LSC(0);
#pragma unroll
                for (int i = 0; i < NG; i++) in_ld2p(gsrc[i], u[i], lane < 4 * NUP && !ABL_NOH);
                if (CFG_HSHADOW) load_w13(CFG_HGATE, bar_tail);
                LSCD(1, u[0].x ^ u[1].x ^ u[2].x ^ u[3].x ^ u[4].x ^ u[5].x);
                uint32_t n = 0;
#pragma unroll 1
                while (__any_sync(0xffffffffu, max(max(max(u[0].x, u[0].y), max(u[1].x, u[1].y)), max(max(max(u[2].x, u[2].y), max(u[3].x, u[3].y)),
                                                                                                    max(max(u[4].x, u[4].y), max(u[5].x, u[5].y)))) == SENT)) {
#pragma unroll
                    for (int i = 0; i < NG; i++) in_ld2p(gsrc[i], u[i], !in_ok(u[i]));
                    if (++n > SPIN_LIMIT) __trap();
                }
                if (tid == 96) LST(100);
                LSC(2);
#pragma unroll
                for (int i = CFG_HGATE + CFG_HSHADOW; i < HPRE; i++) load_w13(i, bar_tail);
#define F_(f, c) (f(xres.c) + bfr(((f(u[0].c) + f(u[1].c)) + (f(u[2].c) + f(u[3].c))) + (f(u[4].c) + f(u[5].c))))
                hp0 = pack_bf(F_(bf_hi, x), F_(bf_lo, x));
                hp1 = pack_bf(F_(bf_hi, y), F_(bf_lo, y));
#undef F_
            }
            {
                uint32_t b0[NUP], b1[NUP];
                float cf[4][4], cs[2][4];
#pragma unroll
                for (int e = 0; e < 4; e++) cf[0][e] = cf[1][e] = cf[2][e] = cf[3][e] = cs[0][e] = cs[1][e] = 0.f;
#pragma unroll
                for (int i = 0; i < NUP; i++) {
                    const uint32_t h0 = __shfl_sync(0xffffffffu, hp0, i * 4 + t), h1 = __shfl_sync(0xffffffffu, hp1, i * 4 + t);
                    b0[i] = (lane & 4) ? 0x3f803f80u : h0;
                    b1[i] = (lane & 4) ? 0x3f803f80u : h1;
                    const uint32_t sa[4] = {h0, h0, h1, h1};
                    mma_bf16(cs[i & 1], sa, b0[i], b1[i]);
                }
                auto mma_w13 = [&](int i) {
#pragma unroll
                    for (int k = 0; k < 4; k++) mma_bf16(cf[k], aw[i][k], b0[i], b1[i]);
                };
                if (lane < 4 * NUP) sts64(hdst, hp0, hp1);
                if (lane == 0) sts64(stat, __float_as_uint(cs[0][0] + cs[1][0]), __float_as_uint(cs[0][1] + cs[1][1]));
                __syncwarp();
                if (lane == 0) mbar_arrive(bar_h);
#pragma unroll
                for (int i = 0; i < HPRE; i++) mma_w13(i);
                LSC(3);
#pragma unroll
                for (int i = HPRE; i < NUP - 1; i++) { load_w13(i, bar_tail); mma_w13(i); }
                LSC(4);
                mbar_wait(bar_h, 0);
                {
                    const float4 pa = lds128f(sbase + SM_MISC), pb = lds128f(sbase + SM_MISC + 16), pc = lds128f(sbase + SM_MISC + 32), pd = lds128f(sbase + SM_MISC + 48);
                    ln_finish(((pa.y + pa.w) + (pb.y + pb.w)) + ((pc.y + pc.w) + (pd.y + pd.w)),
                              ((pa.x + pa.z) + (pb.x + pb.z)) + ((pc.x + pc.z) + (pd.x + pd.z)), mean_b, inv_den);
                }
                LSC(5);
#pragma unroll
                for (int m = 0; m < 2; m++) {
                    mbar_wait(after(bar_tail + 8 * (NUP - 1 + m), __float_as_uint(CFG_DEP4), p.zero), 0);
#pragma unroll
                    for (int k = 2 * m; k < 2 * m + 2; k++) ldsm_x4_t(aw[NUP - 1][k], (w13a ^ (k << 5 & 32)) + (NUP - 1) * WPIECE + m * (WPIECE / 2));
                }
                LSC(6);
                mma_w13(NUP - 1);
                mbar_wait(bar_tail + 8 * 6, 0);
#define SEL_(k, e) ((t & 2) ? ((t & 1) ? cf[k + 1][e + 2] : cf[k + 1][e]) : ((t & 1) ? cf[k][e + 2] : cf[k][e]))
                sts64(red_dst, __float_as_uint(fmaf(-mean_b, SEL_(0, 1), SEL_(0, 0))), __float_as_uint(fmaf(-mean_b, SEL_(2, 1), SEL_(2, 0))));
#undef SEL_
            }
            LSC(7);
            cons_sync();
            uint32_t bb[2][2], dep2, a0[5][4], a1[5][4];
            {
                float2 r[8];
#pragma unroll
                for (int i = 0; i < 8; i++) r[i] = lds64f(red_src + i * 256);
#pragma unroll
                for (int i = 0; i < 5; i++) ldsm_x4_t(a0[i], aoff[i]);
#define S_(c) (((r[0].c + r[1].c) + (r[2].c + r[3].c)) + ((r[4].c + r[5].c) + (r[6].c + r[7].c)))
                const float gate = bfr(S_(x) * inv_den), up = bfr(S_(y) * inv_den);
#undef S_
                LSCD(8, __float_as_uint(gate));
                const float act = bfr(__fdividef(gate, 1.0f + ex2(-gate * L2E)));
                const uint32_t hv1 = __float_as_uint(bfr(act * up));
                dep2 = hv1;
#pragma unroll
                for (int k = 0; k < 4; k++)
                    bb[k >> 1][k & 1] = __byte_perm(__shfl_sync(0xffffffffu, hv1, 8 * k + 2 * t), __shfl_sync(0xffffffffu, hv1, 8 * k + 2 * t + 1), 0x7632);
            }
            LSCD(9, bb[1][1]);
            float cw[5][4];
#pragma unroll
            for (int i = 0; i < 5; i++) cw[i][0] = cw[i][1] = cw[i][2] = cw[i][3] = 0.f;
            mbar_wait(after(bar_tail + 8 * (7 + (warp >> 2)), dep2, p.zero), 0);
#pragma unroll
            for (int i = 0; i < 5; i++) ldsm_x4_t(a1[i], aoff[i] + 2 * PIECE);
            LSC(10);
#pragma unroll
            for (int i = 0; i < 5; i++) mma_bf16(cw[i], a0[i], bb[0][0], bb[0][1]);
#pragma unroll
            for (int i = 0; i < 5; i++) mma_bf16(cw[i], a1[i], bb[1][0], bb[1][1]);
            if ((lane & 2) == 0) {
#pragma unroll
                for (int i = 0; i < 5; i++) in_st1(dst[i], (lane & 1) ? cw[i][2] : cw[i][0]);
            }
            __syncwarp();
            if (lane == 0) mbar_arrive(bar_red);
            LSC(11);
            if (lane == 0) LST(110 + warp);
        }
    }
}

typedef CUresult (*EncodeTiledFn)(CUtensorMap*, CUtensorMapDataType, cuuint32_t, void*, const cuuint64_t*, const cuuint64_t*,
                                  const cuuint32_t*, const cuuint32_t*, CUtensorMapInterleave, CUtensorMapSwizzle,
                                  CUtensorMapL2promotion, CUtensorMapFloatOOBfill);

void make_map(EncodeTiledFn fn, CUtensorMap* tm, const void* w, const int (&d)[5], const int (&st)[4], const int (&bx)[5],
              CUtensorMapSwizzle sw, int promo) {
    cuuint64_t dims[5], strides[4];
    cuuint32_t box[5], estr[5];
    for (int i = 0; i < 5; i++) { dims[i] = (cuuint64_t)d[i]; box[i] = (cuuint32_t)bx[i]; estr[i] = 1; }
    for (int i = 0; i < 4; i++) strides[i] = (cuuint64_t)st[i];
    fn(tm, CU_TENSOR_MAP_DATA_TYPE_BFLOAT16, 5, const_cast<void*>(w), dims, strides, box, estr, CU_TENSOR_MAP_INTERLEAVE_NONE, sw,
       (CUtensorMapL2promotion)promo, CU_TENSOR_MAP_FLOAT_OOB_FILL_NONE);
}

}

extern "C" void kernel_launch(void* const* d_in, const int* in_sizes, int n_in, void* d_out, int out_size) {
    (void)in_sizes; (void)n_in; (void)out_size;
    static EncodeTiledFn encode = nullptr;
    static Scratch* scratch = nullptr;
    static unsigned char* xarea = nullptr;
    static double tscale = 1.0;
    if (!encode) {
        void* sp = nullptr;
        cudaGetSymbolAddress(&sp, g_scratch);
        scratch = reinterpret_cast<Scratch*>(sp);
        cudaGetSymbolAddress(&sp, g_xarea);
        xarea = reinterpret_cast<unsigned char*>((reinterpret_cast<uintptr_t>(sp) + XA_ALIGN - 1) / XA_ALIGN * XA_ALIGN);
        void* fn = nullptr;
        cudaDriverEntryPointQueryResult st;
        cudaGetDriverEntryPoint("cuTensorMapEncodeTiled", &fn, cudaEnableDefault, &st);
        encode = reinterpret_cast<EncodeTiledFn>(fn);
        int dev = 0, khz = 0, bits = 0;
        cudaGetDevice(&dev);
        cudaDeviceGetAttribute(&khz, cudaDevAttrMemoryClockRate, dev);
        cudaDeviceGetAttribute(&bits, cudaDevAttrGlobalMemoryBusWidth, dev);
        if (khz > 0 && bits > 0) tscale = (2619000.0 * 5120.0) / ((double)khz * bits);
        cudaFuncSetAttribute(fused_decode_kernel, cudaFuncAttributeMaxDynamicSharedMemorySize, SM_TOTAL);
    }
    KParams p;
    p.x = (const __nv_bfloat16*)d_in[0];
    p.k = (const __nv_bfloat16*)d_in[1];
    p.v = (const __nv_bfloat16*)d_in[2];
    p.wq = (const __nv_bfloat16*)d_in[3];
    p.out = (__nv_bfloat16*)d_out;
    p.sc = scratch;
    p.xa = xarea;
    p.zero = 0;
    p.t_first = (uint32_t)(4 * CFG_OFF0 * tscale);
    p.t_step = (uint32_t)(CFG_T * tscale);
    p.t_smax = (uint32_t)(CFG_SMAX * tscale);
    p.t_lat = (uint32_t)(4 * (450 + (CFG_LAT - 450) * tscale));
    TMaps tm;
    constexpr int R1 = FF * 2, R2 = D_MODEL * 2;
    make_map(encode, &tm.wo, d_in[4], {D_MODEL, NHEAD * DH, 1, 1, 1}, {R2, R2, R2, R2}, {64, 128, 1, 1, 1}, CU_TENSOR_MAP_SWIZZLE_128B, CFG_PROMO_WO);
    make_map(encode, &tm.w1, d_in[6], {FF, 2, 20, 2, 8}, {R1, 4 * R1, 2 * R1, 80 * R1}, {32, 2, 4, 2, 8}, CU_TENSOR_MAP_SWIZZLE_64B, CFG_PROMO_W13);
    make_map(encode, &tm.w3, d_in[7], {FF, 2, 20, 2, 8}, {R1, 4 * R1, 2 * R1, 80 * R1}, {32, 2, 4, 2, 8}, CU_TENSOR_MAP_SWIZZLE_64B, CFG_PROMO_W13);
    make_map(encode, &tm.w2, d_in[8], {64, FF, 10, 1, 1}, {R2, 128, R2, R2}, {64, 16, 5, 1, 1}, CU_TENSOR_MAP_SWIZZLE_128B, CFG_PROMO_W2);
    fused_decode_kernel<<<NCTA, NTHREADS, SM_TOTAL, cudaStreamPerThread>>>(p, tm);
}
```

```cpp
#include <cuda_runtime.h>
#include <cuda_bf16.h>
#include <cuda.h>
#include <stdint.h>

namespace {

constexpr int D_MODEL = 640;
constexpr int NHEAD = 32;
constexpr int DH = 192;
constexpr int SK = 32768;
constexpr int WIN = 4096;
constexpr int FF = 1536;

constexpr int NCTA = 128;
constexpr int NCONS = 256;
constexpr int NTHREADS = NCONS + 96;
constexpr int ROW_BYTES = DH * 2;
constexpr int TILE_BYTES = 32 * ROW_BYTES;
constexpr int NSLOT = 16;
constexpr int NKT = 32;
constexpr int NQT = 5;
constexpr int QSLOT = NSLOT - NQT;
constexpr int NWO = 60;
constexpr int NG = 6;
constexpr int NFFN = 48;
constexpr int OUT0 = 24;
constexpr int NWP = 8;
constexpr int NUP = 5;
constexpr int WPIECE = 16384;
constexpr int NDP = 6;
constexpr int PIECE = 8192;
constexpr int NTAIL = NWP + NDP;
constexpr int N_TAIL0 = 2 * NKT;

#define CFG_NPROBE 4
#define CFG_OGATE 2
#define CFG_OSLEEP 100
#define CFG_PROMO_WO 2
#define CFG_PROMO_W13 2
#define CFG_PROMO_W2 2
#define CFG_PROBE_AT 12
#define CFG_QDELAY 1500
#define CFG_QSLEEP 400
#define CFG_BOUNDED_MBAR 0
#define CFG_T 1908
#define CFG_OFF0 2000
#define CFG_TWO 296
#define CFG_TFF 234
#define CFG_TW2 140
#define CFG_HGATE 1
#define ABL_NOH 0
#define CFG_HCOPY 2
#define CFG_MA 16
#define CFG_MB 40
#define CFG_ADAPT 58
#define CFG_LAT 1440
#define CFG_SMAX 1964
#define CFG_PSLEEP 1000
#define CFG_HSHADOW 0
#define CFG_T4 122
#define CFG_HPOST 0
constexpr int HPRE = CFG_HGATE + CFG_HSHADOW + CFG_HPOST;
#define CFG_KEEP 150
#define CFG_KEEP_AT 7
#define CFG_W2AT 1200
#define CFG_AGATE 4
#define CFG_DEPLAST 0
#define CFG_GAPWO 0
#define CFG_GAPFF 170
#define CFG_CAP 8

constexpr int SM_RING = 0;
constexpr int SM_W2 = NWP * WPIECE;
constexpr int SM_SC = SM_RING + NSLOT * TILE_BYTES;
constexpr int SM_RED = SM_SC + 8 * 128 * 4;
constexpr int SM_Q = SM_RED + 8 * DH * 4;
constexpr int SM_OB = SM_Q + DH * 4;
constexpr int SM_HN = SM_OB + 1024 * 2;
constexpr int SM_MISC = SM_HN + D_MODEL * 2;
constexpr int SM_BAR = SM_MISC + 128;
constexpr int SM_TOTAL = SM_BAR + 512;
static_assert(SM_TOTAL <= 232448, "shared memory");

struct __align__(128) Scratch {
    uint64_t qbuf[NHEAD * 4 * DH];
    uint4 mbuf[NHEAD * 32];
    uint32_t epoch;
    uint32_t pad[31];
    unsigned long long pace[2];
};
__device__ Scratch g_scratch;
constexpr int XA_ALIGN = 1 << 20;
constexpr uint32_t SENT = 0xffffffffu;
constexpr int L_GATHER = 0;
constexpr int HCOPY_BYTES = NG * D_MODEL * 2;
constexpr int L_O = 9 * 4096;
constexpr int L_ACT = 30 * 4096;
constexpr int L_PROBE = 32 * 4096;
static_assert(2 * (L_PROBE + NCTA * 1024) <= XA_ALIGN, "");
__device__ unsigned char g_xarea[2 * XA_ALIGN];
__device__ __forceinline__ uint32_t xa_off(uint32_t l, uint32_t side) {
    const uint32_t k = l >> 12;
    return (2 * k + ((side ^ k ^ (k >> 3) ^ (k >> 4) ^ (k >> 6)) & 1)) * 4096 + (l & 4095);
}

#define LST(i) do { } while (0)
#define LSC(i) do { } while (0)
#define LSCD(i, v) do { } while (0)
constexpr uint32_t SPIN_LIMIT = CFG_BOUNDED_MBAR ? 1u << 14 : 1u << 22;

__device__ __forceinline__ uint32_t now_q() { uint32_t t; asm volatile("mov.u32 %0, %globaltimer_lo;" : "=r"(t)); return t * 4; }
__device__ __forceinline__ void wait_until(uint32_t due) {
#pragma unroll 1
    for (int n = 0; n < 4096 && (int)(now_q() - due) < 0; n++) { }
}
__device__ __forceinline__ void sleep_until(uint32_t due) {
#pragma unroll 1
    for (int n = 0; n < 4096 && (int)(now_q() - due) < 0; n++) __nanosleep(200);
}
__device__ __forceinline__ uint32_t smem_u32(const void* p) { return (uint32_t)__cvta_generic_to_shared(p); }
__device__ __forceinline__ void mbar_init(uint32_t bar, uint32_t cnt) {
    asm volatile("mbarrier.init.shared::cta.b64 [%0], %1;" ::"r"(bar), "r"(cnt) : "memory");
}
__device__ __forceinline__ void mbar_expect_tx(uint32_t bar, uint32_t bytes) {
    asm volatile("mbarrier.arrive.expect_tx.shared::cta.b64 _, [%0], %1;" ::"r"(bar), "r"(bytes) : "memory");
}
__device__ __forceinline__ void mbar_arrive(uint32_t bar) {
    asm volatile("mbarrier.arrive.shared::cta.b64 _, [%0];" ::"r"(bar) : "memory");
}
__device__ __forceinline__ bool mbar_test(uint32_t bar, uint32_t parity) {
    uint32_t ok;
    asm volatile("{\n.reg .pred p;\nmbarrier.test_wait.parity.shared::cta.b64 p, [%1], %2;\nselp.u32 %0, 1, 0, p;\n}"
                 : "=r"(ok) : "r"(bar), "r"(parity) : "memory");
    return ok;
}
__device__ __forceinline__ void mbar_wait(uint32_t bar, uint32_t parity) {
    asm volatile("{\n.reg .pred p;\nW_%=:\nmbarrier.try_wait.parity.shared::cta.b64 p, [%0], %1;\n@!p bra W_%=;\n}" ::"r"(bar), "r"(parity) : "memory");
}
__device__ __forceinline__ void bulk_load(uint32_t dst, const void* src, uint32_t bytes, uint32_t bar, uint64_t pol) {
    asm volatile("cp.async.bulk.shared::cluster.global.mbarrier::complete_tx::bytes.L2::cache_hint [%0], [%1], %2, [%3], %4;"
                 ::"r"(dst), "l"(src), "r"(bytes), "r"(bar), "l"(pol) : "memory");
}
__device__ __forceinline__ void tma_5d(uint32_t dst, const CUtensorMap* tm, int c0, int c1, int c2, int c4, uint32_t bar) {
    asm volatile("cp.async.bulk.tensor.5d.shared::cluster.global.mbarrier::complete_tx::bytes [%0], [%1, {%3, %4, %5, %7, %6}], [%2];"
                 ::"r"(dst), "l"(reinterpret_cast<uint64_t>(tm)), "r"(bar), "r"(c0), "r"(c1), "r"(c2), "r"(c4), "r"(0) : "memory");
}
__device__ __forceinline__ uint32_t bits(uint32_t v) { return v; }
__device__ __forceinline__ uint32_t bits(float v) { return __float_as_uint(v); }
__device__ __forceinline__ uint32_t bits(const void* v) { return (uint32_t)(uintptr_t)v ^ (uint32_t)((uintptr_t)v >> 32); }
template <class... T> __device__ __forceinline__ uint32_t after(uint32_t zero, uint32_t bar, T... v) { return bar | ((bits(v) ^ ...) & zero); }
__device__ __forceinline__ void sts32(uint32_t a, float v) { asm volatile("st.shared.f32 [%0], %1;" ::"r"(a), "f"(v) : "memory"); }
__device__ __forceinline__ void sts64(uint32_t a, uint32_t x, uint32_t y) { asm volatile("st.shared.v2.u32 [%0], {%1, %2};" ::"r"(a), "r"(x), "r"(y) : "memory"); }
__device__ __forceinline__ void cons_sync() { asm volatile("bar.sync 1, 256;" ::: "memory"); }

__device__ __forceinline__ uint4 lds128(uint32_t a) {
    uint4 v;
    asm volatile("ld.shared.v4.u32 {%0,%1,%2,%3}, [%4];" : "=r"(v.x), "=r"(v.y), "=r"(v.z), "=r"(v.w) : "r"(a));
    return v;
}
__device__ __forceinline__ float4 lds128f(uint32_t a) {
    float4 v;
    asm volatile("ld.shared.v4.f32 {%0,%1,%2,%3}, [%4];" : "=f"(v.x), "=f"(v.y), "=f"(v.z), "=f"(v.w) : "r"(a) : "memory");
    return v;
}
__device__ __forceinline__ float2 lds64f(uint32_t a) {
    float2 v;
    asm volatile("ld.shared.v2.f32 {%0,%1}, [%2];" : "=f"(v.x), "=f"(v.y) : "r"(a) : "memory");
    return v;
}
__device__ __forceinline__ uint32_t lds32(uint32_t a) {
    uint32_t v;
    asm volatile("ld.shared.u32 %0, [%1];" : "=r"(v) : "r"(a));
    return v;
}
__device__ __forceinline__ void ldsm_x4_t(uint32_t* r, uint32_t a) {
    asm volatile("ldmatrix.sync.aligned.m8n8.x4.trans.shared.b16 {%0,%1,%2,%3}, [%4];"
                 : "=r"(r[0]), "=r"(r[1]), "=r"(r[2]), "=r"(r[3]) : "r"(a));
}
__device__ __forceinline__ void mma_bf16(float* c, const uint32_t* a, uint32_t b0, uint32_t b1) {
    asm volatile("mma.sync.aligned.m16n8k16.row.col.f32.bf16.bf16.f32 {%0,%1,%2,%3}, {%4,%5,%6,%7}, {%8,%9}, {%0,%1,%2,%3};"
                 : "+f"(c[0]), "+f"(c[1]), "+f"(c[2]), "+f"(c[3]) : "r"(a[0]), "r"(a[1]), "r"(a[2]), "r"(a[3]), "r"(b0), "r"(b1));
}
__device__ __forceinline__ float bf_lo(uint32_t u) { return __uint_as_float(u << 16); }
__device__ __forceinline__ float bf_hi(uint32_t u) { return __uint_as_float(u & 0xffff0000u); }
__device__ __forceinline__ uint32_t pack_bf(float hi, float lo) { uint32_t r; asm("cvt.rn.bf16x2.f32 %0, %1, %2;" : "=r"(r) : "f"(hi), "f"(lo)); return r; }
__device__ __forceinline__ float bfr(float x) { return __uint_as_float(pack_bf(x, 0.f)); }

__device__ __forceinline__ uint64_t pk(float v, uint32_t tag) { return ((uint64_t)tag << 32) | (uint64_t)__float_as_uint(v); }
__device__ __forceinline__ void ll_st1(uint64_t* p, float a, uint32_t tag) {
    asm volatile("st.relaxed.gpu.global.b64 [%0], %1;" ::"l"(p), "l"(pk(a, tag)) : "memory");
}
__device__ __forceinline__ uint64_t ll_ld1(const uint64_t* p) {
    uint64_t v;
    asm volatile("ld.relaxed.gpu.global.b64 %0, [%1];" : "=l"(v) : "l"(p) : "memory");
    return v;
}
__device__ __forceinline__ uint32_t in_word(float v) {
    uint32_t r;
    asm("min.u32 %0, %1, 0xfffffffe;" : "=r"(r) : "r"(__float_as_uint(v)));
    return r;
}
__device__ __forceinline__ void in_st1(void* p, float v) {
    asm volatile("st.relaxed.gpu.global.u32 [%0], %1;" ::"l"(p), "r"(in_word(v)) : "memory");
}
__device__ __forceinline__ void in_st4(void* p, uint32_t a, uint32_t b, uint32_t c, uint32_t d) {
    asm volatile("st.relaxed.gpu.global.v4.u32 [%0], {%1, %2, %3, %4};" ::"l"(p), "r"(a), "r"(b), "r"(c), "r"(d) : "memory");
}
__device__ __forceinline__ uint32_t in_ld1(const void* p) {
    uint32_t v;
    asm volatile("ld.relaxed.gpu.global.u32 %0, [%1];" : "=r"(v) : "l"(p) : "memory");
    return v;
}
__device__ __forceinline__ uint4 in_ld4(const void* p) {
    uint4 v;
    asm volatile("ld.relaxed.gpu.global.v4.u32 {%0, %1, %2, %3}, [%4];" : "=r"(v.x), "=r"(v.y), "=r"(v.z), "=r"(v.w) : "l"(p) : "memory");
    return v;
}
__device__ __forceinline__ void in_st2(void* p, uint32_t a, uint32_t b) {
    asm volatile("st.relaxed.gpu.global.v2.u32 [%0], {%1, %2};" ::"l"(p), "r"(min(a, SENT - 1)), "r"(min(b, SENT - 1)) : "memory");
}
__device__ __forceinline__ void in_ld2p(const void* p, uint2& v, bool on) {
    asm volatile("{\n.reg .pred q;\nsetp.ne.u32 q, %3, 0;\n@q ld.relaxed.gpu.global.v2.u32 {%0, %1}, [%2];\n}"
                 : "+r"(v.x), "+r"(v.y) : "l"(p), "r"((uint32_t)on) : "memory");
}
__device__ __forceinline__ bool in_ok(const uint2& v) { return max(v.x, v.y) != SENT; }
__device__ __forceinline__ void in_ld4p(const void* p, uint4& v, bool on) {
    asm volatile("{\n.reg .pred q;\nsetp.ne.u32 q, %5, 0;\n@q ld.relaxed.gpu.global.v4.u32 {%0, %1, %2, %3}, [%4];\n}"
                 : "+r"(v.x), "+r"(v.y), "+r"(v.z), "+r"(v.w) : "l"(p), "r"((uint32_t)on) : "memory");
}
__device__ __forceinline__ bool tag_ok(uint64_t v, uint32_t tag) { return (uint32_t)(v >> 32) == tag; }
__device__ __forceinline__ float val_of(uint64_t v) { return __uint_as_float((uint32_t)v); }
__device__ __forceinline__ void pkt_st(uint4* p, uint64_t lo, uint64_t hi) {
    asm volatile("{\n.reg .b128 t;\nmov.b128 t, {%1, %2};\nst.relaxed.gpu.global.b128 [%0], t;\n}" ::"l"(p), "l"(lo), "l"(hi) : "memory");
}
__device__ __forceinline__ void pkt_ld(const uint4* p, uint64_t& lo, uint64_t& hi) {
    asm volatile("{\n.reg .b128 t;\nld.relaxed.gpu.global.b128 t, [%2];\nmov.b128 {%0, %1}, t;\n}" : "=l"(lo), "=l"(hi) : "l"(p) : "memory");
}

__device__ __forceinline__ float warp_sum(float v) {
#pragma unroll
    for (int o = 16; o > 0; o >>= 1) v += __shfl_xor_sync(0xffffffffu, v, o);
    return v;
}
__device__ __forceinline__ float warp_max(float v) {
#pragma unroll
    for (int o = 16; o > 0; o >>= 1) v = fmaxf(v, __shfl_xor_sync(0xffffffffu, v, o));
    return v;
}
__device__ __forceinline__ void fma8(float* acc, const uint4& u, float w) {
    acc[0] = fmaf(w, bf_lo(u.x), acc[0]); acc[1] = fmaf(w, bf_hi(u.x), acc[1]);
    acc[2] = fmaf(w, bf_lo(u.y), acc[2]); acc[3] = fmaf(w, bf_hi(u.y), acc[3]);
    acc[4] = fmaf(w, bf_lo(u.z), acc[4]); acc[5] = fmaf(w, bf_hi(u.z), acc[5]);
    acc[6] = fmaf(w, bf_lo(u.w), acc[6]); acc[7] = fmaf(w, bf_hi(u.w), acc[7]);
}
__device__ __forceinline__ void dot8(float& s0, float& s1, const uint4& u, const float* q) {
    s0 = fmaf(q[0], bf_lo(u.x), s0); s1 = fmaf(q[1], bf_hi(u.x), s1);
    s0 = fmaf(q[2], bf_lo(u.y), s0); s1 = fmaf(q[3], bf_hi(u.y), s1);
    s0 = fmaf(q[4], bf_lo(u.z), s0); s1 = fmaf(q[5], bf_hi(u.z), s1);
    s0 = fmaf(q[6], bf_lo(u.w), s0); s1 = fmaf(q[7], bf_hi(u.w), s1);
}
__device__ __forceinline__ float sqrt_fast(float x) { float r; asm("sqrt.approx.ftz.f32 %0, %1;" : "=f"(r) : "f"(x)); return r; }
__device__ __forceinline__ float rcp_fast(float x) { float r; asm("rcp.approx.ftz.f32 %0, %1;" : "=f"(r) : "f"(x)); return r; }
__device__ __forceinline__ float ex2(float x) { float r; asm("ex2.approx.ftz.f32 %0, %1;" : "=f"(r) : "f"(x)); return r; }
constexpr float L2E = 1.4426950408889634f;
__device__ __forceinline__ void ln_finish(float s1, float s2, float& mean_b, float& inv_den) {
    const float mean = s1 * (1.0f / D_MODEL);
    const float var = fmaxf(fmaf(-mean, mean, s2 * (1.0f / D_MODEL)), 0.f);
    mean_b = bfr(mean);
    inv_den = rcp_fast(bfr(sqrt_fast(bfr(bfr(var) + 1e-5f))));
}
__device__ __forceinline__ float ln_apply(float v, float mean_b, float inv_den) { return bfr(bfr(v - mean_b) * inv_den); }

struct KParams {
    const __nv_bfloat16* wq;
    const __nv_bfloat16* k;
    uint32_t t_first;
    uint32_t t_step;
    const __nv_bfloat16* x;
    Scratch* sc;
    unsigned char* xa;
    const __nv_bfloat16* v;
    __nv_bfloat16* out;
    uint32_t t_smax;
    uint32_t t_lat;
    uint32_t zero;
};
struct TMaps { CUtensorMap wo, w1, w3, w2; };

__global__ void __launch_bounds__(NTHREADS, 1)
fused_decode_kernel(const KParams p, const __grid_constant__ TMaps tm) {
    extern __shared__ __align__(1024) unsigned char smem[];
    const uint32_t sbase = smem_u32(smem);
    const int tid = threadIdx.x;
    const int b = blockIdx.x;
    const int head = b >> 2, sp = b & 3;
    {
        if (tid < 240) {
            const int rg = tid / 24, ch = tid - rg * 24;
            const char* src = reinterpret_cast<const char*>(p.wq) + (size_t)(sp * 160 + rg) * (NHEAD * DH * 2) + head * ROW_BYTES + ch * 16;
            uint32_t dst = sbase + SM_RING + QSLOT * TILE_BYTES + tid * 16;
#pragma unroll 1
            for (int i = 0; i < 16; i++) {
                asm volatile("cp.async.cg.shared.global [%0], [%1], 16;" ::"r"(dst), "l"(src) : "memory");
                dst += 10 * ROW_BYTES;
                src += (size_t)10 * (NHEAD * DH * 2);
            }
        }
    }
    const int warp = __shfl_sync(0xffffffffu, tid >> 5, 0), lane = tid & 31;
    const int rr = b >> 1;
    const bool is_wo = !(b & 1) && rr < NWO, is_ffn = (b & 1) && rr < NFFN, is_out = !(b & 1) && rr >= OUT0;
    const int kg = min(rr / 10, NG - 1), ng = rr % 10;
    const uint32_t bar_full = sbase + SM_BAR;
    const uint32_t bar_empty = sbase + SM_BAR + 128;
    const uint32_t bar_tail = sbase + SM_BAR + 256;
    const uint32_t bar_h = bar_tail + 8 * NTAIL;
    const uint32_t bar_set = bar_h + 8;
    const uint32_t bar_pace = bar_h + 16;
    volatile uint32_t* s_pace = reinterpret_cast<volatile uint32_t*>(smem + SM_MISC + 64);

    if (warp == 8) {
        const uint32_t c_start = now_q();
        uint64_t pol_stream;
        asm volatile("createpolicy.fractional.L2::evict_first.b64 %0, 1.0;" : "=l"(pol_stream));
        const size_t kv_off = ((size_t)head * SK + (SK - WIN)) * ROW_BYTES + (size_t)sp * TILE_BYTES;
        const char* kp = reinterpret_cast<const char*>(p.k) + kv_off;
        if (lane == 0) {
#pragma unroll 1
            for (int i = 0; i < NSLOT; i++) { mbar_init(bar_full + 8 * i, 1); mbar_init(bar_empty + 8 * i, 8); }
#pragma unroll 1
            for (int i = 0; i < NTAIL + 3; i++) mbar_init(bar_tail + 8 * i, i == NTAIL ? 8 : 1);
            asm volatile("fence.mbarrier_init.release.cluster;" ::: "memory");
        }
        __syncwarp();
        asm volatile("bar.arrive 2, 288;" ::: "memory");
        asm volatile("bar.arrive 3, 64;" ::: "memory");
        asm volatile("bar.arrive 4, 64;" ::: "memory");
        if (lane >= 1 && lane <= 4) asm volatile("prefetch.tensormap [%0];" ::"l"(reinterpret_cast<uint64_t>(&tm.wo + (lane - 1))) : "memory");
        if (lane == 0) {
            const char* vp = reinterpret_cast<const char*>(p.v) + kv_off;
            uint32_t due = c_start + p.t_first, step = p.t_step;
            const char* src = kp;
#pragma unroll 1
            for (int n = 0; n < N_TAIL0; n++) {
                const int slot = n & (NSLOT - 1);
                const int use = (n >> 4) + (slot >= QSLOT);
                if (n >= CFG_CAP) mbar_wait(bar_full + 8 * ((n - CFG_CAP) & (NSLOT - 1)), ((n - CFG_CAP) >> 4) & 1);
                if (use >= 1) mbar_wait(bar_empty + 8 * slot, (use - 1) & 1);
                if (n == CFG_ADAPT) { mbar_wait(bar_pace, 0); due = s_pace[0]; step = s_pace[1]; }
                const uint32_t full = bar_full + 8 * slot;
                mbar_expect_tx(full, TILE_BYTES);
                wait_until(due);
                LST(128 + n);
                bulk_load(sbase + SM_RING + slot * TILE_BYTES, src, TILE_BYTES, full, pol_stream);
                due += step;
                src = n == NKT - 1 ? vp : src + 4 * TILE_BYTES;
            }
            const uint32_t t_wo = step * (CFG_TWO * 4096 / 478) >> 12;
            due += 4 * CFG_GAPWO;
            if (is_wo) {
#pragma unroll 1
                for (int j = 0; j < NWP; j++) {
                    mbar_wait(bar_empty + 8 * (((j + 1) * WPIECE - 1) / TILE_BYTES), 1);
                    mbar_expect_tx(bar_tail + 8 * j, WPIECE);
                    wait_until(due);
                    LST(128 + N_TAIL0 + j);
                    tma_5d(sbase + j * WPIECE, &tm.wo, ng * 64, kg * 1024 + j * 128, 0, 0, bar_tail + 8 * j);
                    due += t_wo;
                }
            } else {
                due += NWP * t_wo;
            }
            due += 4 * CFG_GAPFF;
            if (is_out) {
                due += step * (CFG_W2AT * 4096 / 478) >> 12;
                static_assert((SM_W2 + NDP * PIECE - 1) / TILE_BYTES >= QSLOT, "one phase more");
                mbar_wait(bar_empty + 8 * ((SM_W2 + NDP * PIECE - 1) / TILE_BYTES), 0);
#pragma unroll
                for (int j = 0; j < NDP; j++) mbar_expect_tx(bar_tail + 8 * (NWP + j), PIECE);
                sleep_until(due - 4 * 400);
#pragma unroll
                for (int j = 0; j < NDP; j++) {
                    wait_until(due);
                    tma_5d(sbase + SM_W2 + j * PIECE, &tm.w2, (rr - OUT0) * 16, j * 256, 0, 0, bar_tail + 8 * (NWP + j));
                    LST(128 + N_TAIL0 + NWP + j);
                    due += 4 * CFG_TW2;
                }
            } else if (is_ffn) {
                mbar_wait(bar_empty + 8 * ((NUP * WPIECE - 1) / TILE_BYTES), 1);
#pragma unroll
                for (int j = 0; j <= NUP; j++) mbar_expect_tx(bar_tail + 8 * j, j < NUP - 1 ? WPIECE : WPIECE / 2);
                sleep_until(due - 4 * 400);
#pragma unroll
                for (int j = 0; j <= NUP; j++) {
                    const uint32_t full = bar_tail + 8 * j;
                    const int i = min(j, NUP - 1);
                    wait_until(due);
                    if (j < NUP) tma_5d(sbase + i * WPIECE, &tm.w1, rr * 32, 0, i * 4, 0, full);
                    if (j != NUP - 1) tma_5d(sbase + i * WPIECE + WPIECE / 2, &tm.w3, rr * 32, 0, i * 4, 0, full);
                    LST(128 + N_TAIL0 + j);
                    due += step * ((j < NUP - 1 ? CFG_TFF : CFG_T4) * 4096 / 478) >> 12;
                }
            }
        }
    } else if (warp == 10) {
        asm volatile("bar.sync 4, 64;" ::: "memory");
        if (lane == 0) {
            uint32_t epoch0;
            asm volatile("ld.relaxed.gpu.global.u32 %0, [%1];" : "=r"(epoch0) : "l"(&p.sc->epoch) : "memory");
            constexpr int MN = 8;
            const uint32_t t0 = now_q();
            uint32_t sa = 0, sb = 0;
#pragma unroll 1
            for (int n = 0; n < CFG_MB + MN; n++) {
                mbar_wait(bar_full + 8 * (n & (NSLOT - 1)), (n >> 4) & 1);
                const uint32_t t = now_q() - t0;
                LST(n);
                if ((uint32_t)(n - CFG_MA) < MN) sa += t;
                if (n >= CFG_MB) sb += t;
            }
            const uint32_t mb = t0 + sb / MN;
            unsigned long long* pace = p.sc->pace + ((epoch0 + 1) & 1);
            mbar_wait(bar_set, 0);
            asm volatile("red.relaxed.gpu.global.add.u64 [%0], %1;" ::"l"(pace), "l"((unsigned long long)mb << 32 | min((sb - sa) / (4 * MN), 0xffffu) << 8 | 1) : "memory");
            if (b == 0) p.sc->pace[epoch0 & 1] = 0;
            unsigned long long v;
            uint32_t n = 0, cnt;
#pragma unroll 1
            do {
                __nanosleep(n ? 200 : CFG_PSLEEP);
                asm volatile("ld.relaxed.gpu.global.u64 %0, [%1];" : "=l"(v) : "l"(pace) : "memory");
                cnt = (uint32_t)v & 0xff;
                if (++n > SPIN_LIMIT) __trap();
            } while (cnt < NCTA);
            const uint32_t step = min(max(((uint32_t)v >> 8) / (NCTA / 4 * (CFG_MB - CFG_MA)), p.t_step), p.t_smax);
            s_pace[0] = mb + (int)((uint32_t)(v >> 32) - NCTA * mb) / NCTA + step * (2 * (CFG_ADAPT - CFG_MB) - (MN - 1)) / 2 - p.t_lat;
            s_pace[1] = step;
            mbar_arrive(bar_pace);
            LST(89);
        }
    } else if (warp == 9) {
        const uint32_t c_start = now_q();
        uint32_t epoch0;
        asm volatile("ld.relaxed.gpu.global.u32 %0, [%1];" : "=r"(epoch0) : "l"(&p.sc->epoch) : "memory");
        sleep_until(c_start + p.t_first + CFG_PROBE_AT * p.t_step);
        unsigned char* slot[3];
#pragma unroll
        for (int i = 0; i < 2; i++) slot[i] = p.xa + xa_off(L_O + (head * 4 + sp) * DH * 2 + min(lane, 23) * 16, i);
        slot[2] = p.xa + (is_wo ? xa_off(L_GATHER + (lane >> 4) * HCOPY_BYTES + (kg * D_MODEL + ng * 64 + (lane & 7) * 8) * 2, lane >> 3 & 1)
                                : xa_off(L_ACT + rr * 64 + (lane & 3) * 16, lane >> 2 & 1));
        const int n2 = is_wo ? 16 * CFG_HCOPY : is_ffn ? 8 : 0;
#pragma unroll
        for (int i = 0; i < 3; i++) if (lane < (i < 2 ? 24 : n2)) in_st4(slot[i], SENT, SENT, SENT, SENT);
        unsigned char* probe = p.xa + xa_off(L_PROBE + b * 1024 + (lane >> 1 & 7) * 128 + (lane & 1) * 16, lane >> 4);
        in_st4(probe, SENT, SENT, SENT, SENT);
        uint32_t acc = SENT;
#pragma unroll
        for (int i = 0; i < 3; i++) if (lane < (i < 2 ? 24 : n2)) acc &= in_ld1(slot[i]);
        if (__any_sync(0xffffffffu, acc != SENT)) __trap();
        int vote = 0;
        uint32_t lat[2] = {0, 0};
#pragma unroll 1
        for (int r = 0; r <= CFG_NPROBE; r++) {
            uint32_t d[2];
#pragma unroll
            for (int i = 0; i < 2; i++) {
                const uint32_t c0 = (uint32_t)clock();
                if (__any_sync(0xffffffffu, in_ld1(p.xa + xa_off(L_PROBE + b * 1024 + (lane & 7) * 128, i)) != SENT)) __trap();
                d[i] = (uint32_t)clock() - c0;
                if (r) lat[i] += min(d[i], 1500u);
            }
            if (r) vote += (d[1] < d[0]) - (d[0] < d[1]);
        }
        const uint32_t sel = vote ? vote > 0 : lat[1] < lat[0];
        const uint32_t tag = epoch0 + 1;
        asm volatile("bar.sync 3, 64;" ::: "memory");
        if (lane == 0) { s_pace[2] = sel; mbar_arrive(bar_set); }
        if (is_ffn || is_wo || is_out) {
            mbar_wait(bar_pace, 0);
            sleep_until(s_pace[0] + CFG_KEEP_AT * s_pace[1]);
            float c[4] = {0.f, 0.f, 0.f, 0.f};
            const uint32_t z[4] = {p.zero, p.zero, p.zero, p.zero};
            uint32_t n = 0;
#pragma unroll 1
            do {
                mma_bf16(c, z, p.zero, p.zero);
                __nanosleep(CFG_KEEP);
                n += 1 + __float_as_uint(c[0]);
            } while (!__all_sync(0xffffffffu, mbar_test(bar_tail + 8 * (is_ffn ? 1 : is_out ? NWP : NWP - 1), 0)) && n < SPIN_LIMIT);
            if (is_ffn) {
                unsigned char* adst = p.xa + xa_off(L_ACT + rr * 64 + (lane >> 3) * 16 + (lane & 3) * 4, lane >> 2 & 1);
                uint32_t src = sbase + SM_RED + lane * 16;
                mbar_wait(after(p.zero, bar_h, adst, src), 0);
                const float4 pa = lds128f(sbase + SM_MISC), pb = lds128f(sbase + SM_MISC + 16), pc = lds128f(sbase + SM_MISC + 32), pd = lds128f(sbase + SM_MISC + 48);
                float mean_b, inv_den;
                ln_finish(((pa.y + pa.w) + (pb.y + pb.w)) + ((pc.y + pc.w) + (pd.y + pd.w)),
                          ((pa.x + pa.z) + (pb.x + pb.z)) + ((pc.x + pc.z) + (pd.x + pd.z)), mean_b, inv_den);
                asm volatile("bar.sync %0, 288;" ::"r"(after(p.zero, 5, inv_den, mean_b)) : "memory");
                float4 r[8];
#pragma unroll
                for (int i = 0; i < 8; i++) r[i] = lds128f(src + i * 512);
#define S_(c) (((r[0].c + r[1].c) + (r[2].c + r[3].c)) + ((r[4].c + r[5].c) + (r[6].c + r[7].c)))
                const float gate = bfr(fmaf(-mean_b, S_(y), S_(x)) * inv_den), up = bfr(fmaf(-mean_b, S_(w), S_(z)) * inv_den);
#undef S_
                const float act = bfr(__fdividef(gate, 1.0f + ex2(-gate * L2E))) * up;
                const float oth = __shfl_xor_sync(0xffffffffu, act, 4);
                in_st1(adst, __uint_as_float((lane & 4) ? pack_bf(act, oth) : pack_bf(oth, act)));
                if (lane == 0) LST(110);
            }
            if (is_out) {
                const int col = (rr - OUT0) * 16 + (lane & 15);
                uint32_t u[NG], xv;
                asm volatile("ld.global.nc.u16 %0, [%1];" : "=r"(xv) : "l"(p.x + col));
                mma_bf16(c, z, p.zero, p.zero);
                n = __float_as_uint(c[0]);
#pragma unroll 1
                do {
#pragma unroll
                    for (int i = 0; i < NG; i++) u[i] = in_ld1(p.xa + xa_off(L_GATHER + rr % CFG_HCOPY * HCOPY_BYTES + (i * D_MODEL + (col & ~1)) * 2, sel));
                    if (++n > SPIN_LIMIT) __trap();
                } while (__any_sync(0xffffffffu, max(max(max(u[0], u[1]), max(u[2], u[3])), max(u[4], u[5])) == SENT));
                if (rr == OUT0 && lane == 0) p.sc->epoch = tag;
#define F_(i) ((lane & 1) ? bf_hi(u[i]) : bf_lo(u[i]))
                float res = bfr(bf_lo(xv) + bfr(((F_(0) + F_(1)) + (F_(2) + F_(3))) + (F_(4) + F_(5))));
#undef F_
                mma_bf16(c, z, p.zero, p.zero);
                res += c[0];
                __nv_bfloat16* dst = p.out + col;
                uint32_t src = sbase + SM_HN + (lane & 15) * 48;
                asm volatile("bar.sync %0, 288;" ::"r"(after(p.zero, 5, src, dst, res)) : "memory");
                const float4 ra = lds128f(src), rb = lds128f(src + 16);
                const float e = ((ra.x + ra.y) + (ra.z + ra.w)) + ((rb.x + rb.y) + (rb.z + rb.w));
                if (lane < 16) asm volatile("st.global.u16 [%0], %1;" ::"l"(dst), "h"((unsigned short)pack_bf(0.f, res + bfr(e))) : "memory");
                if (lane == 0) LST(96);
            }
        }
    } else {
        float* s_red = reinterpret_cast<float*>(smem + SM_RED);
        float* s_q = reinterpret_cast<float*>(smem + SM_Q);
        float* sc = reinterpret_cast<float*>(smem + SM_SC) + warp * 128;
        const int g = lane >> 3, c = lane & 7;
        const int hcol = warp * 80 + min(lane, 4 * NUP - 1) * 4;
        uint32_t xr, epoch0;
        uint2 xu[5], xres;
        {
            const char* xb = reinterpret_cast<const char*>(p.x);
            asm volatile("ld.global.nc.u16 %0, [%1];" : "=r"(xr) : "l"(xb + (sp * 160 + min(lane >> 2, NQT - 1) * 32 + warp * 4 + (lane & 3)) * 2));
#pragma unroll
            for (int i = 0; i < 5; i++) asm volatile("ld.global.nc.v2.u32 {%0, %1}, [%2];" : "=r"(xu[i].x), "=r"(xu[i].y) : "l"(xb + i * 256 + lane * 8));
            asm volatile("ld.global.nc.v2.u32 {%0, %1}, [%2];" : "=r"(xres.x), "=r"(xres.y) : "l"(xb + hcol * 2));
            asm volatile("ld.relaxed.gpu.global.u32 %0, [%1];" : "=r"(epoch0) : "l"(&p.sc->epoch) : "memory");
        }
        if (tid < DH) ll_st1(p.sc->qbuf + (head * 4 + sp) * DH + tid, 0.f, 0);
        if (lane == 0) pkt_st(p.sc->mbuf + head * 32 + sp * 8 + warp, 0, 0);
        const uint32_t rowoff = sbase + SM_RING + (warp * 4 + g) * ROW_BYTES + c * 16;

        float mean_b, inv_den;
        uint32_t tag = 0;
        unsigned char* odst = p.xa + xa_off(L_O + ((head * 4 + sp) * DH + (tid % 48) * 4) * 2, tid / 48 & 1);

        {
            float s1 = 0.f, s2 = 0.f;
#pragma unroll
            for (int i = 0; i < 5; i++) {
                const float a0 = bf_lo(xu[i].x), a1 = bf_hi(xu[i].x), a2 = bf_lo(xu[i].y), a3 = bf_hi(xu[i].y);
                s1 += (a0 + a1) + (a2 + a3);
                s2 = fmaf(a0, a0, fmaf(a1, a1, fmaf(a2, a2, fmaf(a3, a3, s2))));
            }
#pragma unroll
            for (int o = 16; o > 0; o >>= 1) { s1 += __shfl_xor_sync(0xffffffffu, s1, o); s2 += __shfl_xor_sync(0xffffffffu, s2, o); }
            ln_finish(s1, s2, mean_b, inv_den);
            sc[lane] = ln_apply(bf_lo(xr), mean_b, inv_den);
            asm volatile("cp.async.wait_all;" ::: "memory");
            if (lane == 0) LST(80 + warp);
            asm volatile("bar.sync 2, 288;" ::: "memory");
            tag = epoch0 + 1;
        }

#pragma unroll 1
        for (int ph = 0; ph < 2; ph++) {
            float m_w = 0.f, fscale = 1.f;
            if (ph == 1) {
                float qv[24];
#pragma unroll
                for (int j = 0; j < 3; j++) {
                    const float4 a = *reinterpret_cast<const float4*>(s_q + j * 64 + c * 8);
                    const float4 bq = *reinterpret_cast<const float4*>(s_q + j * 64 + c * 8 + 4);
                    qv[j * 8 + 0] = a.x; qv[j * 8 + 1] = a.y; qv[j * 8 + 2] = a.z; qv[j * 8 + 3] = a.w;
                    qv[j * 8 + 4] = bq.x; qv[j * 8 + 5] = bq.y; qv[j * 8 + 6] = bq.z; qv[j * 8 + 7] = bq.w;
                }
                const float scale = 0.07216878364870322f;
#pragma unroll 1
                for (int t = 0; t < NKT; t++) {
                    const int slot = t & (NSLOT - 1);
                    mbar_wait(bar_full + 8 * slot, (t >> 4) & 1);
                    const uint32_t a = rowoff + slot * TILE_BYTES;
                    const uint4 u0 = lds128(a), u1 = lds128(a + 128), u2 = lds128(a + 256);
                    float s0 = 0.f, s1 = 0.f, s2 = 0.f, s3 = 0.f;
                    dot8(s0, s1, u0, qv); dot8(s2, s3, u1, qv + 8); dot8(s0, s1, u2, qv + 16);
                    s0 = (s0 + s1) + (s2 + s3);
#pragma unroll
                    for (int o = 1; o < 8; o <<= 1) s0 += __shfl_xor_sync(0xffffffffu, s0, o);
                    __syncwarp();
                    if (lane == 0) mbar_arrive(bar_empty + 8 * slot);
                    if (c == 0) sc[t * 4 + g] = bfr(bfr(s0) * scale);
                }
                __syncwarp();
                float4 sv = *reinterpret_cast<const float4*>(sc + lane * 4);
                m_w = warp_max(fmaxf(fmaxf(sv.x, sv.y), fmaxf(sv.z, sv.w)));
                sv.x = ex2((sv.x - m_w) * L2E); sv.y = ex2((sv.y - m_w) * L2E);
                sv.z = ex2((sv.z - m_w) * L2E); sv.w = ex2((sv.w - m_w) * L2E);
                const float l_w = warp_sum((sv.x + sv.y) + (sv.z + sv.w));
                if (lane == 0) pkt_st(p.sc->mbuf + head * 32 + sp * 8 + warp, ((uint64_t)__float_as_uint(l_w) << 32) | __float_as_uint(m_w), (uint64_t)tag << 32);
                *reinterpret_cast<float4*>(sc + lane * 4) = sv;
            }
            __syncwarp();
            float acc[24];
#pragma unroll
            for (int e = 0; e < 24; e++) acc[e] = 0.f;
            const int nt = ph ? NKT : NQT;
#pragma unroll 1
            for (int t = 0; t < nt; t++) {
                const int slot = ph ? (t & (NSLOT - 1)) : QSLOT + t;
                if (ph) mbar_wait(bar_full + 8 * slot, (t >> 4) & 1);
                const uint32_t a = rowoff + slot * TILE_BYTES;
                const uint4 u0 = lds128(a), u1 = lds128(a + 128), u2 = lds128(a + 256);
                const float p0 = sc[t * 4 + g];
                fma8(acc, u0, p0); fma8(acc + 8, u1, p0); fma8(acc + 16, u2, p0);
                __syncwarp();
                if (lane == 0) mbar_arrive(bar_empty + 8 * slot);
                if (t == NKT / 2) {
                    const uint4* q = p.sc->mbuf + head * 32 + lane;
                    uint64_t lo, hi;
                    uint32_t n = 0;
                    bool ok;
#pragma unroll 1
                    do {
                        pkt_ld(q, lo, hi);
                        ok = __all_sync(0xffffffffu, tag_ok(hi, tag));
                        if (++n > SPIN_LIMIT) __trap();
                    } while (!ok);
                    const float ms = val_of(lo), ls = __uint_as_float((uint32_t)(lo >> 32));
                    const float M = warp_max(ms);
                    fscale = ex2((m_w - M) * L2E) * __frcp_rn(warp_sum(ex2((ms - M) * L2E) * ls));
                }
                if (t == NKT - 4) mbar_wait(after(p.zero, bar_pace, odst), 0);
            }
            if (tid == 0) LST(ph ? 91 : 90);
            {
                const bool hi16 = lane & 16, hi8 = lane & 8;
                float r12[12], r6[6];
#pragma unroll
                for (int i = 0; i < 12; i++) {
                    const float send = hi16 ? acc[i] : acc[i + 12];
                    const float keep = hi16 ? acc[i + 12] : acc[i];
                    r12[i] = keep + __shfl_xor_sync(0xffffffffu, send, 16);
                }
#pragma unroll
                for (int i = 0; i < 6; i++) {
                    const float send = hi8 ? r12[i] : r12[i + 6];
                    const float keep = hi8 ? r12[i + 6] : r12[i];
                    r6[i] = (keep + __shfl_xor_sync(0xffffffffu, send, 8)) * fscale;
                }
                const int f0 = (hi16 ? 12 : 0) + (hi8 ? 6 : 0);
#pragma unroll
                for (int i = 0; i < 6; i++) {
                    const int f = f0 + i;
                    s_red[warp * DH + (f >> 3) * 64 + c * 8 + (f & 7)] = r6[i];
                }
            }
            cons_sync();
            if (ph == 0) {
                if (tid < DH) {
                    const float* r = s_red + tid;
                    ll_st1(p.sc->qbuf + (head * 4 + sp) * DH + tid,
                           ((r[0] + r[DH]) + (r[2 * DH] + r[3 * DH])) + ((r[4 * DH] + r[5 * DH]) + (r[6 * DH] + r[7 * DH])), tag);
                    const uint64_t* src = p.sc->qbuf + head * 4 * DH + tid;
                    uint64_t u0, u1, u2, u3;
                    uint32_t n = 0;
                    bool ok;
                    __nanosleep(CFG_QDELAY);
#pragma unroll 1
                    do {
                        if (n) __nanosleep(CFG_QSLEEP);
                        u0 = ll_ld1(src); u1 = ll_ld1(src + DH); u2 = ll_ld1(src + 2 * DH); u3 = ll_ld1(src + 3 * DH);
                        ok = __all_sync(0xffffffffu, tag_ok(u0, tag) && tag_ok(u1, tag) && tag_ok(u2, tag) && tag_ok(u3, tag));
                        if (++n > SPIN_LIMIT) __trap();
                    } while (!ok);
                    s_q[tid] = bfr((val_of(u0) + val_of(u1)) + (val_of(u2) + val_of(u3)));
                }
            } else {
                if (tid < 96) {
                    const float4* r = reinterpret_cast<const float4*>(s_red) + tid % 48;
                    const float4 r0 = r[0], r1 = r[48], r2 = r[96], r3 = r[144], r4 = r[192], r5 = r[240], r6 = r[288], r7 = r[336];
#define S_(c) (((r0.c + r1.c) + (r2.c + r3.c)) + ((r4.c + r5.c) + (r6.c + r7.c)))
                    in_st2(odst, pack_bf(S_(y), S_(x)), pack_bf(S_(w), S_(z)));
#undef S_
                }
                break;
            }
            cons_sync();
            if (tid == 0) LST(92);
        }
        const int t = lane & 3;
        const int arow = (lane & 7) + ((lane >> 4) << 3), ahalf = (lane >> 3) & 1;
        const uint32_t msel = s_pace[2];
        if (is_wo) {
            uint32_t wa = sbase + (warp * 16 + arow) * 128 + ((ahalf ^ (lane & 7)) << 4), oa = sbase + SM_OB + warp * 32 + t * 4;
            uint32_t pw = sbase + SM_RED + (warp * 64 + t * 16 + (lane >> 2)) * 4, pr = sbase + SM_RED + lane * 8;
            unsigned char* gdst = p.xa + xa_off(L_GATHER + (warp >> 1) % CFG_HCOPY * HCOPY_BYTES + (kg * D_MODEL + ng * 64 + lane * 2) * 2, warp & 1);
            {
                const int dim = kg * 1024 + tid * 4, oh = dim / DH;
                const unsigned char* osrc[4];
                uint2 u[4];
#pragma unroll
                for (int i = 0; i < 4; i++) { osrc[i] = p.xa + xa_off(L_O + ((oh * 4 + i) * DH + dim - oh * DH) * 2, msel); u[i] = make_uint2(SENT, SENT); }
                mbar_wait(after(p.zero, bar_tail + 8 * CFG_OGATE, osrc[0], osrc[1], osrc[2], osrc[3], wa, oa, pw, pr, gdst), 0);
                uint32_t n = 0;
#pragma unroll 1
                do {
                    if (n) __nanosleep(CFG_OSLEEP);
#pragma unroll
                    for (int i = 0; i < 4; i++) in_ld2p(osrc[i], u[i], !in_ok(u[i]));
                    if (++n > SPIN_LIMIT) __trap();
                } while (__any_sync(0xffffffffu, max(max(max(u[0].x, u[0].y), max(u[1].x, u[1].y)), max(max(u[2].x, u[2].y), max(u[3].x, u[3].y))) == SENT));
#define F_(f, c) ((f(u[0].c) + f(u[1].c)) + (f(u[2].c) + f(u[3].c)))
                sts64(sbase + SM_OB + tid * 8, pack_bf(F_(bf_hi, x), F_(bf_lo, x)), pack_bf(F_(bf_hi, y), F_(bf_lo, y)));
#undef F_
            }
            cons_sync();
            if (tid == 0) LST(93);
            float cw[4][4];
#pragma unroll
            for (int i = 0; i < 4; i++) cw[i][0] = cw[i][1] = cw[i][2] = cw[i][3] = 0.f;
            uint32_t ov[NWP][2];
#pragma unroll
            for (int j = 0; j < NWP; j++) { ov[j][0] = lds32(oa + j * 256); ov[j][1] = lds32(oa + j * 256 + 16); }
#pragma unroll
            for (int j = 0; j < NWP; j++) {
                mbar_wait(CFG_DEPLAST && j == NWP - 1 ? after(p.zero, bar_tail + 8 * j, cw[3][0]) : bar_tail + 8 * j, 0);
                uint32_t a[4][4];
#pragma unroll
                for (int i = 0; i < 4; i++) ldsm_x4_t(a[i], (wa ^ (i << 5)) + j * WPIECE);
#pragma unroll
                for (int i = 0; i < 4; i++) mma_bf16(cw[i], a[i], ov[j][0], ov[j][1]);
            }
#define SEL_(e) ((t & 2) ? ((t & 1) ? cw[3][e] : cw[2][e]) : ((t & 1) ? cw[1][e] : cw[0][e]))
            sts32(pw, SEL_(0)); sts32(pw + 32, SEL_(2));
#undef SEL_
            cons_sync();
            if (warp < 2 * CFG_HCOPY) {
                float2 r[8];
#pragma unroll
                for (int i = 0; i < 8; i++) r[i] = lds64f(pr + i * 256);
#define S_(c) (((r[0].c + r[1].c) + (r[2].c + r[3].c)) + ((r[4].c + r[5].c) + (r[6].c + r[7].c)))
                in_st1(gdst, __uint_as_float(pack_bf(S_(y), S_(x))));
#undef S_
            }
            if (tid == 0) LST(94);
        } else if (is_ffn) {
            uint32_t w13a = sbase + (warp * 16 + arow) * 64 + ((ahalf ^ (lane >> 1 & 3)) << 4);
            uint32_t red_dst = sbase + SM_RED + tid * 16;
            uint32_t stat = sbase + SM_MISC + warp * 8;
            cons_sync();
            uint32_t aw[NUP][4][4];
            auto load_w13 = [&](int i, uint32_t bar) {
                mbar_wait(bar + 8 * i, 0);
#pragma unroll
                for (int k = 0; k < 4; k++) ldsm_x4_t(aw[i][k], (w13a ^ (k << 5 & 32)) + i * WPIECE + (k >> 1) * (WPIECE / 2));
            };
            uint32_t hp0, hp1;
            {
                const unsigned char* gsrc[NG];
                uint2 u[NG];
#pragma unroll
                for (int i = 0; i < NG; i++) { u[i] = make_uint2(0, 0); gsrc[i] = p.xa + xa_off(L_GATHER + rr % CFG_HCOPY * HCOPY_BYTES + (i * D_MODEL + hcol) * 2, msel); }
#pragma unroll
                for (int i = 0; i < CFG_HGATE; i++) load_w13(i, after(p.zero, bar_tail, gsrc[0], gsrc[1], gsrc[2], gsrc[3], gsrc[4], gsrc[5], w13a, red_dst, stat));
                LSC(0);
#pragma unroll
                for (int i = 0; i < NG; i++) in_ld2p(gsrc[i], u[i], lane < 4 * NUP && !ABL_NOH);
                if (CFG_HSHADOW) load_w13(CFG_HGATE, bar_tail);
                LSCD(1, u[0].x ^ u[1].x ^ u[2].x ^ u[3].x ^ u[4].x ^ u[5].x);
                uint32_t n = 0;
#pragma unroll 1
                while (__any_sync(0xffffffffu, max(max(max(u[0].x, u[0].y), max(u[1].x, u[1].y)), max(max(max(u[2].x, u[2].y), max(u[3].x, u[3].y)),
                                                                                                    max(max(u[4].x, u[4].y), max(u[5].x, u[5].y)))) == SENT)) {
#pragma unroll
                    for (int i = 0; i < NG; i++) in_ld2p(gsrc[i], u[i], !in_ok(u[i]));
                    if (++n > SPIN_LIMIT) __trap();
                }
                if (tid == 96) LST(100);
                LSC(2);
#pragma unroll
                for (int i = CFG_HGATE + CFG_HSHADOW; i < HPRE; i++) load_w13(i, bar_tail);
#define F_(f, c) (f(xres.c) + bfr(((f(u[0].c) + f(u[1].c)) + (f(u[2].c) + f(u[3].c))) + (f(u[4].c) + f(u[5].c))))
                hp0 = pack_bf(F_(bf_hi, x), F_(bf_lo, x));
                hp1 = pack_bf(F_(bf_hi, y), F_(bf_lo, y));
#undef F_
            }
            {
                uint32_t b0[NUP], b1[NUP];
                float cf[4][4], cs[2][4];
#pragma unroll
                for (int e = 0; e < 4; e++) cf[0][e] = cf[1][e] = cf[2][e] = cf[3][e] = cs[0][e] = cs[1][e] = 0.f;
#pragma unroll
                for (int i = 0; i < NUP; i++) {
                    const uint32_t h0 = __shfl_sync(0xffffffffu, hp0, i * 4 + t), h1 = __shfl_sync(0xffffffffu, hp1, i * 4 + t);
                    b0[i] = (lane & 4) ? 0x3f803f80u : h0;
                    b1[i] = (lane & 4) ? 0x3f803f80u : h1;
                    const uint32_t sa[4] = {h0, h0, h1, h1};
                    mma_bf16(cs[i & 1], sa, b0[i], b1[i]);
                }
                auto mma_w13 = [&](int i) {
#pragma unroll
                    for (int k = 0; k < 4; k++) mma_bf16(cf[k], aw[i][k], b0[i], b1[i]);
                };
                if (lane == 0) sts64(stat, __float_as_uint(cs[0][0] + cs[1][0]), __float_as_uint(cs[0][1] + cs[1][1]));
                __syncwarp();
                if (lane == 0) mbar_arrive(bar_h);
#pragma unroll
                for (int i = 0; i < HPRE; i++) mma_w13(i);
                LSC(3);
#pragma unroll
                for (int i = HPRE; i < NUP - 1; i++) { load_w13(i, bar_tail); mma_w13(i); }
                LSC(4);
#pragma unroll
                for (int m = 0; m < 2; m++) {
                    mbar_wait(CFG_DEPLAST && m ? after(p.zero, bar_tail + 8 * NUP, cf[1][0]) : bar_tail + 8 * (NUP - 1 + m), 0);
#pragma unroll
                    for (int k = 2 * m; k < 2 * m + 2; k++) ldsm_x4_t(aw[NUP - 1][k], (w13a ^ (k << 5 & 32)) + (NUP - 1) * WPIECE + m * (WPIECE / 2));
#pragma unroll
                    for (int k = 2 * m; k < 2 * m + 2; k++) mma_bf16(cf[k], aw[NUP - 1][k], b0[NUP - 1], b1[NUP - 1]);
                }
                LSC(6);
#define SEL_(k, e) ((t & 2) ? ((t & 1) ? cf[k + 1][e + 2] : cf[k + 1][e]) : ((t & 1) ? cf[k][e + 2] : cf[k][e]))
                asm volatile("st.shared.v4.f32 [%0], {%1, %2, %3, %4};" ::"r"(red_dst), "f"(SEL_(0, 0)), "f"(SEL_(0, 1)), "f"(SEL_(2, 0)), "f"(SEL_(2, 1)) : "memory");
#undef SEL_
            }
            LSC(7);
            asm volatile("bar.arrive 5, 288;" ::: "memory");
        }
        if (is_out) {
            uint32_t w2a = sbase + SM_W2 + (warp * 32 + arow) * 32 + ((ahalf ^ (lane >> 2 & 1)) << 4);
            uint32_t ydst = sbase + SM_HN + ((t & 1) * 8 + (lane >> 2)) * 48 + warp * 4;
            const unsigned char* asrc = p.xa + xa_off(L_ACT, msel) + warp * 64 + t * 16;
            const uint32_t bar_w2 = after(p.zero, bar_tail + 8 * NWP, w2a, ydst, asrc);
            uint32_t a[NDP][2][4];
            auto load_w2 = [&](int i) {
                mbar_wait(bar_w2 + 8 * i, 0);
                ldsm_x4_t(a[i][0], w2a + i * PIECE); ldsm_x4_t(a[i][1], w2a + i * PIECE + 512);
            };
#pragma unroll
            for (int i = 0; i < CFG_AGATE; i++) load_w2(i);
            uint4 u[NDP];
            LSC(0);
#pragma unroll
            for (int i = 0; i < NDP; i++) u[i] = in_ld4(asrc + i * 512);
            int have = CFG_AGATE;
            auto try_w2 = [&]() {
#pragma unroll
                for (int i = CFG_AGATE; i < NDP; i++)
                    if (have == i && __all_sync(0xffffffffu, mbar_test(bar_tail + 8 * (NWP + i), 0))) {
                        ldsm_x4_t(a[i][0], w2a + i * PIECE); ldsm_x4_t(a[i][1], w2a + i * PIECE + 512);
                        have++;
                    }
            };
            try_w2();
            uint32_t n = 0;
#pragma unroll 1
            while (true) {
                uint32_t m[NDP];
#pragma unroll
                for (int i = 0; i < NDP; i++) m[i] = max(max(u[i].x, u[i].y), max(u[i].z, u[i].w));
                if (!__any_sync(0xffffffffu, max(max(max(m[0], m[1]), m[2]), max(max(m[3], m[4]), m[5])) == SENT)) break;
#pragma unroll
                for (int i = 0; i < NDP; i++) in_ld4p(asrc + i * 512, u[i], m[i] == SENT);
                try_w2();
                if (++n > SPIN_LIMIT) __trap();
            }
            LSC(12);
            if (tid == 96) LST(118);
            float cy[4][4];
#pragma unroll
            for (int e = 0; e < 4; e++) cy[0][e] = cy[1][e] = cy[2][e] = cy[3][e] = 0.f;
#pragma unroll
            for (int i = 0; i < NDP; i++) {
                if (i >= CFG_AGATE && i >= have) load_w2(i);
                mma_bf16(cy[2 * (i & 1)], a[i][0], u[i].x, u[i].y);
                mma_bf16(cy[2 * (i & 1) + 1], a[i][1], u[i].z, u[i].w);
            }
            const float y = (t & 1) ? (cy[0][2] + cy[1][2]) + (cy[2][2] + cy[3][2]) : (cy[0][0] + cy[1][0]) + (cy[2][0] + cy[3][0]);
            if (t < 2) sts32(ydst, y);
            LSC(13);
            asm volatile("bar.arrive 5, 288;" ::: "memory");
        }
    }
}

typedef CUresult (*EncodeTiledFn)(CUtensorMap*, CUtensorMapDataType, cuuint32_t, void*, const cuuint64_t*, const cuuint64_t*,
                                  const cuuint32_t*, const cuuint32_t*, CUtensorMapInterleave, CUtensorMapSwizzle,
                                  CUtensorMapL2promotion, CUtensorMapFloatOOBfill);

void make_map(EncodeTiledFn fn, CUtensorMap* tm, const void* w, const int (&d)[5], const int (&st)[4], const int (&bx)[5],
              CUtensorMapSwizzle sw, int promo) {
    cuuint64_t dims[5], strides[4];
    cuuint32_t box[5], estr[5];
    for (int i = 0; i < 5; i++) { dims[i] = (cuuint64_t)d[i]; box[i] = (cuuint32_t)bx[i]; estr[i] = 1; }
    for (int i = 0; i < 4; i++) strides[i] = (cuuint64_t)st[i];
    fn(tm, CU_TENSOR_MAP_DATA_TYPE_BFLOAT16, 5, const_cast<void*>(w), dims, strides, box, estr, CU_TENSOR_MAP_INTERLEAVE_NONE, sw,
       (CUtensorMapL2promotion)promo, CU_TENSOR_MAP_FLOAT_OOB_FILL_NONE);
}

}

extern "C" void kernel_launch(void* const* d_in, const int* in_sizes, int n_in, void* d_out, int out_size) {
    (void)in_sizes; (void)n_in; (void)out_size;
    static EncodeTiledFn encode = nullptr;
    static Scratch* scratch = nullptr;
    static unsigned char* xarea = nullptr;
    static double tscale = 1.0;
    if (!encode) {
        void* sp = nullptr;
        cudaGetSymbolAddress(&sp, g_scratch);
        scratch = reinterpret_cast<Scratch*>(sp);
        cudaGetSymbolAddress(&sp, g_xarea);
        xarea = reinterpret_cast<unsigned char*>((reinterpret_cast<uintptr_t>(sp) + XA_ALIGN - 1) / XA_ALIGN * XA_ALIGN);
        void* fn = nullptr;
        cudaDriverEntryPointQueryResult st;
        cudaGetDriverEntryPoint("cuTensorMapEncodeTiled", &fn, cudaEnableDefault, &st);
        encode = reinterpret_cast<EncodeTiledFn>(fn);
        int dev = 0, khz = 0, bits = 0;
        cudaGetDevice(&dev);
        cudaDeviceGetAttribute(&khz, cudaDevAttrMemoryClockRate, dev);
        cudaDeviceGetAttribute(&bits, cudaDevAttrGlobalMemoryBusWidth, dev);
        if (khz > 0 && bits > 0) tscale = (2619000.0 * 5120.0) / ((double)khz * bits);
        cudaFuncSetAttribute(fused_decode_kernel, cudaFuncAttributeMaxDynamicSharedMemorySize, SM_TOTAL);
    }
    KParams p;
    p.x = (const __nv_bfloat16*)d_in[0];
    p.k = (const __nv_bfloat16*)d_in[1];
    p.v = (const __nv_bfloat16*)d_in[2];
    p.wq = (const __nv_bfloat16*)d_in[3];
    p.out = (__nv_bfloat16*)d_out;
    p.sc = scratch;
    p.xa = xarea;
    p.zero = 0;
    p.t_first = (uint32_t)(4 * CFG_OFF0 * tscale);
    p.t_step = (uint32_t)(CFG_T * tscale);
    p.t_smax = (uint32_t)(CFG_SMAX * tscale);
    p.t_lat = (uint32_t)(4 * (450 + (CFG_LAT - 450) * tscale));
    TMaps tm;
    constexpr int R1 = FF * 2, R2 = D_MODEL * 2;
    make_map(encode, &tm.wo, d_in[4], {D_MODEL, NHEAD * DH, 1, 1, 1}, {R2, R2, R2, R2}, {64, 128, 1, 1, 1}, CU_TENSOR_MAP_SWIZZLE_128B, CFG_PROMO_WO);
    make_map(encode, &tm.w1, d_in[6], {FF, 2, 20, 2, 8}, {R1, 4 * R1, 2 * R1, 80 * R1}, {32, 2, 4, 2, 8}, CU_TENSOR_MAP_SWIZZLE_64B, CFG_PROMO_W13);
    make_map(encode, &tm.w3, d_in[7], {FF, 2, 20, 2, 8}, {R1, 4 * R1, 2 * R1, 80 * R1}, {32, 2, 4, 2, 8}, CU_TENSOR_MAP_SWIZZLE_64B, CFG_PROMO_W13);
    make_map(encode, &tm.w2, d_in[8], {D_MODEL, FF, 1, 1, 1}, {R2, R2, R2, R2}, {16, 256, 1, 1, 1}, CU_TENSOR_MAP_SWIZZLE_32B, CFG_PROMO_W2);
    fused_decode_kernel<<<NCTA, NTHREADS, SM_TOTAL, cudaStreamPerThread>>>(p, tm);
}
```

```cpp
#include <cuda_runtime.h>
#include <cuda_bf16.h>
#include <cuda.h>
#include <stdint.h>
#include <math.h>

namespace {

constexpr int D_MODEL = 640;
constexpr int NHEAD = 32;
constexpr int DH = 192;
constexpr int SK = 32768;
constexpr int WIN = 4096;
constexpr int FF = 1536;

constexpr int NCTA = 128;
constexpr int NCONS = 256;
constexpr int NTHREADS = NCONS + 96;
constexpr int ROW_BYTES = DH * 2;
constexpr int TILE_BYTES = 32 * ROW_BYTES;
constexpr int NSLOT = 16;
constexpr int NKT = 32;
constexpr int NQT = 5;
constexpr int QSLOT = NSLOT - NQT;
constexpr int NWO = 60;
constexpr int NG = 6;
constexpr int NFFN = 48;
constexpr int OUT0 = 24;
constexpr int NWP = 8;
constexpr int NUP = 5;
constexpr int WPIECE = 16384;
constexpr int NDP = 6;
constexpr int PIECE = 8192;
constexpr int NTAIL = NWP + NDP;
constexpr int N_TAIL0 = 2 * NKT;

#define CFG_NPROBE 4
#define CFG_OGATE 1
#define CFG_OSLEEP 100
#define CFG_PROMO_WO 2
#define CFG_PROMO_W13 2
#define CFG_PROMO_W2 2
#define CFG_PROBE_AT 6
#define CFG_QDELAY 900
#define CFG_QSLEEP 400
#define CFG_BOUNDED_MBAR 0
#define CFG_T 1900
#define CFG_OFF0 2000
#define CFG_TWO 296
#define CFG_TFF 234
#define CFG_TW2 140
#define CFG_HGATE 1
#define ABL_NOH 0
#define CFG_HCOPY 2
#define CFG_MA 16
#define CFG_MB 40
#define CFG_ADAPT 58
#define CFG_LAT 1340
#define CFG_SMAX 1940
#define CFG_PSLEEP 1000
#define CFG_HSHADOW 0
#define CFG_T4 122
#define CFG_HPOST 0
constexpr int HPRE = CFG_HGATE + CFG_HSHADOW + CFG_HPOST;
#define CFG_KEEP 150
#define CFG_KEEP_AT 7
#define CFG_W2AT 1200
#define CFG_AGATE 4
#define CFG_DEPLAST 0
#define CFG_PREQ 1
#define CFG_PREM 1
#define CFG_PLINES 8
#define CFG_WQUNROLL_ 1
constexpr int CFG_WQUNROLL = CFG_WQUNROLL_;
#define CFG_QDELAY2 700
#define CFG_PDELAY 2500
#define CFG_PDELAY_LAST 250
#define CFG_PREPART 3
#define CFG_OGATE2 5
#define CFG_PROMO_KV 2
#define CFG_PDELAY_STEP 650
#define CFG_OGATE3 5
#define CFG_ASHADOW 1
constexpr int APRE = CFG_AGATE + CFG_ASHADOW;
#define CFG_GAPWO 0
#define CFG_GAPFF 170
#define CFG_CAP 5

constexpr int SM_RING = 0;
constexpr int SM_W2 = NWP * WPIECE;
constexpr int SM_Q = SM_RING + NSLOT * TILE_BYTES;
constexpr int SM_RED = SM_Q + NHEAD * ROW_BYTES;
constexpr int SM_HN = SM_RED + 4096;
constexpr int SM_MISC = SM_HN + D_MODEL * 2;
constexpr int SM_BAR = SM_MISC + 128;
constexpr int SM_TOTAL = SM_BAR + 512;
static_assert(SM_TOTAL <= 232448, "shared memory");

struct __align__(128) Scratch {
    uint4 part[NHEAD * 4 * NCTA * 8];
    uint64_t q1[NHEAD * 4 * DH];
    uint4 q2[NHEAD * 32];
    uint32_t epoch;
    uint32_t pad[31];
    unsigned long long pace[2];
};
__device__ Scratch g_scratch;
constexpr int XA_ALIGN = 1 << 20;
constexpr uint32_t SENT = 0xffffffffu;
constexpr int L_GATHER = 0;
constexpr int HCOPY_BYTES = NG * D_MODEL * 2;
constexpr int L_O = 9 * 4096;
constexpr int L_ACT = 30 * 4096;
constexpr int L_PROBE = 32 * 4096;
static_assert(2 * (L_PROBE + NCTA * 1024) <= XA_ALIGN, "");
__device__ unsigned char g_xarea[2 * XA_ALIGN];
__device__ __forceinline__ uint32_t xa_off(uint32_t l, uint32_t side) {
    const uint32_t k = l >> 12;
    return (2 * k + ((side ^ k ^ (k >> 3) ^ (k >> 4) ^ (k >> 6)) & 1)) * 4096 + (l & 4095);
}

__device__ __forceinline__ uint32_t o_off(uint32_t r) { return L_O + (r >> 7) % NG * 2048 + (r >> 7) / NG * 256 + (r & 127) * 2; }

#define LST(i) do { } while (0)
#define LSC(i) do { } while (0)
#define LSCD(i, v) do { } while (0)
constexpr uint32_t SPIN_LIMIT = CFG_BOUNDED_MBAR ? 1u << 14 : 1u << 22;

__device__ __forceinline__ uint32_t now_q() { uint32_t t; asm volatile("mov.u32 %0, %globaltimer_lo;" : "=r"(t)); return t * 4; }
__device__ __forceinline__ void wait_until(uint32_t due) {
#pragma unroll 1
    for (int n = 0; n < 4096 && (int)(now_q() - due) < 0; n++) { }
}
__device__ __forceinline__ void sleep_until(uint32_t due) {
#pragma unroll 1
    for (int n = 0; n < 4096 && (int)(now_q() - due) < 0; n++) __nanosleep(200);
}
__device__ __forceinline__ uint32_t smem_u32(const void* p) { return (uint32_t)__cvta_generic_to_shared(p); }
__device__ __forceinline__ void mbar_init(uint32_t bar, uint32_t cnt) {
    asm volatile("mbarrier.init.shared::cta.b64 [%0], %1;" ::"r"(bar), "r"(cnt) : "memory");
}
__device__ __forceinline__ void mbar_expect_tx(uint32_t bar, uint32_t bytes) {
    asm volatile("mbarrier.arrive.expect_tx.shared::cta.b64 _, [%0], %1;" ::"r"(bar), "r"(bytes) : "memory");
}
__device__ __forceinline__ void mbar_arrive(uint32_t bar) {
    asm volatile("mbarrier.arrive.shared::cta.b64 _, [%0];" ::"r"(bar) : "memory");
}
__device__ __forceinline__ bool mbar_test(uint32_t bar, uint32_t parity) {
    uint32_t ok;
    asm volatile("{\n.reg .pred p;\nmbarrier.test_wait.parity.shared::cta.b64 p, [%1], %2;\nselp.u32 %0, 1, 0, p;\n}"
                 : "=r"(ok) : "r"(bar), "r"(parity) : "memory");
    return ok;
}
__device__ __forceinline__ void mbar_wait(uint32_t bar, uint32_t parity) {
    asm volatile("{\n.reg .pred p;\nW_%=:\nmbarrier.try_wait.parity.shared::cta.b64 p, [%0], %1;\n@!p bra W_%=;\n}" ::"r"(bar), "r"(parity) : "memory");
}
__device__ __forceinline__ void tma_tile(uint32_t dst, const CUtensorMap* tm, int c1, uint32_t bar, uint64_t pol) {
    asm volatile("cp.async.bulk.tensor.5d.shared::cluster.global.mbarrier::complete_tx::bytes.L2::cache_hint [%0], [%1, {%4, %3, %4, %4, %4}], [%2], %5;"
                 ::"r"(dst), "l"(reinterpret_cast<uint64_t>(tm)), "r"(bar), "r"(c1), "r"(0), "l"(pol) : "memory");
}
__device__ __forceinline__ void tma_5d(uint32_t dst, const CUtensorMap* tm, int c0, int c1, int c2, int c4, uint32_t bar) {
    asm volatile("cp.async.bulk.tensor.5d.shared::cluster.global.mbarrier::complete_tx::bytes [%0], [%1, {%3, %4, %5, %7, %6}], [%2];"
                 ::"r"(dst), "l"(reinterpret_cast<uint64_t>(tm)), "r"(bar), "r"(c0), "r"(c1), "r"(c2), "r"(c4), "r"(0) : "memory");
}
__device__ __forceinline__ uint32_t bits(uint32_t v) { return v; }
__device__ __forceinline__ uint32_t bits(float v) { return __float_as_uint(v); }
__device__ __forceinline__ uint32_t bits(const void* v) { return (uint32_t)(uintptr_t)v ^ (uint32_t)((uintptr_t)v >> 32); }
template <class... T> __device__ __forceinline__ uint32_t after(uint32_t zero, uint32_t bar, T... v) { return bar | ((bits(v) ^ ...) & zero); }
__device__ __forceinline__ void sts32(uint32_t a, float v) { asm volatile("st.shared.f32 [%0], %1;" ::"r"(a), "f"(v) : "memory"); }
__device__ __forceinline__ void sts64(uint32_t a, uint32_t x, uint32_t y) { asm volatile("st.shared.v2.u32 [%0], {%1, %2};" ::"r"(a), "r"(x), "r"(y) : "memory"); }
__device__ __forceinline__ void cons_sync() { asm volatile("bar.sync 1, 256;" ::: "memory"); }

__device__ __forceinline__ uint4 lds128(uint32_t a) {
    uint4 v;
    asm volatile("ld.shared.v4.u32 {%0,%1,%2,%3}, [%4];" : "=r"(v.x), "=r"(v.y), "=r"(v.z), "=r"(v.w) : "r"(a));
    return v;
}
__device__ __forceinline__ float4 lds128f(uint32_t a) {
    float4 v;
    asm volatile("ld.shared.v4.f32 {%0,%1,%2,%3}, [%4];" : "=f"(v.x), "=f"(v.y), "=f"(v.z), "=f"(v.w) : "r"(a) : "memory");
    return v;
}
__device__ __forceinline__ float2 lds64f(uint32_t a) {
    float2 v;
    asm volatile("ld.shared.v2.f32 {%0,%1}, [%2];" : "=f"(v.x), "=f"(v.y) : "r"(a) : "memory");
    return v;
}
__device__ __forceinline__ uint32_t lds32(uint32_t a) {
    uint32_t v;
    asm volatile("ld.shared.u32 %0, [%1];" : "=r"(v) : "r"(a));
    return v;
}
__device__ __forceinline__ void ldsm_x4(uint32_t* r, uint32_t a) {
    asm volatile("ldmatrix.sync.aligned.m8n8.x4.shared.b16 {%0,%1,%2,%3}, [%4];"
                 : "=r"(r[0]), "=r"(r[1]), "=r"(r[2]), "=r"(r[3]) : "r"(a));
}
__device__ __forceinline__ void ldsm_x4_t(uint32_t* r, uint32_t a) {
    asm volatile("ldmatrix.sync.aligned.m8n8.x4.trans.shared.b16 {%0,%1,%2,%3}, [%4];"
                 : "=r"(r[0]), "=r"(r[1]), "=r"(r[2]), "=r"(r[3]) : "r"(a));
}
__device__ __forceinline__ void mma_bf16(float* c, const uint32_t* a, uint32_t b0, uint32_t b1) {
    asm volatile("mma.sync.aligned.m16n8k16.row.col.f32.bf16.bf16.f32 {%0,%1,%2,%3}, {%4,%5,%6,%7}, {%8,%9}, {%0,%1,%2,%3};"
                 : "+f"(c[0]), "+f"(c[1]), "+f"(c[2]), "+f"(c[3]) : "r"(a[0]), "r"(a[1]), "r"(a[2]), "r"(a[3]), "r"(b0), "r"(b1));
}
__device__ __forceinline__ float bf_lo(uint32_t u) { return __uint_as_float(u << 16); }
__device__ __forceinline__ float bf_hi(uint32_t u) { return __uint_as_float(u & 0xffff0000u); }
__device__ __forceinline__ uint32_t pack_bf(float hi, float lo) { uint32_t r; asm("cvt.rn.bf16x2.f32 %0, %1, %2;" : "=r"(r) : "f"(hi), "f"(lo)); return r; }
__device__ __forceinline__ float bfr(float x) { return __uint_as_float(pack_bf(x, 0.f)); }

__device__ __forceinline__ uint64_t pk(float v, uint32_t tag) { return ((uint64_t)tag << 32) | (uint64_t)__float_as_uint(v); }
__device__ __forceinline__ void ll_st1(uint64_t* p, float a, uint32_t tag) {
    asm volatile("st.relaxed.gpu.global.b64 [%0], %1;" ::"l"(p), "l"(pk(a, tag)) : "memory");
}
__device__ __forceinline__ uint4 ll_ld2(const uint4* p) {
    uint4 v;
    asm volatile("{\n.reg .b64 a, b;\nld.relaxed.gpu.global.v2.b64 {a, b}, [%4];\nmov.b64 {%0, %1}, a;\nmov.b64 {%2, %3}, b;\n}"
                 : "=r"(v.x), "=r"(v.y), "=r"(v.z), "=r"(v.w) : "l"(p) : "memory");
    return v;
}
__device__ __forceinline__ uint64_t ll_ld1(const uint64_t* p) {
    uint64_t v;
    asm volatile("ld.relaxed.gpu.global.b64 %0, [%1];" : "=l"(v) : "l"(p) : "memory");
    return v;
}
__device__ __forceinline__ uint32_t in_word(float v) {
    uint32_t r;
    asm("min.u32 %0, %1, 0xfffffffe;" : "=r"(r) : "r"(__float_as_uint(v)));
    return r;
}
__device__ __forceinline__ void in_st1(void* p, float v) {
    asm volatile("st.relaxed.gpu.global.u32 [%0], %1;" ::"l"(p), "r"(in_word(v)) : "memory");
}
__device__ __forceinline__ void in_st4(void* p, uint32_t a, uint32_t b, uint32_t c, uint32_t d) {
    asm volatile("st.relaxed.gpu.global.v4.u32 [%0], {%1, %2, %3, %4};" ::"l"(p), "r"(a), "r"(b), "r"(c), "r"(d) : "memory");
}
__device__ __forceinline__ uint32_t in_ld1(const void* p) {
    uint32_t v;
    asm volatile("ld.relaxed.gpu.global.u32 %0, [%1];" : "=r"(v) : "l"(p) : "memory");
    return v;
}
__device__ __forceinline__ uint4 in_ld4(const void* p) {
    uint4 v;
    asm volatile("ld.relaxed.gpu.global.v4.u32 {%0, %1, %2, %3}, [%4];" : "=r"(v.x), "=r"(v.y), "=r"(v.z), "=r"(v.w) : "l"(p) : "memory");
    return v;
}
__device__ __forceinline__ void in_st2(void* p, uint32_t a, uint32_t b) {
    asm volatile("st.relaxed.gpu.global.v2.u32 [%0], {%1, %2};" ::"l"(p), "r"(min(a, SENT - 1)), "r"(min(b, SENT - 1)) : "memory");
}
__device__ __forceinline__ void in_ld2p(const void* p, uint2& v, bool on) {
    asm volatile("{\n.reg .pred q;\nsetp.ne.u32 q, %3, 0;\n@q ld.relaxed.gpu.global.v2.u32 {%0, %1}, [%2];\n}"
                 : "+r"(v.x), "+r"(v.y) : "l"(p), "r"((uint32_t)on) : "memory");
}
__device__ __forceinline__ bool in_ok(const uint2& v) { return max(v.x, v.y) != SENT; }
__device__ __forceinline__ void in_ld4p(const void* p, uint4& v, bool on) {
    asm volatile("{\n.reg .pred q;\nsetp.ne.u32 q, %5, 0;\n@q ld.relaxed.gpu.global.v4.u32 {%0, %1, %2, %3}, [%4];\n}"
                 : "+r"(v.x), "+r"(v.y), "+r"(v.z), "+r"(v.w) : "l"(p), "r"((uint32_t)on) : "memory");
}
__device__ __forceinline__ bool tag_ok(uint64_t v, uint32_t tag) { return (uint32_t)(v >> 32) == tag; }
__device__ __forceinline__ float val_of(uint64_t v) { return __uint_as_float((uint32_t)v); }
__device__ __forceinline__ void pkt_st(uint4* p, uint32_t x, uint32_t y, uint32_t z, uint32_t w) {
    asm volatile("{\n.reg .b128 t;\n.reg .b64 a, b;\nmov.b64 a, {%1, %2};\nmov.b64 b, {%3, %4};\nmov.b128 t, {a, b};\nst.relaxed.gpu.global.b128 [%0], t;\n}"
                 ::"l"(p), "r"(x), "r"(y), "r"(z), "r"(w) : "memory");
}
__device__ __forceinline__ void pkt_ldp(const uint4* p, uint4& v, bool on) {
    asm volatile("{\n.reg .pred q;\n.reg .b128 t;\n.reg .b64 a, b;\nsetp.ne.u32 q, %5, 0;\nmov.b64 a, {%0, %1};\nmov.b64 b, {%2, %3};\nmov.b128 t, {a, b};\n"
                 "@q ld.relaxed.gpu.global.b128 t, [%4];\nmov.b128 {a, b}, t;\nmov.b64 {%0, %1}, a;\nmov.b64 {%2, %3}, b;\n}"
                 : "+r"(v.x), "+r"(v.y), "+r"(v.z), "+r"(v.w) : "l"(p), "r"((uint32_t)on) : "memory");
}

__device__ __forceinline__ float sqrt_fast(float x) { float r; asm("sqrt.approx.ftz.f32 %0, %1;" : "=f"(r) : "f"(x)); return r; }
__device__ __forceinline__ float rcp_fast(float x) { float r; asm("rcp.approx.ftz.f32 %0, %1;" : "=f"(r) : "f"(x)); return r; }
__device__ __forceinline__ float ex2(float x) { float r; asm("ex2.approx.ftz.f32 %0, %1;" : "=f"(r) : "f"(x)); return r; }
constexpr float L2E = 1.4426950408889634f;
__device__ __forceinline__ void ln_finish(float s1, float s2, float& mean_b, float& inv_den) {
    const float mean = s1 * (1.0f / D_MODEL);
    const float var = fmaxf(fmaf(-mean, mean, s2 * (1.0f / D_MODEL)), 0.f);
    mean_b = bfr(mean);
    inv_den = rcp_fast(bfr(sqrt_fast(bfr(bfr(var) + 1e-5f))));
}
__device__ __forceinline__ float ln_apply(float v, float mean_b, float inv_den) { return bfr(bfr(v - mean_b) * inv_den); }

struct KParams {
    const __nv_bfloat16* wq;
    uint32_t t_first;
    uint32_t t_step;
    const __nv_bfloat16* x;
    Scratch* sc;
    unsigned char* xa;
    __nv_bfloat16* out;
    uint32_t t_smax;
    uint32_t t_lat;
    uint32_t zero;
};
struct TMaps { CUtensorMap k, v, wo, w1, w3, w2; };

__global__ void __launch_bounds__(NTHREADS, 1)
fused_decode_kernel(const KParams p, const __grid_constant__ TMaps tm) {
    extern __shared__ __align__(1024) unsigned char smem[];
    const uint32_t sbase = smem_u32(smem);
    const int tid = threadIdx.x;
    const int b = blockIdx.x;
    const int head = b >> 2, sp = b & 3;
    {
        if (tid < 192) {
            const int rg = tid / 24, ch = tid - rg * 24;
            const char* src = reinterpret_cast<const char*>(p.wq) + (size_t)(sp * 160 + rg) * (NHEAD * DH * 2) + head * ROW_BYTES + ch * 16;
            uint32_t dst = sbase + SM_RING + QSLOT * TILE_BYTES + ((tid ^ (tid >> 3 & 7)) << 4);
#pragma unroll 1
            for (int i = 0; i < 20; i++) {
                asm volatile("cp.async.cg.shared.global [%0], [%1], 16;" ::"r"(dst), "l"(src) : "memory");
                dst += 8 * ROW_BYTES;
                src += (size_t)8 * (NHEAD * DH * 2);
            }
        }
    }
    const int warp = __shfl_sync(0xffffffffu, tid >> 5, 0), lane = tid & 31;
    const int rr = b >> 1;
    const bool is_wo = !(b & 1) && rr < NWO, is_ffn = (b & 1) && rr < NFFN, is_out = !(b & 1) && rr >= OUT0;
    const int kg = min(rr / 10, NG - 1), ng = rr % 10;
    const uint32_t bar_full = sbase + SM_BAR;
    const uint32_t bar_empty = sbase + SM_BAR + 128;
    const uint32_t bar_tail = sbase + SM_BAR + 256;
    const uint32_t bar_h = bar_tail + 8 * NTAIL;
    const uint32_t bar_set = bar_h + 8;
    const uint32_t bar_pace = bar_h + 16;
    const uint32_t bar_q = bar_h + 24;
    const uint32_t bar_part = bar_h + 32;
    volatile uint32_t* s_pace = reinterpret_cast<volatile uint32_t*>(smem + SM_MISC + 64);

    if (warp == 8) {
        const uint32_t c_start = now_q();
        uint64_t pol_stream;
        asm volatile("createpolicy.fractional.L2::evict_first.b64 %0, 1.0;" : "=l"(pol_stream));
        if (lane == 0) {
#pragma unroll 1
            for (int i = 0; i < NSLOT; i++) { mbar_init(bar_full + 8 * i, 1); mbar_init(bar_empty + 8 * i, 1); }
#pragma unroll 1
            for (int i = 0; i < NTAIL + 5; i++) mbar_init(bar_tail + 8 * i, i == NTAIL ? 8 : i == NTAIL + 3 ? 4 : 1);
            asm volatile("fence.mbarrier_init.release.cluster;" ::: "memory");
        }
        __syncwarp();
        asm volatile("bar.arrive 2, 288;" ::: "memory");
        asm volatile("bar.arrive 3, 64;" ::: "memory");
        asm volatile("bar.arrive 4, 64;" ::: "memory");
        if (lane >= 1 && lane <= 6) asm volatile("prefetch.tensormap [%0];" ::"l"(reinterpret_cast<uint64_t>(&tm.k + (lane - 1))) : "memory");
        if (lane == 0) {
            uint32_t due = c_start + p.t_first, step = p.t_step;
#pragma unroll 1
            for (int n = 0; n < N_TAIL0; n++) {
                const int slot = n & (NSLOT - 1);
                const int use = (n >> 4) + (slot >= QSLOT);
                if (n >= CFG_CAP) mbar_wait(bar_full + 8 * ((n - CFG_CAP) & (NSLOT - 1)), ((n - CFG_CAP) >> 4) & 1);
                if (use >= 1) mbar_wait(bar_empty + 8 * slot, (use - 1) & 1);
                if (n == CFG_ADAPT) { mbar_wait(bar_pace, 0); due = s_pace[0]; step = s_pace[1]; }
                const uint32_t full = bar_full + 8 * slot;
                mbar_expect_tx(full, TILE_BYTES);
                wait_until(due);
                LST(128 + n);
                tma_tile(sbase + SM_RING + slot * TILE_BYTES, &tm.k + (n & 1), ((n >> 1) * SK + (SK - WIN) + b * 32) * 3, full, pol_stream);
                due += step;
            }
            int rel = 0;
            auto released = [&](int end) {
#pragma unroll 1
                for (; rel * TILE_BYTES < end; rel++) mbar_wait(bar_empty + 8 * rel, rel < QSLOT);
            };
            const uint32_t t_wo = step * (CFG_TWO * 4096 / 478) >> 12;
            due += 4 * CFG_GAPWO;
            if (is_wo) {
#pragma unroll 1
                for (int j = 0; j < NWP; j++) {
                    released((j + 1) * WPIECE);
                    mbar_expect_tx(bar_tail + 8 * j, WPIECE);
                    wait_until(due);
                    LST(128 + N_TAIL0 + j);
                    tma_5d(sbase + j * WPIECE, &tm.wo, ng * 64, j * (NG * 128) + kg * 128, 0, 0, bar_tail + 8 * j);
                    due += t_wo;
                }
            } else {
                due += NWP * t_wo;
            }
            due += 4 * CFG_GAPFF;
            if (is_out) {
                due += step * (CFG_W2AT * 4096 / 478) >> 12;
                released(SM_W2 + NDP * PIECE);
#pragma unroll
                for (int j = 0; j < NDP; j++) mbar_expect_tx(bar_tail + 8 * (NWP + j), PIECE);
                sleep_until(due - 4 * 400);
#pragma unroll
                for (int j = 0; j < NDP; j++) {
                    wait_until(due);
                    tma_5d(sbase + SM_W2 + j * PIECE, &tm.w2, (rr - OUT0) * 16, j * 256, 0, 0, bar_tail + 8 * (NWP + j));
                    LST(128 + N_TAIL0 + NWP + j);
                    due += 4 * CFG_TW2;
                }
            } else if (is_ffn) {
                released(NUP * WPIECE);
#pragma unroll
                for (int j = 0; j <= NUP; j++) mbar_expect_tx(bar_tail + 8 * j, j < NUP - 1 ? WPIECE : WPIECE / 2);
                sleep_until(due - 4 * 400);
#pragma unroll
                for (int j = 0; j <= NUP; j++) {
                    const uint32_t full = bar_tail + 8 * j;
                    const int i = min(j, NUP - 1);
                    wait_until(due);
                    if (j < NUP) tma_5d(sbase + i * WPIECE, &tm.w1, rr * 32, 0, i * 4, 0, full);
                    if (j != NUP - 1) tma_5d(sbase + i * WPIECE + WPIECE / 2, &tm.w3, rr * 32, 0, i * 4, 0, full);
                    LST(128 + N_TAIL0 + j);
                    due += step * ((j < NUP - 1 ? CFG_TFF : CFG_T4) * 4096 / 478) >> 12;
                }
            }
        }
    } else if (warp == 10) {
        asm volatile("bar.sync 4, 64;" ::: "memory");
        if (lane == 0) {
            uint32_t epoch0;
            asm volatile("ld.relaxed.gpu.global.u32 %0, [%1];" : "=r"(epoch0) : "l"(&p.sc->epoch) : "memory");
            constexpr int MN = 8;
            const uint32_t t0 = now_q();
            uint32_t sa = 0, sb = 0;
#pragma unroll 1
            for (int n = 0; n < CFG_MB + MN; n++) {
                mbar_wait(bar_full + 8 * (n & (NSLOT - 1)), (n >> 4) & 1);
                const uint32_t t = now_q() - t0;
                LST(n);
                if ((uint32_t)(n - CFG_MA) < MN) sa += t;
                if (n >= CFG_MB) sb += t;
            }
            const uint32_t mb = t0 + sb / MN;
            unsigned long long* pace = p.sc->pace + ((epoch0 + 1) & 1);
            mbar_wait(bar_set, 0);
            asm volatile("red.relaxed.gpu.global.add.u64 [%0], %1;" ::"l"(pace), "l"((unsigned long long)mb << 32 | min((sb - sa) / (4 * MN), 0xffffu) << 8 | 1) : "memory");
            if (b == 0) p.sc->pace[epoch0 & 1] = 0;
            unsigned long long v;
            uint32_t n = 0, cnt;
#pragma unroll 1
            do {
                __nanosleep(n ? 200 : CFG_PSLEEP);
                asm volatile("ld.relaxed.gpu.global.u64 %0, [%1];" : "=l"(v) : "l"(pace) : "memory");
                cnt = (uint32_t)v & 0xff;
                if (++n > SPIN_LIMIT) __trap();
            } while (cnt < NCTA);
            const uint32_t step = min(max(((uint32_t)v >> 8) / (NCTA / 4 * (CFG_MB - CFG_MA)), p.t_step), p.t_smax);
            s_pace[0] = mb + (int)((uint32_t)(v >> 32) - NCTA * mb) / NCTA + step * (2 * (CFG_ADAPT - CFG_MB) - (MN - 1)) / 2 - p.t_lat;
            s_pace[1] = step;
            mbar_arrive(bar_pace);
            LST(89);
        }
    } else if (warp == 9) {
        const uint32_t c_start = now_q();
        uint32_t epoch0;
        asm volatile("ld.relaxed.gpu.global.u32 %0, [%1];" : "=r"(epoch0) : "l"(&p.sc->epoch) : "memory");
        sleep_until(c_start + p.t_first + CFG_PROBE_AT * p.t_step);
        unsigned char* slot[2];
        slot[0] = p.xa + xa_off(o_off(b * 48 + (lane % 6) * 8), lane / 6 & 1);
        slot[1] = p.xa + (is_wo ? xa_off(L_GATHER + (lane >> 4) * HCOPY_BYTES + (kg * D_MODEL + ng * 64 + (lane & 7) * 8) * 2, lane >> 3 & 1)
                                : xa_off(L_ACT + rr * 64 + (lane & 3) * 16, lane >> 2 & 1));
        const int n2 = is_wo ? 16 * CFG_HCOPY : is_ffn ? 8 : 0;
#pragma unroll
        for (int i = 0; i < 2; i++) if (lane < (i ? n2 : 12)) in_st4(slot[i], SENT, SENT, SENT, SENT);
#pragma unroll
        for (int i = 1; i <= CFG_PREPART; i++) pkt_st(p.sc->part + (((NHEAD - i) * 4 + (lane & 3)) * NCTA + b) * 8 + (lane >> 2), 0, 0, 0, epoch0 & 3);
        unsigned char* probe = p.xa + xa_off(L_PROBE + b * 1024 + (lane >> 1 & 7) * 128 + (lane & 1) * 16, lane >> 4);
        if ((lane >> 1 & 7) < CFG_PLINES) in_st4(probe, SENT, SENT, SENT, SENT);
        uint32_t acc = SENT;
#pragma unroll
        for (int i = 0; i < 2; i++) if (lane < (i ? n2 : 12)) acc &= in_ld1(slot[i]);
        if (__any_sync(0xffffffffu, acc != SENT)) __trap();
        int vote = 0;
        uint32_t lat[2] = {0, 0};
#pragma unroll 1
        for (int r = 0; r <= CFG_NPROBE; r++) {
            uint32_t d[2];
#pragma unroll
            for (int i = 0; i < 2; i++) {
                const uint32_t c0 = (uint32_t)clock();
                if (__any_sync(0xffffffffu, in_ld1(p.xa + xa_off(L_PROBE + b * 1024 + (lane & (CFG_PLINES - 1)) * 128, i)) != SENT)) __trap();
                d[i] = (uint32_t)clock() - c0;
                if (r) lat[i] += min(d[i], 1500u);
            }
            if (r) vote += (d[1] < d[0]) - (d[0] < d[1]);
        }
        const uint32_t sel = vote ? vote > 0 : lat[1] < lat[0];
        const uint32_t tag = epoch0 + 1;
        asm volatile("bar.sync 3, 64;" ::: "memory");
        if (lane == 0) { s_pace[2] = sel; mbar_arrive(bar_set); }
        if (is_ffn || is_wo || is_out) {
            mbar_wait(bar_pace, 0);
            sleep_until(s_pace[0] + CFG_KEEP_AT * s_pace[1]);
            float c[4] = {0.f, 0.f, 0.f, 0.f};
            const uint32_t z[4] = {p.zero, p.zero, p.zero, p.zero};
            uint32_t n = 0;
#pragma unroll 1
            do {
                mma_bf16(c, z, p.zero, p.zero);
                __nanosleep(CFG_KEEP);
                n += 1 + __float_as_uint(c[0]);
            } while (!__all_sync(0xffffffffu, mbar_test(bar_tail + 8 * (is_ffn ? 1 : is_out ? NWP : NWP - 1), 0)) && n < SPIN_LIMIT);
            if (is_ffn) {
                unsigned char* adst = p.xa + xa_off(L_ACT + rr * 64 + (lane >> 3) * 16 + (lane & 3) * 4, lane >> 2 & 1);
                uint32_t src = sbase + SM_RED + lane * 16;
                mbar_wait(after(p.zero, bar_h, adst, src), 0);
                const float4 pa = lds128f(sbase + SM_MISC), pb = lds128f(sbase + SM_MISC + 16), pc = lds128f(sbase + SM_MISC + 32), pd = lds128f(sbase + SM_MISC + 48);
                float mean_b, inv_den;
                ln_finish(((pa.y + pa.w) + (pb.y + pb.w)) + ((pc.y + pc.w) + (pd.y + pd.w)),
                          ((pa.x + pa.z) + (pb.x + pb.z)) + ((pc.x + pc.z) + (pd.x + pd.z)), mean_b, inv_den);
                asm volatile("bar.sync %0, 288;" ::"r"(after(p.zero, 5, inv_den, mean_b)) : "memory");
                float4 r[8];
#pragma unroll
                for (int i = 0; i < 8; i++) r[i] = lds128f(src + i * 512);
#define S_(c) (((r[0].c + r[1].c) + (r[2].c + r[3].c)) + ((r[4].c + r[5].c) + (r[6].c + r[7].c)))
                const float gate = bfr(fmaf(-mean_b, S_(y), S_(x)) * inv_den), up = bfr(fmaf(-mean_b, S_(w), S_(z)) * inv_den);
#undef S_
                const float act = bfr(__fdividef(gate, 1.0f + ex2(-gate * L2E))) * up;
                const float oth = __shfl_xor_sync(0xffffffffu, act, 4);
                in_st1(adst, __uint_as_float((lane & 4) ? pack_bf(act, oth) : pack_bf(oth, act)));
                if (lane == 0) LST(110);
            }
            if (is_out) {
                const int col = (rr - OUT0) * 16 + (lane & 15);
                uint32_t u[NG], xv;
                asm volatile("ld.global.nc.u16 %0, [%1];" : "=r"(xv) : "l"(p.x + col));
                mma_bf16(c, z, p.zero, p.zero);
                n = __float_as_uint(c[0]);
#pragma unroll 1
                do {
#pragma unroll
                    for (int i = 0; i < NG; i++) u[i] = in_ld1(p.xa + xa_off(L_GATHER + rr % CFG_HCOPY * HCOPY_BYTES + (i * D_MODEL + (col & ~1)) * 2, sel));
                    if (++n > SPIN_LIMIT) __trap();
                } while (__any_sync(0xffffffffu, max(max(max(u[0], u[1]), max(u[2], u[3])), max(u[4], u[5])) == SENT));
                if (rr == OUT0 && lane == 0) p.sc->epoch = tag;
#define F_(i) ((lane & 1) ? bf_hi(u[i]) : bf_lo(u[i]))
                float res = bfr(bf_lo(xv) + bfr(((F_(0) + F_(1)) + (F_(2) + F_(3))) + (F_(4) + F_(5))));
#undef F_
                mma_bf16(c, z, p.zero, p.zero);
                res += c[0];
                __nv_bfloat16* dst = p.out + col;
                uint32_t src = sbase + SM_HN + (lane & 15) * 48;
                asm volatile("bar.sync %0, 288;" ::"r"(after(p.zero, 5, src, dst, res)) : "memory");
                const float4 ra = lds128f(src), rb = lds128f(src + 16);
                const float e = ((ra.x + ra.y) + (ra.z + ra.w)) + ((rb.x + rb.y) + (rb.z + rb.w));
                if (lane < 16) asm volatile("st.global.u16 [%0], %1;" ::"l"(dst), "h"((unsigned short)pack_bf(0.f, res + bfr(e))) : "memory");
                if (lane == 0) LST(96);
            }
        }
    } else {
        const int t = lane & 3, g = lane >> 2;
        const int arow = (lane & 7) + ((lane >> 4) << 3), ahalf = (lane >> 3) & 1;
        const int hcol = warp * 80 + min(lane, 4 * NUP - 1) * 4;
        uint32_t epoch0;
        uint2 xres;
        const char* xb = reinterpret_cast<const char*>(p.x);
        asm volatile("ld.relaxed.gpu.global.u32 %0, [%1];" : "=r"(epoch0) : "l"(&p.sc->epoch) : "memory");
        asm volatile("ld.global.nc.v2.u32 {%0, %1}, [%2];" : "=r"(xres.x), "=r"(xres.y) : "l"(xb + hcol * 2));
        uint64_t* q1dst = p.sc->q1 + ((head * 4 + (warp & 3)) * 4 + sp) * 48 + min(t, 2) * 16 + g;
        uint4* q2dst = p.sc->q2 + (head * 8 + sp * 2 + lane / 12) * 4 + t;
        if (warp == 7) {
            uint2 xu[5];
#pragma unroll
            for (int i = 0; i < 5; i++) asm volatile("ld.global.nc.v2.u32 {%0, %1}, [%2];" : "=r"(xu[i].x), "=r"(xu[i].y) : "l"(xb + i * 256 + lane * 8));
            float s1 = 0.f, s2 = 0.f, mean_b, inv_den;
#pragma unroll
            for (int i = 0; i < 5; i++) {
                const float a0 = bf_lo(xu[i].x), a1 = bf_hi(xu[i].x), a2 = bf_lo(xu[i].y), a3 = bf_hi(xu[i].y);
                s1 += (a0 + a1) + (a2 + a3);
                s2 = fmaf(a0, a0, fmaf(a1, a1, fmaf(a2, a2, fmaf(a3, a3, s2))));
            }
#pragma unroll
            for (int o = 16; o > 0; o >>= 1) { s1 += __shfl_xor_sync(0xffffffffu, s1, o); s2 += __shfl_xor_sync(0xffffffffu, s2, o); }
            ln_finish(s1, s2, mean_b, inv_den);
#define N_(v) (bfr((v) - mean_b) * inv_den)
#pragma unroll
            for (int i = 0; i < 5; i++)
                sts64(sbase + SM_HN + i * 256 + lane * 8, pack_bf(N_(bf_hi(xu[i].x)), N_(bf_lo(xu[i].x))), pack_bf(N_(bf_hi(xu[i].y)), N_(bf_lo(xu[i].y))));
#undef N_
        } else if (CFG_PREQ) {
            if (warp < 4 && t < 3) { ll_st1(q1dst, 0.f, 0); ll_st1(q1dst + 8, 0.f, 0); }
            if (warp == 4 && lane < 24 && lane % 12 < 4) pkt_st(q2dst, 0, 0, 0, 0);
        }
        asm volatile("cp.async.wait_all;" ::: "memory");
        if (lane == 0) LST(80 + warp);
        asm volatile("bar.sync 2, 288;" ::: "memory");
        const uint32_t tag = epoch0 + 1;
        auto block = [&](int i) { const int unit = arow * 3 + (i >> 2); return sbase + SM_RING + unit * 128 + ((((i & 3) * 2 + ahalf) ^ (unit & 7)) << 4); };

        if (warp < 4) {
            {
                float c[3][4];
                uint32_t wa[3];
#pragma unroll
                for (int k = 0; k < 3; k++) { c[k][0] = c[k][1] = c[k][2] = c[k][3] = 0.f; wa[k] = block(warp * 3 + k) + QSLOT * TILE_BYTES; }
                const uint32_t xa = sbase + SM_HN + sp * 320 + t * 4;
#pragma unroll 2
                for (int ks = 0; ks < 2 * NQT; ks++) {
                    const uint32_t b0 = lds32(xa + ks * 32), b1 = lds32(xa + ks * 32 + 16);
#pragma unroll
                    for (int k = 0; k < 3; k++) { uint32_t a[4]; ldsm_x4_t(a, wa[k] + ks * (TILE_BYTES / 2)); mma_bf16(c[k], a, b0, b1); }
                }
                if (t < 3) {
                    ll_st1(q1dst, t == 0 ? c[0][0] : t == 1 ? c[1][0] : c[2][0], tag);
                    ll_st1(q1dst + 8, t == 0 ? c[0][2] : t == 1 ? c[1][2] : c[2][2], tag);
                }
                asm volatile("bar.sync 6, 128;" ::: "memory");
                if (tid < NQT) mbar_arrive(bar_empty + 8 * (QSLOT + tid));
                if (tid == 0) LST(90);
            }
            const uint32_t ta[3] = {block(0), block(4), block(8)};
            mbar_wait(bar_q, 0);
            if (tid == 0) LST(92);
#pragma unroll 1
            for (int h = warp; h < NHEAD; h += 4) {
                const int slot = (2 * h) & (NSLOT - 1);
                const uint32_t par = (h >> 3) & 1;
                uint32_t qf[24];
#pragma unroll
                for (int i = 0; i < 6; i++) { const uint4 v = lds128(sbase + SM_Q + h * ROW_BYTES + t * 96 + i * 16); qf[4 * i] = v.x; qf[4 * i + 1] = v.y; qf[4 * i + 2] = v.z; qf[4 * i + 3] = v.w; }
                uint32_t ad[12];
#pragma unroll
                for (int i = 0; i < 12; i++) ad[i] = (ta[i >> 2] + slot * TILE_BYTES) ^ ((i & 3) << 5);
                float sc[4][4];
#pragma unroll
                for (int j = 0; j < 4; j++) sc[j][0] = sc[j][1] = sc[j][2] = sc[j][3] = 0.f;
                mbar_wait(bar_full + 8 * slot, par);
#pragma unroll
                for (int i = 0; i < 12; i++) {
                    const uint32_t a[4] = {qf[2 * i], qf[2 * i], qf[2 * i + 1], qf[2 * i + 1]};
                    uint32_t k0[4], k1[4];
                    ldsm_x4(k0, ad[i]); ldsm_x4(k1, ad[i] + TILE_BYTES / 2);
                    mma_bf16(sc[0], a, k0[0], k0[1]); mma_bf16(sc[1], a, k0[2], k0[3]);
                    mma_bf16(sc[2], a, k1[0], k1[1]); mma_bf16(sc[3], a, k1[2], k1[3]);
                }
                const float scale = 0.07216878364870322f;
                float m = -INFINITY;
#pragma unroll
                for (int j = 0; j < 4; j++) { sc[j][0] = bfr(bfr(sc[j][0]) * scale); sc[j][1] = bfr(bfr(sc[j][1]) * scale); m = fmaxf(m, fmaxf(sc[j][0], sc[j][1])); }
                if (lane == 0) mbar_arrive(after(p.zero, bar_empty + 8 * slot, m));
                m = fmaxf(m, __shfl_xor_sync(0xffffffffu, m, 1));
                m = fmaxf(m, __shfl_xor_sync(0xffffffffu, m, 2));
                float l = 0.f;
                uint32_t pf[4];
#pragma unroll
                for (int j = 0; j < 4; j++) {
                    const float p0 = ex2((sc[j][0] - m) * L2E), p1 = ex2((sc[j][1] - m) * L2E);
                    l += p0 + p1;
                    const uint32_t hi = pack_bf(p1, p0);
                    pf[j] = (g & 1) ? pack_bf(p1 - bf_hi(hi), p0 - bf_lo(hi)) : hi;
                }
                l += __shfl_xor_sync(0xffffffffu, l, 1);
                l += __shfl_xor_sync(0xffffffffu, l, 2);
                const uint32_t meta = (__float_as_uint(m) & 0xffff0000u) | ((__float_as_uint(l) - 0x3f800000u + 0x800u) >> 10 & 0xfffcu) | (tag & 3);
                uint32_t pq[4][4];
#pragma unroll
                for (int q = 0; q < 4; q++)
#pragma unroll
                    for (int j = 0; j < 4; j++) pq[q][j] = (g >> 1) == q ? pf[j] : 0;
                float o[6][4];
#pragma unroll
                for (int k = 0; k < 6; k++) o[k][0] = o[k][1] = o[k][2] = o[k][3] = 0.f;
                uint4* dst = p.sc->part + ((h * 4 + t) * NCTA + b) * 8 + g;
                mbar_wait(after(p.zero, bar_full + 8 * slot + 8, meta, dst, pq[0][0], pq[1][1], pq[2][2], pq[3][3]), par);
#pragma unroll
                for (int i = 0; i < 12; i++) {
                    uint32_t v0[4], v1[4];
                    ldsm_x4_t(v0, ad[i] + TILE_BYTES); ldsm_x4_t(v1, ad[i] + TILE_BYTES + TILE_BYTES / 2);
                    mma_bf16(o[i % 3], v0, pq[i / 3][0], pq[i / 3][1]);
                    mma_bf16(o[3 + i % 3], v1, pq[i / 3][2], pq[i / 3][3]);
                }
                uint32_t w[3];
#pragma unroll
                for (int k = 0; k < 3; k++) w[k] = pack_bf((o[k][2] + o[k][3]) + (o[k + 3][2] + o[k + 3][3]), (o[k][0] + o[k][1]) + (o[k + 3][0] + o[k + 3][1]));
                pkt_st(dst, w[0], w[1], w[2], meta);
                if (lane == 0) {
                    mbar_arrive(after(p.zero, bar_empty + 8 * slot + 8, w[0], w[1], w[2]));
                    if (h == head) mbar_arrive(bar_part);
                }
            }
            if (tid == 96) LST(91);
        } else {
            const int u = tid - 128;
            uint32_t n = 0;
            if (warp == 4) {
                const uint4* src = reinterpret_cast<const uint4*>(p.sc->q1 + (head * 4 + sp) * 4 * 48) + min(lane, 23);
                uint4 v[4];
                __nanosleep(CFG_QDELAY);
#pragma unroll 1
                do {
                    if (n) __nanosleep(CFG_QSLEEP);
#pragma unroll
                    for (int i = 0; i < 4; i++) v[i] = ll_ld2(src + i * 24);
                    if (++n > SPIN_LIMIT) __trap();
                } while (__any_sync(0xffffffffu, ((v[0].y ^ tag) | (v[0].w ^ tag) | (v[1].y ^ tag) | (v[1].w ^ tag) | (v[2].y ^ tag) | (v[2].w ^ tag) | (v[3].y ^ tag) | (v[3].w ^ tag)) != 0));
#define F_(c) ((__uint_as_float(v[0].c) + __uint_as_float(v[1].c)) + (__uint_as_float(v[2].c) + __uint_as_float(v[3].c)))
                const uint32_t w0 = pack_bf(F_(z), F_(x));
#undef F_
                const uint32_t w1 = __shfl_down_sync(0xffffffffu, w0, 4), w2 = __shfl_down_sync(0xffffffffu, w0, 8);
                if (lane < 24 && lane % 12 < 4) pkt_st(q2dst, w0, w1, w2, tag);
            }
            asm volatile("bar.sync 7, 128;" ::: "memory");
            uint4 v[8];
            {
#pragma unroll
                for (int i = 0; i < 8; i++) v[i] = make_uint4(0, 0, 0, ~tag);
                __nanosleep(CFG_QDELAY2);
                n = 0;
                bool ok;
#pragma unroll 1
                do {
                    if (n) __nanosleep(CFG_QSLEEP);
#pragma unroll
                    for (int i = 0; i < 8; i++) pkt_ldp(p.sc->q2 + u + i * 128, v[i], v[i].w != tag);
                    ok = true;
#pragma unroll
                    for (int i = 0; i < 8; i++) ok &= v[i].w == tag;
                    if (++n > SPIN_LIMIT) __trap();
                } while (!__all_sync(0xffffffffu, ok));
                const uint32_t qd = sbase + SM_Q + (u >> 5) * ROW_BYTES + t * 96 + g * 12;
#pragma unroll
                for (int i = 0; i < 8; i++) {
                    sts32(qd + i * 4 * ROW_BYTES, __uint_as_float(v[i].x)); sts32(qd + i * 4 * ROW_BYTES + 4, __uint_as_float(v[i].y)); sts32(qd + i * 4 * ROW_BYTES + 8, __uint_as_float(v[i].z));
                }
                __syncwarp();
                if (lane == 0) mbar_arrive(bar_q);
            }
            {
                const uint4* src = p.sc->part + b * NCTA * 8 + u;
                const uint32_t rdst = sbase + SM_RED + (warp - 4) * 256 + min(lane >> 3, 2) * 64 + (lane & 7) * 4;
                const uint32_t lo = o_off(b * 48 + (min(lane, 23) >> 3) * 16) + (lane & 3) * 8 + (lane & 4);
                unsigned char *od0 = p.xa + xa_off(lo, 0), *od1 = p.xa + xa_off(lo, 1);
#pragma unroll
                for (int i = 0; i < 8; i++) v[i].w = ~tag;
                mbar_wait(bar_set, 0);
                mbar_wait(after(p.zero, bar_part, src, rdst, od0, od1), 0);
                {
                    const uint32_t at = now_q() + 4 * min(CFG_PDELAY, CFG_PDELAY_LAST + (NHEAD - 1 - head) * CFG_PDELAY_STEP);
                    sleep_until(at - 4 * 300);
                    wait_until(at);
                }
                n = 0;
                uint32_t bad;
#pragma unroll 1
                do {
                    if (n && head != NHEAD - 1) __nanosleep(CFG_QSLEEP);
#pragma unroll
                    for (int i = 0; i < 8; i++) pkt_ldp(src + i * 128, v[i], ((v[i].w ^ tag) & 3) != 0);
                    bad = 0;
#pragma unroll
                    for (int i = 0; i < 8; i++) bad |= v[i].w ^ tag;
                    if (++n > SPIN_LIMIT) __trap();
                } while (__any_sync(0xffffffffu, (bad & 3) != 0));
                if (u == 0) LST(119);
                float m = -INFINITY;
#pragma unroll
                for (int i = 0; i < 8; i++) m = fmaxf(m, bf_hi(v[i].w));
                m = fmaxf(m, __shfl_xor_sync(0xffffffffu, m, 8));
                m = fmaxf(m, __shfl_xor_sync(0xffffffffu, m, 16));
                float a[7] = {0.f, 0.f, 0.f, 0.f, 0.f, 0.f, 0.f};
#pragma unroll
                for (int i = 0; i < 8; i++) {
                    const float f = ex2((bf_hi(v[i].w) - m) * L2E);
                    a[0] = fmaf(f, bf_lo(v[i].x), a[0]); a[1] = fmaf(f, bf_hi(v[i].x), a[1]);
                    a[2] = fmaf(f, bf_lo(v[i].y), a[2]); a[3] = fmaf(f, bf_hi(v[i].y), a[3]);
                    a[4] = fmaf(f, bf_lo(v[i].z), a[4]); a[5] = fmaf(f, bf_hi(v[i].z), a[5]);
                    a[6] = fmaf(f, __uint_as_float(((v[i].w & 0xfffcu) << 10) + 0x3f800000u), a[6]);
                }
#pragma unroll
                for (int o = 8; o < 32; o <<= 1)
#pragma unroll
                    for (int i = 0; i < 7; i++) a[i] += __shfl_xor_sync(0xffffffffu, a[i], o);
                if (lane < 24) { sts32(rdst, lane < 8 ? a[0] : lane < 16 ? a[2] : a[4]); sts32(rdst + 32, lane < 8 ? a[1] : lane < 16 ? a[3] : a[5]); }
                if (lane == 24) sts64(rdst + 64, __float_as_uint(a[6]), __float_as_uint(m));
                asm volatile("bar.sync 7, 128;" ::: "memory");
                if (warp == 4) {
                    float2 st[4], r[4];
#pragma unroll
                    for (int i = 0; i < 4; i++) { st[i] = lds64f(sbase + SM_RED + i * 256 + 192); r[i] = lds64f(sbase + SM_RED + i * 256 + lane * 8); }
                    const float mm = fmaxf(fmaxf(st[0].y, st[1].y), fmaxf(st[2].y, st[3].y));
                    float den = 0.f, x0 = 0.f, x1 = 0.f;
#pragma unroll
                    for (int i = 0; i < 4; i++) { const float f = ex2((st[i].y - mm) * L2E); den = fmaf(f, st[i].x, den); x0 = fmaf(f, r[i].x, x0); x1 = fmaf(f, r[i].y, x1); }
                    const float inv = rcp_fast(den);
                    const float ow = __uint_as_float(pack_bf(x1 * inv, x0 * inv));
                    if (lane < 24) { in_st1(od0, ow); in_st1(od1, ow); }
                    if (lane == 0) LST(120);
                }
            }
        }
        mbar_wait(bar_pace, 0);
        const uint32_t msel = s_pace[2];
        cons_sync();
        if (is_wo) {
            uint32_t wa = sbase + (warp * 16 + arow) * 128 + ((ahalf ^ (lane & 7)) << 4);
            uint32_t pw = sbase + SM_RED + (warp * 64 + t * 16 + (lane >> 2)) * 4, pr = sbase + SM_RED + lane * 8;
            unsigned char* gdst = p.xa + xa_off(L_GATHER + (warp >> 1) % CFG_HCOPY * HCOPY_BYTES + (kg * D_MODEL + ng * 64 + lane * 2) * 2, warp & 1);
            const unsigned char* osrc = p.xa + xa_off(L_O + kg * 2048, msel) + warp * 32 + t * 8;
            uint2 ov[NWP];
#pragma unroll
            for (int j = 0; j < NWP; j++) ov[j] = make_uint2(SENT, SENT);
            auto gather = [&](int j0, int j1) {
                uint32_t n = 0;
#pragma unroll 1
                while (true) {
                    uint32_t mx = 0;
#pragma unroll
                    for (int j = j0; j < j1; j++) mx = max(mx, max(ov[j].x, ov[j].y));
                    if (!__any_sync(0xffffffffu, mx == SENT)) break;
#pragma unroll
                    for (int j = j0; j < j1; j++) in_ld2p(osrc + j * 256, ov[j], !in_ok(ov[j]));
                    if (++n > SPIN_LIMIT) __trap();
                }
            };
            float cw[4][4];
#pragma unroll
            for (int i = 0; i < 4; i++) cw[i][0] = cw[i][1] = cw[i][2] = cw[i][3] = 0.f;
            mbar_wait(after(p.zero, bar_tail + 8 * CFG_OGATE, osrc, wa, pw, pr, gdst), 0);
#pragma unroll
            for (int j = 0; j < NWP; j++) in_ld2p(osrc + j * 256, ov[j], true);
            gather(0, NWP - 1);
#pragma unroll
            for (int j = 0; j < NWP; j++) {
                if (j == NWP - 1) { gather(NWP - 1, NWP); if (tid == 224) LST(93); }
                mbar_wait(bar_tail + 8 * j, 0);
                if (j >= CFG_OGATE2 && j <= CFG_OGATE3) in_ld2p(osrc + (NWP - 1) * 256, ov[NWP - 1], !in_ok(ov[NWP - 1]));
                uint32_t a[4][4];
#pragma unroll
                for (int i = 0; i < 4; i++) ldsm_x4_t(a[i], (wa ^ (i << 5)) + j * WPIECE);
#pragma unroll
                for (int i = 0; i < 4; i++) mma_bf16(cw[i], a[i], ov[j].x, ov[j].y);
            }
#define SEL_(e) ((t & 2) ? ((t & 1) ? cw[3][e] : cw[2][e]) : ((t & 1) ? cw[1][e] : cw[0][e]))
            sts32(pw, SEL_(0)); sts32(pw + 32, SEL_(2));
#undef SEL_
            cons_sync();
            if (warp < 2 * CFG_HCOPY) {
                float2 r[8];
#pragma unroll
                for (int i = 0; i < 8; i++) r[i] = lds64f(pr + i * 256);
#define S_(c) (((r[0].c + r[1].c) + (r[2].c + r[3].c)) + ((r[4].c + r[5].c) + (r[6].c + r[7].c)))
                in_st1(gdst, __uint_as_float(pack_bf(S_(y), S_(x))));
#undef S_
            }
            if (tid == 0) LST(94);
        } else if (is_ffn) {
            uint32_t w13a = sbase + (warp * 16 + arow) * 64 + ((ahalf ^ (lane >> 1 & 3)) << 4);
            uint32_t red_dst = sbase + SM_RED + tid * 16;
            uint32_t stat = sbase + SM_MISC + warp * 8;
            uint32_t aw[NUP][4][4];
            auto load_w13 = [&](int i, uint32_t bar) {
                mbar_wait(bar + 8 * i, 0);
#pragma unroll
                for (int k = 0; k < 4; k++) ldsm_x4_t(aw[i][k], (w13a ^ (k << 5 & 32)) + i * WPIECE + (k >> 1) * (WPIECE / 2));
            };
            uint32_t hp0, hp1;
            {
                const unsigned char* gsrc[NG];
                uint2 u[NG];
#pragma unroll
                for (int i = 0; i < NG; i++) { u[i] = make_uint2(0, 0); gsrc[i] = p.xa + xa_off(L_GATHER + rr % CFG_HCOPY * HCOPY_BYTES + (i * D_MODEL + hcol) * 2, msel); }
#pragma unroll
                for (int i = 0; i < CFG_HGATE; i++) load_w13(i, after(p.zero, bar_tail, gsrc[0], gsrc[1], gsrc[2], gsrc[3], gsrc[4], gsrc[5], w13a, red_dst, stat));
                LSC(0);
#pragma unroll
                for (int i = 0; i < NG; i++) in_ld2p(gsrc[i], u[i], lane < 4 * NUP && !ABL_NOH);
                if (CFG_HSHADOW) load_w13(CFG_HGATE, bar_tail);
                LSCD(1, u[0].x ^ u[1].x ^ u[2].x ^ u[3].x ^ u[4].x ^ u[5].x);
                uint32_t n = 0;
#pragma unroll 1
                while (__any_sync(0xffffffffu, max(max(max(u[0].x, u[0].y), max(u[1].x, u[1].y)), max(max(max(u[2].x, u[2].y), max(u[3].x, u[3].y)),
                                                                                                    max(max(u[4].x, u[4].y), max(u[5].x, u[5].y)))) == SENT)) {
#pragma unroll
                    for (int i = 0; i < NG; i++) in_ld2p(gsrc[i], u[i], !in_ok(u[i]));
                    if (++n > SPIN_LIMIT) __trap();
                }
                if (tid == 96) LST(100);
                LSC(2);
#pragma unroll
                for (int i = CFG_HGATE + CFG_HSHADOW; i < HPRE; i++) load_w13(i, bar_tail);
#define F_(f, c) (f(xres.c) + bfr(((f(u[0].c) + f(u[1].c)) + (f(u[2].c) + f(u[3].c))) + (f(u[4].c) + f(u[5].c))))
                hp0 = pack_bf(F_(bf_hi, x), F_(bf_lo, x));
                hp1 = pack_bf(F_(bf_hi, y), F_(bf_lo, y));
#undef F_
            }
            {
                uint32_t b0[NUP], b1[NUP];
                float cf[4][4], cs[2][4];
#pragma unroll
                for (int e = 0; e < 4; e++) cf[0][e] = cf[1][e] = cf[2][e] = cf[3][e] = cs[0][e] = cs[1][e] = 0.f;
#pragma unroll
                for (int i = 0; i < NUP; i++) {
                    const uint32_t h0 = __shfl_sync(0xffffffffu, hp0, i * 4 + t), h1 = __shfl_sync(0xffffffffu, hp1, i * 4 + t);
                    b0[i] = (lane & 4) ? 0x3f803f80u : h0;
                    b1[i] = (lane & 4) ? 0x3f803f80u : h1;
                    const uint32_t sa[4] = {h0, h0, h1, h1};
                    mma_bf16(cs[i & 1], sa, b0[i], b1[i]);
                }
                auto mma_w13 = [&](int i) {
#pragma unroll
                    for (int k = 0; k < 4; k++) mma_bf16(cf[k], aw[i][k], b0[i], b1[i]);
                };
                if (lane == 0) sts64(stat, __float_as_uint(cs[0][0] + cs[1][0]), __float_as_uint(cs[0][1] + cs[1][1]));
                __syncwarp();
                if (lane == 0) mbar_arrive(bar_h);
#pragma unroll
                for (int i = 0; i < HPRE; i++) mma_w13(i);
                LSC(3);
#pragma unroll
                for (int i = HPRE; i < NUP - 1; i++) { load_w13(i, bar_tail); mma_w13(i); }
                LSC(4);
#pragma unroll
                for (int m = 0; m < 2; m++) {
                    mbar_wait(CFG_DEPLAST && m ? after(p.zero, bar_tail + 8 * NUP, cf[1][0]) : bar_tail + 8 * (NUP - 1 + m), 0);
#pragma unroll
                    for (int k = 2 * m; k < 2 * m + 2; k++) ldsm_x4_t(aw[NUP - 1][k], (w13a ^ (k << 5 & 32)) + (NUP - 1) * WPIECE + m * (WPIECE / 2));
#pragma unroll
                    for (int k = 2 * m; k < 2 * m + 2; k++) mma_bf16(cf[k], aw[NUP - 1][k], b0[NUP - 1], b1[NUP - 1]);
                }
                LSC(6);
#define SEL_(k, e) ((t & 2) ? ((t & 1) ? cf[k + 1][e + 2] : cf[k + 1][e]) : ((t & 1) ? cf[k][e + 2] : cf[k][e]))
                asm volatile("st.shared.v4.f32 [%0], {%1, %2, %3, %4};" ::"r"(red_dst), "f"(SEL_(0, 0)), "f"(SEL_(0, 1)), "f"(SEL_(2, 0)), "f"(SEL_(2, 1)) : "memory");
#undef SEL_
            }
            LSC(7);
            asm volatile("bar.arrive 5, 288;" ::: "memory");
        }
        if (is_out) {
            uint32_t w2a = sbase + SM_W2 + (warp * 32 + arow) * 32 + ((ahalf ^ (lane >> 2 & 1)) << 4);
            uint32_t ydst = sbase + SM_HN + ((t & 1) * 8 + (lane >> 2)) * 48 + warp * 4;
            const unsigned char* asrc = p.xa + xa_off(L_ACT, msel) + warp * 64 + t * 16;
            const uint32_t bar_w2 = after(p.zero, bar_tail + 8 * NWP, w2a, ydst, asrc);
            uint32_t a[NDP][2][4];
            auto load_w2 = [&](int i) {
                mbar_wait(bar_w2 + 8 * i, 0);
                ldsm_x4_t(a[i][0], w2a + i * PIECE); ldsm_x4_t(a[i][1], w2a + i * PIECE + 512);
            };
#pragma unroll
            for (int i = 0; i < CFG_AGATE; i++) load_w2(i);
            uint4 u[NDP];
            LSC(0);
#pragma unroll
            for (int i = 0; i < NDP; i++) u[i] = in_ld4(asrc + i * 512);
#pragma unroll
            for (int i = CFG_AGATE; i < APRE; i++) load_w2(i);
            int have = APRE;
            auto try_w2 = [&]() {
#pragma unroll
                for (int i = APRE; i < NDP; i++)
                    if (have == i && __all_sync(0xffffffffu, mbar_test(bar_tail + 8 * (NWP + i), 0))) {
                        ldsm_x4_t(a[i][0], w2a + i * PIECE); ldsm_x4_t(a[i][1], w2a + i * PIECE + 512);
                        have++;
                    }
            };
            try_w2();
            uint32_t n = 0;
#pragma unroll 1
            while (true) {
                uint32_t m[NDP];
#pragma unroll
                for (int i = 0; i < NDP; i++) m[i] = max(max(u[i].x, u[i].y), max(u[i].z, u[i].w));
                if (!__any_sync(0xffffffffu, max(max(max(m[0], m[1]), m[2]), max(max(m[3], m[4]), m[5])) == SENT)) break;
#pragma unroll
                for (int i = 0; i < NDP; i++) in_ld4p(asrc + i * 512, u[i], m[i] == SENT);
                try_w2();
                if (++n > SPIN_LIMIT) __trap();
            }
            LSC(12);
            if (tid == 96) LST(118);
            float cy[4][4];
#pragma unroll
            for (int e = 0; e < 4; e++) cy[0][e] = cy[1][e] = cy[2][e] = cy[3][e] = 0.f;
#pragma unroll
            for (int i = 0; i < NDP; i++) {
                if (i >= APRE && i >= have) load_w2(i);
                mma_bf16(cy[2 * (i & 1)], a[i][0], u[i].x, u[i].y);
                mma_bf16(cy[2 * (i & 1) + 1], a[i][1], u[i].z, u[i].w);
            }
            const float y = (t & 1) ? (cy[0][2] + cy[1][2]) + (cy[2][2] + cy[3][2]) : (cy[0][0] + cy[1][0]) + (cy[2][0] + cy[3][0]);
            if (t < 2) sts32(ydst, y);
            LSC(13);
            asm volatile("bar.arrive 5, 288;" ::: "memory");
        }
    }
}

typedef CUresult (*EncodeTiledFn)(CUtensorMap*, CUtensorMapDataType, cuuint32_t, void*, const cuuint64_t*, const cuuint64_t*,
                                  const cuuint32_t*, const cuuint32_t*, CUtensorMapInterleave, CUtensorMapSwizzle,
                                  CUtensorMapL2promotion, CUtensorMapFloatOOBfill);

void make_map(EncodeTiledFn fn, CUtensorMap* tm, const void* w, const int (&d)[5], const int (&st)[4], const int (&bx)[5],
              CUtensorMapSwizzle sw, int promo) {
    cuuint64_t dims[5], strides[4];
    cuuint32_t box[5], estr[5];
    for (int i = 0; i < 5; i++) { dims[i] = (cuuint64_t)d[i]; box[i] = (cuuint32_t)bx[i]; estr[i] = 1; }
    for (int i = 0; i < 4; i++) strides[i] = (cuuint64_t)st[i];
    fn(tm, CU_TENSOR_MAP_DATA_TYPE_BFLOAT16, 5, const_cast<void*>(w), dims, strides, box, estr, CU_TENSOR_MAP_INTERLEAVE_NONE, sw,
       (CUtensorMapL2promotion)promo, CU_TENSOR_MAP_FLOAT_OOB_FILL_NONE);
}

}

extern "C" void kernel_launch(void* const* d_in, const int* in_sizes, int n_in, void* d_out, int out_size) {
    (void)in_sizes; (void)n_in; (void)out_size;
    static EncodeTiledFn encode = nullptr;
    static Scratch* scratch = nullptr;
    static unsigned char* xarea = nullptr;
    static double tscale = 1.0;
    if (!encode) {
        void* sp = nullptr;
        cudaGetSymbolAddress(&sp, g_scratch);
        scratch = reinterpret_cast<Scratch*>(sp);
        cudaGetSymbolAddress(&sp, g_xarea);
        xarea = reinterpret_cast<unsigned char*>((reinterpret_cast<uintptr_t>(sp) + XA_ALIGN - 1) / XA_ALIGN * XA_ALIGN);
        void* fn = nullptr;
        cudaDriverEntryPointQueryResult st;
        cudaGetDriverEntryPoint("cuTensorMapEncodeTiled", &fn, cudaEnableDefault, &st);
        encode = reinterpret_cast<EncodeTiledFn>(fn);
        int dev = 0, khz = 0, bits = 0;
        cudaGetDevice(&dev);
        cudaDeviceGetAttribute(&khz, cudaDevAttrMemoryClockRate, dev);
        cudaDeviceGetAttribute(&bits, cudaDevAttrGlobalMemoryBusWidth, dev);
        if (khz > 0 && bits > 0) tscale = (2619000.0 * 5120.0) / ((double)khz * bits);
        cudaFuncSetAttribute(fused_decode_kernel, cudaFuncAttributeMaxDynamicSharedMemorySize, SM_TOTAL);
    }
    KParams p;
    p.x = (const __nv_bfloat16*)d_in[0];
    p.wq = (const __nv_bfloat16*)d_in[3];
    p.out = (__nv_bfloat16*)d_out;
    p.sc = scratch;
    p.xa = xarea;
    p.zero = 0;
    p.t_first = (uint32_t)(4 * CFG_OFF0 * tscale);
    p.t_step = (uint32_t)(CFG_T * tscale);
    p.t_smax = (uint32_t)(CFG_SMAX * tscale);
    p.t_lat = (uint32_t)(4 * (450 + (CFG_LAT - 450) * tscale));
    TMaps tm;
    constexpr int R1 = FF * 2, R2 = D_MODEL * 2;
    make_map(encode, &tm.k, d_in[1], {64, NHEAD * SK * 3, 1, 1, 1}, {128, 128, 128, 128}, {64, 96, 1, 1, 1}, CU_TENSOR_MAP_SWIZZLE_128B, CFG_PROMO_KV);
    make_map(encode, &tm.v, d_in[2], {64, NHEAD * SK * 3, 1, 1, 1}, {128, 128, 128, 128}, {64, 96, 1, 1, 1}, CU_TENSOR_MAP_SWIZZLE_128B, CFG_PROMO_KV);
    make_map(encode, &tm.wo, d_in[4], {D_MODEL, NHEAD * DH, 1, 1, 1}, {R2, R2, R2, R2}, {64, 128, 1, 1, 1}, CU_TENSOR_MAP_SWIZZLE_128B, CFG_PROMO_WO);
    make_map(encode, &tm.w1, d_in[6], {FF, 2, 20, 2, 8}, {R1, 4 * R1, 2 * R1, 80 * R1}, {32, 2, 4, 2, 8}, CU_TENSOR_MAP_SWIZZLE_64B, CFG_PROMO_W13);
    make_map(encode, &tm.w3, d_in[7], {FF, 2, 20, 2, 8}, {R1, 4 * R1, 2 * R1, 80 * R1}, {32, 2, 4, 2, 8}, CU_TENSOR_MAP_SWIZZLE_64B, CFG_PROMO_W13);
    make_map(encode, &tm.w2, d_in[8], {D_MODEL, FF, 1, 1, 1}, {R2, R2, R2, R2}, {16, 256, 1, 1, 1}, CU_TENSOR_MAP_SWIZZLE_32B, CFG_PROMO_W2);
    fused_decode_kernel<<<NCTA, NTHREADS, SM_TOTAL, cudaStreamPerThread>>>(p, tm);
}
```

```cpp
#include <cuda_runtime.h>
#include <cuda_bf16.h>
#include <cuda.h>
#include <stdint.h>
#include <math.h>

namespace {

constexpr int D_MODEL = 640;
constexpr int NHEAD = 32;
constexpr int DH = 192;
constexpr int SK = 32768;
constexpr int WIN = 4096;
constexpr int FF = 1536;

constexpr int NCTA = 128;
constexpr int NCONS = 256;
constexpr int NTHREADS = NCONS + 96;
constexpr int ROW_BYTES = DH * 2;
constexpr int TILE_BYTES = 32 * ROW_BYTES;
constexpr int NSLOT = 16;
constexpr int NQT = 5;
constexpr int QSLOT = NSLOT - NQT;
constexpr int NWO = 60;
constexpr int NG = 6;
constexpr int NFFN = 48;
constexpr int NWP = 8;
constexpr int NUP = 5;
constexpr int WPIECE = 16384;
constexpr int NDP = 3;
constexpr int PIECE = 8192;
constexpr int NTAIL = NWP + NDP;
constexpr int N_TAIL0 = 2 * NHEAD;

#define CFG(name, value) constexpr int name = value
#define CFG_OVERRIDE
namespace cfg_default {
CFG(T_FIRST, 2000);
CFG(T_STEP, 1900);
CFG(T_SMAX, 1940);
CFG(CAP, 5);
CFG(MA, 16);
CFG(MB, 40);
CFG(ADAPT, 58);
CFG(T_LAT, 1340);
CFG(T_WO, 296);
CFG(T_GAP, 130);
CFG(T_UP, 234);
CFG(T_UP2, 140);
CFG(T_W2AT, 1325);
CFG(T_W2, 200);
CFG(T_HAT, 1240);
CFG(T_RESAT, 1750);
CFG(AGATE, 2);
CFG(KEEP_AT, 7);
CFG(KEEP, 150);
CFG(HCOPY, 2);
CFG(QDELAY, 900);
CFG(QDELAY2, 700);
CFG(QSLEEP, 400);
CFG(PDELAY, 2500);
CFG(PDELAY_LAST, 250);
CFG(PDELAY_STEP, 650);
CFG(PREPART, 3);
CFG(RBDELAY, 5000);
CFG(NPROBE, 10);
CFG(VOTES, 3);
CFG(PROMO_KV, 2);
CFG(PROMO_WO, 2);
CFG(PROMO_W13, 2);
CFG(PROMO_W2, 2);
CFG(BOUNDED_MBAR, 0);
}
namespace cfg { using namespace cfg_default; CFG_OVERRIDE }

constexpr int SM_RING = 0;
constexpr int SM_W2 = NWP * WPIECE;
constexpr int SM_Q = SM_RING + NSLOT * TILE_BYTES;
constexpr int SM_RED = SM_Q + NHEAD * ROW_BYTES;
constexpr int SM_HN = SM_RED + 4096;
constexpr int SM_MISC = SM_HN + D_MODEL * 2;
constexpr int SM_BAR = SM_MISC + 128;
constexpr int SM_TOTAL = SM_BAR + 512;
static_assert(SM_TOTAL <= 232448, "shared memory");

struct __align__(128) Scratch {
    uint4 part[NHEAD * 4 * NCTA * 8];
    uint64_t q1[NHEAD * 4 * DH];
    uint4 q2[NHEAD * 32];
    uint32_t epoch;
    uint32_t pad[31];
    unsigned long long pace[2];
};
__device__ Scratch g_scratch;
constexpr int XA_ALIGN = 1 << 20;
constexpr uint32_t SENT = 0xffffffffu;
constexpr int L_GATHER = 0;
constexpr int HCOPY_BYTES = NG * D_MODEL * 2;
constexpr int L_O = 9 * 4096;
constexpr int L_ACT = 30 * 4096;
constexpr int L_PROBE = 32 * 4096;
static_assert(2 * (L_PROBE + NCTA * 1024) <= XA_ALIGN, "");
__device__ unsigned char g_xarea[2 * XA_ALIGN];
__device__ __forceinline__ uint32_t xa_off(uint32_t l, uint32_t side) {
    const uint32_t k = l >> 12;
    return (2 * k + ((side ^ k ^ (k >> 3) ^ (k >> 4) ^ (k >> 6)) & 1)) * 4096 + (l & 4095);
}

__device__ __forceinline__ uint32_t o_off(uint32_t r) { return L_O + (r >> 7) % NG * 2048 + (r >> 7) / NG * 256 + (r & 127) * 2; }

#define LST(i) do { } while (0)
#define LSC(i) do { } while (0)
#define LSCD(i, v) do { } while (0)
constexpr uint32_t SPIN_LIMIT = cfg::BOUNDED_MBAR ? 1u << 14 : 1u << 22;

__device__ __forceinline__ uint32_t now_q() { uint32_t t; asm volatile("mov.u32 %0, %globaltimer_lo;" : "=r"(t)); return t * 4; }
__device__ __forceinline__ void wait_until(uint32_t due) {
#pragma unroll 1
    for (int n = 0; n < 4096 && (int)(now_q() - due) < 0; n++) { }
}
__device__ __forceinline__ void sleep_until(uint32_t due) {
#pragma unroll 1
    for (int n = 0; n < 4096 && (int)(now_q() - due) < 0; n++) __nanosleep(200);
}
__device__ __forceinline__ uint32_t smem_u32(const void* p) { return (uint32_t)__cvta_generic_to_shared(p); }
__device__ __forceinline__ void mbar_init(uint32_t bar, uint32_t cnt) {
    asm volatile("mbarrier.init.shared::cta.b64 [%0], %1;" ::"r"(bar), "r"(cnt) : "memory");
}
__device__ __forceinline__ void mbar_expect_tx(uint32_t bar, uint32_t bytes) {
    asm volatile("mbarrier.arrive.expect_tx.shared::cta.b64 _, [%0], %1;" ::"r"(bar), "r"(bytes) : "memory");
}
__device__ __forceinline__ void mbar_arrive(uint32_t bar) {
    asm volatile("mbarrier.arrive.shared::cta.b64 _, [%0];" ::"r"(bar) : "memory");
}
__device__ __forceinline__ bool mbar_test(uint32_t bar, uint32_t parity) {
    uint32_t ok;
    asm volatile("{\n.reg .pred p;\nmbarrier.test_wait.parity.shared::cta.b64 p, [%1], %2;\nselp.u32 %0, 1, 0, p;\n}"
                 : "=r"(ok) : "r"(bar), "r"(parity) : "memory");
    return ok;
}
__device__ __forceinline__ bool mbar_try(uint32_t bar, uint32_t parity) {
    uint32_t ok;
    asm volatile("{\n.reg .pred p;\nmbarrier.try_wait.parity.shared::cta.b64 p, [%1], %2;\nselp.u32 %0, 1, 0, p;\n}"
                 : "=r"(ok) : "r"(bar), "r"(parity) : "memory");
    return ok;
}
__device__ __forceinline__ void mbar_wait(uint32_t bar, uint32_t parity) {
    if (cfg::BOUNDED_MBAR) {
        uint32_t n = 0;
        while (!mbar_try(bar, parity)) if (++n > SPIN_LIMIT) __trap();
    } else {
        asm volatile("{\n.reg .pred p;\nW_%=:\nmbarrier.try_wait.parity.shared::cta.b64 p, [%0], %1;\n@!p bra W_%=;\n}" ::"r"(bar), "r"(parity) : "memory");
    }
}
__device__ __forceinline__ void tma_tile(uint32_t dst, const CUtensorMap* tm, int c1, uint32_t bar, uint64_t pol) {
    asm volatile("cp.async.bulk.tensor.5d.shared::cluster.global.mbarrier::complete_tx::bytes.L2::cache_hint [%0], [%1, {%4, %3, %4, %4, %4}], [%2], %5;"
                 ::"r"(dst), "l"(reinterpret_cast<uint64_t>(tm)), "r"(bar), "r"(c1), "r"(0), "l"(pol) : "memory");
}
__device__ __forceinline__ void tma_5d(uint32_t dst, const CUtensorMap* tm, int c0, int c1, int c2, int c4, uint32_t bar) {
    asm volatile("cp.async.bulk.tensor.5d.shared::cluster.global.mbarrier::complete_tx::bytes [%0], [%1, {%3, %4, %5, %7, %6}], [%2];"
                 ::"r"(dst), "l"(reinterpret_cast<uint64_t>(tm)), "r"(bar), "r"(c0), "r"(c1), "r"(c2), "r"(c4), "r"(0) : "memory");
}
__device__ __forceinline__ uint32_t bits(uint32_t v) { return v; }
__device__ __forceinline__ uint32_t bits(float v) { return __float_as_uint(v); }
__device__ __forceinline__ uint32_t bits(const void* v) { return (uint32_t)(uintptr_t)v ^ (uint32_t)((uintptr_t)v >> 32); }
template <class... T> __device__ __forceinline__ uint32_t after(uint32_t zero, uint32_t bar, T... v) { return bar | ((bits(v) ^ ...) & zero); }
__device__ __forceinline__ void sts32(uint32_t a, float v) { asm volatile("st.shared.f32 [%0], %1;" ::"r"(a), "f"(v) : "memory"); }
__device__ __forceinline__ void sts64(uint32_t a, uint32_t x, uint32_t y) { asm volatile("st.shared.v2.u32 [%0], {%1, %2};" ::"r"(a), "r"(x), "r"(y) : "memory"); }
__device__ __forceinline__ void cons_sync() { asm volatile("bar.sync 1, 256;" ::: "memory"); }

__device__ __forceinline__ uint4 lds128(uint32_t a) {
    uint4 v;
    asm volatile("ld.shared.v4.u32 {%0,%1,%2,%3}, [%4];" : "=r"(v.x), "=r"(v.y), "=r"(v.z), "=r"(v.w) : "r"(a));
    return v;
}
__device__ __forceinline__ float4 lds128f(uint32_t a) {
    float4 v;
    asm volatile("ld.shared.v4.f32 {%0,%1,%2,%3}, [%4];" : "=f"(v.x), "=f"(v.y), "=f"(v.z), "=f"(v.w) : "r"(a) : "memory");
    return v;
}
__device__ __forceinline__ float2 lds64f(uint32_t a) {
    float2 v;
    asm volatile("ld.shared.v2.f32 {%0,%1}, [%2];" : "=f"(v.x), "=f"(v.y) : "r"(a) : "memory");
    return v;
}
__device__ __forceinline__ uint32_t lds32(uint32_t a) {
    uint32_t v;
    asm volatile("ld.shared.u32 %0, [%1];" : "=r"(v) : "r"(a));
    return v;
}
__device__ __forceinline__ void ldsm_x4(uint32_t* r, uint32_t a) {
    asm volatile("ldmatrix.sync.aligned.m8n8.x4.shared.b16 {%0,%1,%2,%3}, [%4];"
                 : "=r"(r[0]), "=r"(r[1]), "=r"(r[2]), "=r"(r[3]) : "r"(a));
}
__device__ __forceinline__ void ldsm_x4_t(uint32_t* r, uint32_t a) {
    asm volatile("ldmatrix.sync.aligned.m8n8.x4.trans.shared.b16 {%0,%1,%2,%3}, [%4];"
                 : "=r"(r[0]), "=r"(r[1]), "=r"(r[2]), "=r"(r[3]) : "r"(a));
}
__device__ __forceinline__ void mma_bf16(float* c, const uint32_t* a, uint32_t b0, uint32_t b1) {
    asm volatile("mma.sync.aligned.m16n8k16.row.col.f32.bf16.bf16.f32 {%0,%1,%2,%3}, {%4,%5,%6,%7}, {%8,%9}, {%0,%1,%2,%3};"
                 : "+f"(c[0]), "+f"(c[1]), "+f"(c[2]), "+f"(c[3]) : "r"(a[0]), "r"(a[1]), "r"(a[2]), "r"(a[3]), "r"(b0), "r"(b1));
}
__device__ __forceinline__ float bf_lo(uint32_t u) { return __uint_as_float(u << 16); }
__device__ __forceinline__ float bf_hi(uint32_t u) { return __uint_as_float(u & 0xffff0000u); }
__device__ __forceinline__ uint32_t pack_bf(float hi, float lo) { uint32_t r; asm("cvt.rn.bf16x2.f32 %0, %1, %2;" : "=r"(r) : "f"(hi), "f"(lo)); return r; }
__device__ __forceinline__ float bfr(float x) { return __uint_as_float(pack_bf(x, 0.f)); }

__device__ __forceinline__ uint64_t pk(float v, uint32_t tag) { return ((uint64_t)tag << 32) | (uint64_t)__float_as_uint(v); }
__device__ __forceinline__ void ll_st1(uint64_t* p, float a, uint32_t tag) {
    asm volatile("st.relaxed.gpu.global.b64 [%0], %1;" ::"l"(p), "l"(pk(a, tag)) : "memory");
}
__device__ __forceinline__ uint4 ll_ld2(const uint4* p) {
    uint4 v;
    asm volatile("{\n.reg .b64 a, b;\nld.relaxed.gpu.global.v2.b64 {a, b}, [%4];\nmov.b64 {%0, %1}, a;\nmov.b64 {%2, %3}, b;\n}"
                 : "=r"(v.x), "=r"(v.y), "=r"(v.z), "=r"(v.w) : "l"(p) : "memory");
    return v;
}
__device__ __forceinline__ uint32_t in_word(float v) {
    uint32_t r;
    asm("min.u32 %0, %1, 0xfffffffe;" : "=r"(r) : "r"(__float_as_uint(v)));
    return r;
}
__device__ __forceinline__ void in_st1(void* p, float v) {
    asm volatile("st.relaxed.gpu.global.u32 [%0], %1;" ::"l"(p), "r"(in_word(v)) : "memory");
}
__device__ __forceinline__ void in_st4(void* p, uint32_t a, uint32_t b, uint32_t c, uint32_t d) {
    asm volatile("st.relaxed.gpu.global.v4.u32 [%0], {%1, %2, %3, %4};" ::"l"(p), "r"(a), "r"(b), "r"(c), "r"(d) : "memory");
}
__device__ __forceinline__ uint32_t in_ld1(const void* p) {
    uint32_t v;
    asm volatile("ld.relaxed.gpu.global.u32 %0, [%1];" : "=r"(v) : "l"(p) : "memory");
    return v;
}
__device__ __forceinline__ uint4 in_ld4(const void* p) {
    uint4 v;
    asm volatile("ld.relaxed.gpu.global.v4.u32 {%0, %1, %2, %3}, [%4];" : "=r"(v.x), "=r"(v.y), "=r"(v.z), "=r"(v.w) : "l"(p) : "memory");
    return v;
}
__device__ __forceinline__ void in_ld2p(const void* p, uint2& v, bool on) {
    asm volatile("{\n.reg .pred q;\nsetp.ne.u32 q, %3, 0;\n@q ld.relaxed.gpu.global.v2.u32 {%0, %1}, [%2];\n}"
                 : "+r"(v.x), "+r"(v.y) : "l"(p), "r"((uint32_t)on) : "memory");
}
__device__ __forceinline__ bool in_ok(const uint2& v) { return max(v.x, v.y) != SENT; }
__device__ __forceinline__ void in_ld4p(const void* p, uint4& v, bool on) {
    asm volatile("{\n.reg .pred q;\nsetp.ne.u32 q, %5, 0;\n@q ld.relaxed.gpu.global.v4.u32 {%0, %1, %2, %3}, [%4];\n}"
                 : "+r"(v.x), "+r"(v.y), "+r"(v.z), "+r"(v.w) : "l"(p), "r"((uint32_t)on) : "memory");
}
__device__ __forceinline__ void pkt_st(uint4* p, uint32_t x, uint32_t y, uint32_t z, uint32_t w) {
    asm volatile("{\n.reg .b128 t;\n.reg .b64 a, b;\nmov.b64 a, {%1, %2};\nmov.b64 b, {%3, %4};\nmov.b128 t, {a, b};\nst.relaxed.gpu.global.b128 [%0], t;\n}"
                 ::"l"(p), "r"(x), "r"(y), "r"(z), "r"(w) : "memory");
}
__device__ __forceinline__ void pkt_ldp(const uint4* p, uint4& v, bool on) {
    asm volatile("{\n.reg .pred q;\n.reg .b128 t;\n.reg .b64 a, b;\nsetp.ne.u32 q, %5, 0;\nmov.b64 a, {%0, %1};\nmov.b64 b, {%2, %3};\nmov.b128 t, {a, b};\n"
                 "@q ld.relaxed.gpu.global.b128 t, [%4];\nmov.b128 {a, b}, t;\nmov.b64 {%0, %1}, a;\nmov.b64 {%2, %3}, b;\n}"
                 : "+r"(v.x), "+r"(v.y), "+r"(v.z), "+r"(v.w) : "l"(p), "r"((uint32_t)on) : "memory");
}

__device__ __forceinline__ float sqrt_fast(float x) { float r; asm("sqrt.approx.ftz.f32 %0, %1;" : "=f"(r) : "f"(x)); return r; }
__device__ __forceinline__ float rcp_fast(float x) { float r; asm("rcp.approx.ftz.f32 %0, %1;" : "=f"(r) : "f"(x)); return r; }
__device__ __forceinline__ float ex2(float x) { float r; asm("ex2.approx.ftz.f32 %0, %1;" : "=f"(r) : "f"(x)); return r; }
constexpr float L2E = 1.4426950408889634f;
__device__ __forceinline__ void ln_finish(float s1, float s2, float& mean_b, float& inv_den) {
    const float mean = s1 * (1.0f / D_MODEL);
    const float var = fmaxf(fmaf(-mean, mean, s2 * (1.0f / D_MODEL)), 0.f);
    mean_b = bfr(mean);
    inv_den = rcp_fast(bfr(sqrt_fast(bfr(bfr(var) + 1e-5f))));
}

struct KParams {
    const __nv_bfloat16* wq;
    uint32_t t_first;
    uint32_t t_step;
    const __nv_bfloat16* x;
    Scratch* sc;
    unsigned char* xa;
    __nv_bfloat16* out;
    uint32_t t_smax;
    uint32_t t_lat;
    uint32_t zero;
};
struct TMaps { CUtensorMap k, v, wo, w1, w3, w2; };

__global__ void __launch_bounds__(NTHREADS, 1)
fused_decode_kernel(const KParams p, const __grid_constant__ TMaps tm) {
    extern __shared__ __align__(1024) unsigned char smem[];
    const uint32_t sbase = smem_u32(smem);
    const int tid = threadIdx.x;
    const int b = blockIdx.x;
    const int head = b >> 2, sp = b & 3;
    {
        if (tid < 192) {
            const int rg = tid / 24, ch = tid - rg * 24;
            const char* src = reinterpret_cast<const char*>(p.wq) + (size_t)(sp * 160 + rg) * (NHEAD * DH * 2) + head * ROW_BYTES + ch * 16;
            uint32_t dst = sbase + SM_RING + QSLOT * TILE_BYTES + ((tid ^ (tid >> 3 & 7)) << 4);
#pragma unroll 1
            for (int i = 0; i < 20; i++) {
                asm volatile("cp.async.cg.shared.global [%0], [%1], 16;" ::"r"(dst), "l"(src) : "memory");
                dst += 8 * ROW_BYTES;
                src += (size_t)8 * (NHEAD * DH * 2);
            }
        }
    }
    const int warp = __shfl_sync(0xffffffffu, tid >> 5, 0), lane = tid & 31;
    const int rr = !(b & 1) ? b >> 1 : (b & 15) < 12 ? (b >> 4) * 6 + (b >> 1 & 7) : NFFN + (b >> 4) * 2 + (b >> 1 & 1);
    const bool is_wo = !(b & 1) && rr < NWO, is_ffn = (b & 1) && rr < NFFN, is_out = !is_ffn;
    const int og = (rr >> 2) + (b & 1) * 4, oh = og >= 10, oq = (og - 10 * oh) * 4 + (rr & 3);
    const int kg = min(rr / 10, NG - 1), ng = rr % 10;
    const uint32_t bar_full = sbase + SM_BAR;
    const uint32_t bar_empty = sbase + SM_BAR + 128;
    const uint32_t bar_tail = sbase + SM_BAR + 256;
    const uint32_t bar_h = bar_tail + 8 * NTAIL;
    const uint32_t bar_set = bar_h + 8;
    const uint32_t bar_pace = bar_h + 16;
    const uint32_t bar_q = bar_h + 24;
    const uint32_t bar_part = bar_h + 32;
    volatile uint32_t* s_pace = reinterpret_cast<volatile uint32_t*>(smem + SM_MISC + 64);
    auto tail_time = [&](int t) { return s_pace[0] + (s_pace[1] * (((N_TAIL0 - cfg::ADAPT) * 478 + NWP * cfg::T_WO + t) * 256 / 478) >> 8); };

    if (warp == 8) {
        const uint32_t c_start = now_q();
        uint64_t pol_stream;
        asm volatile("createpolicy.fractional.L2::evict_first.b64 %0, 1.0;" : "=l"(pol_stream));
        if (lane == 0) {
#pragma unroll 1
            for (int i = 0; i < NSLOT; i++) { mbar_init(bar_full + 8 * i, 1); mbar_init(bar_empty + 8 * i, 1); }
#pragma unroll 1
            for (int i = 0; i < NTAIL + 5; i++) mbar_init(bar_tail + 8 * i, i == NTAIL ? 8 : i == NTAIL + 3 ? 4 : 1);
            asm volatile("fence.mbarrier_init.release.cluster;" ::: "memory");
        }
        __syncwarp();
        asm volatile("bar.arrive 2, 288;" ::: "memory");
        asm volatile("bar.arrive 3, 64;" ::: "memory");
        asm volatile("bar.arrive 4, 64;" ::: "memory");
        if (lane >= 1 && lane <= 6) asm volatile("prefetch.tensormap [%0];" ::"l"(reinterpret_cast<uint64_t>(&tm.k + (lane - 1))) : "memory");
        if (lane == 0) {
            uint32_t due = c_start + p.t_first, step = p.t_step;
#pragma unroll 1
            for (int n = 0; n < N_TAIL0; n++) {
                const int slot = n & (NSLOT - 1);
                const int use = (n >> 4) + (slot >= QSLOT);
                if (n >= cfg::CAP) mbar_wait(bar_full + 8 * ((n - cfg::CAP) & (NSLOT - 1)), ((n - cfg::CAP) >> 4) & 1);
                if (use >= 1) mbar_wait(bar_empty + 8 * slot, (use - 1) & 1);
                if (n == cfg::ADAPT) { mbar_wait(bar_pace, 0); due = s_pace[0]; step = s_pace[1]; }
                const uint32_t full = bar_full + 8 * slot;
                mbar_expect_tx(full, TILE_BYTES);
                wait_until(due);
                LST(128 + n);
                tma_tile(sbase + SM_RING + slot * TILE_BYTES, &tm.k + (n & 1), ((n >> 1) * SK + (SK - WIN) + b * 32) * 3, full, pol_stream);
                due += step;
            }
            int rel = 0;
            auto released = [&](int end) {
#pragma unroll 1
                for (; rel * TILE_BYTES < end; rel++) mbar_wait(bar_empty + 8 * rel, rel < QSLOT);
            };
            const uint32_t t_wo = step * (cfg::T_WO * 4096 / 478) >> 12;
            if (is_wo) {
#pragma unroll 1
                for (int j = 0; j < NWP; j++) {
                    released((j + 1) * WPIECE);
                    mbar_expect_tx(bar_tail + 8 * j, WPIECE);
                    wait_until(due);
                    LST(128 + N_TAIL0 + j);
                    tma_5d(sbase + j * WPIECE, &tm.wo, ng * 64, j * (NG * 128) + kg * 128, 0, 0, bar_tail + 8 * j);
                    due += t_wo;
                }
            } else {
                due += NWP * t_wo;
            }
            due += 4 * cfg::T_GAP;
            if (is_out) {
                due += step * (cfg::T_W2AT * 4096 / 478) >> 12;
                released(SM_W2 + NDP * PIECE);
#pragma unroll
                for (int j = 0; j < NDP; j++) mbar_expect_tx(bar_tail + 8 * (NWP + j), PIECE);
                sleep_until(due - 4 * 400);
#pragma unroll
                for (int j = 0; j < NDP; j++) {
                    wait_until(due);
                    tma_5d(sbase + SM_W2 + j * PIECE, &tm.w2, oq * 16, (oh * NDP + j) * 256, 0, 0, bar_tail + 8 * (NWP + j));
                    LST(128 + N_TAIL0 + NWP + j);
                    due += step * (cfg::T_W2 * 4096 / 478) >> 12;
                }
            } else if (is_ffn) {
                released(NUP * WPIECE);
#pragma unroll
                for (int j = 0; j <= NUP; j++) mbar_expect_tx(bar_tail + 8 * j, j < NUP - 1 ? WPIECE : WPIECE / 2);
                sleep_until(due - 4 * 400);
#pragma unroll
                for (int j = 0; j <= NUP; j++) {
                    const uint32_t full = bar_tail + 8 * j;
                    const int i = min(j, NUP - 1);
                    wait_until(due);
                    if (j < NUP) tma_5d(sbase + i * WPIECE, &tm.w1, rr * 32, 0, i * 4, 0, full);
                    if (j != NUP - 1) tma_5d(sbase + i * WPIECE + WPIECE / 2, &tm.w3, rr * 32, 0, i * 4, 0, full);
                    LST(128 + N_TAIL0 + j);
                    due += step * ((j < NUP - 1 ? cfg::T_UP : cfg::T_UP2) * 4096 / 478) >> 12;
                }
            }
        }
    } else if (warp == 10) {
        asm volatile("bar.sync 4, 64;" ::: "memory");
        if (lane == 0) {
            uint32_t epoch0;
            asm volatile("ld.relaxed.gpu.global.u32 %0, [%1];" : "=r"(epoch0) : "l"(&p.sc->epoch) : "memory");
            constexpr int MN = 8;
            const uint32_t t0 = now_q();
            uint32_t sa = 0, sb = 0;
#pragma unroll 1
            for (int n = 0; n < cfg::MB + MN; n++) {
#pragma unroll 1
                for (int k = 0; k < 256 && !mbar_try(bar_full + 8 * (n & (NSLOT - 1)), (n >> 4) & 1); k++) { }
                const uint32_t t = now_q() - t0;
                LST(n);
                if ((uint32_t)(n - cfg::MA) < MN) sa += t;
                if (n >= cfg::MB) sb += t;
            }
            const uint32_t mb = t0 + sb / MN;
            unsigned long long* pace = p.sc->pace + ((epoch0 + 1) & 1);
            mbar_wait(bar_set, 0);
            asm volatile("red.relaxed.gpu.global.add.u64 [%0], %1;" ::"l"(pace), "l"((unsigned long long)mb << 32 | min((sb - sa) / (4 * MN), 0xffffu) << 8 | 1) : "memory");
            if (b == 0) p.sc->pace[epoch0 & 1] = 0;
            unsigned long long v;
            uint32_t n = 0, cnt;
#pragma unroll 1
            do {
                __nanosleep(n ? 200 : 1000);
                asm volatile("ld.relaxed.gpu.global.u64 %0, [%1];" : "=l"(v) : "l"(pace) : "memory");
                cnt = (uint32_t)v & 0xff;
                if (++n > SPIN_LIMIT) __trap();
            } while (cnt < NCTA);
            const uint32_t step = min(max(((uint32_t)v >> 8) / (NCTA / 4 * (cfg::MB - cfg::MA)), p.t_step), p.t_smax);
            s_pace[0] = mb + (int)((uint32_t)(v >> 32) - NCTA * mb) / NCTA + step * (2 * (cfg::ADAPT - cfg::MB) - (MN - 1)) / 2 - p.t_lat;
            s_pace[1] = step;
            mbar_arrive(bar_pace);
            LST(89);
        }
    } else if (warp == 9) {
        const uint32_t c_start = now_q();
        uint32_t epoch0;
        asm volatile("ld.relaxed.gpu.global.u32 %0, [%1];" : "=r"(epoch0) : "l"(&p.sc->epoch) : "memory");
        sleep_until(c_start + p.t_first);
        unsigned char* slot[2];
        slot[0] = p.xa + xa_off(o_off(b * 48 + (lane % 6) * 8), lane / 6 & 1);
        slot[1] = p.xa + (is_wo ? xa_off(L_GATHER + (lane >> 4) * HCOPY_BYTES + (kg * D_MODEL + ng * 64 + (lane & 7) * 8) * 2, lane >> 3 & 1)
                                : xa_off(L_ACT + rr * 64 + (lane & 3) * 16, lane >> 2 & 1));
        const int n2 = is_wo ? 16 * cfg::HCOPY : is_ffn ? 8 : 0;
#pragma unroll
        for (int i = 0; i < 2; i++) if (lane < (i ? n2 : 12)) in_st4(slot[i], SENT, SENT, SENT, SENT);
#pragma unroll
        for (int i = 1; i <= cfg::PREPART; i++) pkt_st(p.sc->part + (((NHEAD - i) * 4 + (lane & 3)) * NCTA + b) * 8 + (lane >> 2), 0, 0, 0, epoch0 & 3);
        unsigned char* probe = p.xa + xa_off(L_PROBE + b * 1024 + (lane >> 1 & 7) * 128 + (lane & 1) * 16, lane >> 4);
        in_st4(probe, SENT, SENT, SENT, SENT);
        const bool clr = is_out && !oh && lane < 2;
        if (clr) in_st4(p.out + oq * 16 + lane * 8, 0, 0, 0, 0);
        sleep_until(now_q() + 4 * cfg::RBDELAY + b * 60);
        uint32_t acc = SENT;
#pragma unroll
        for (int i = 0; i < 2; i++) if (lane < (i ? n2 : 12)) acc &= in_ld1(slot[i]);
        if (clr) acc &= ~in_ld1(p.out + oq * 16 + lane * 8);
        if (__any_sync(0xffffffffu, acc != SENT)) __trap();
        int vote = 0;
        uint32_t lat[2] = {0, 0};
#pragma unroll 1
        for (int r = 0; r <= cfg::NPROBE && abs(vote) < cfg::VOTES; r++) {
            __nanosleep(300);
            uint32_t d[2];
#pragma unroll
            for (int i = 0; i < 2; i++) {
                const uint32_t c0 = (uint32_t)clock();
                if (__any_sync(0xffffffffu, in_ld1(p.xa + xa_off(L_PROBE + b * 1024 + (lane & 7) * 128, i)) != SENT)) __trap();
                d[i] = (uint32_t)clock() - c0;
                if (r) lat[i] += min(d[i], 1500u);
            }
            if (r) vote = __shfl_sync(0xffffffffu, vote + (d[1] < d[0]) - (d[0] < d[1]), 0);
        }
        const uint32_t sel = vote ? vote > 0 : lat[1] < lat[0];
        const uint32_t tag = epoch0 + 1;
        asm volatile("bar.sync 3, 64;" ::: "memory");
        if (lane == 0) { s_pace[2] = sel; mbar_arrive(bar_set); }
        {
            mbar_wait(bar_pace, 0);
            sleep_until(s_pace[0] + cfg::KEEP_AT * s_pace[1]);
            const uint32_t t_res = tail_time(cfg::T_RESAT);
            float c[4] = {0.f, 0.f, 0.f, 0.f};
            const uint32_t z[4] = {p.zero, p.zero, p.zero, p.zero};
            uint32_t n = 0;
#pragma unroll 1
            do {
                mma_bf16(c, z, p.zero, p.zero);
                __nanosleep(cfg::KEEP);
                n += 1 + __float_as_uint(c[0]);
            } while (!__all_sync(0xffffffffu, is_ffn ? mbar_test(bar_tail + 8, 0) : (int)(now_q() - t_res) >= 0) && n < SPIN_LIMIT);
            if (is_ffn) {
                unsigned char* adst = p.xa + xa_off(L_ACT + rr * 64 + (lane >> 3) * 16 + (lane & 3) * 4, lane >> 2 & 1);
                uint32_t src = sbase + SM_RED + lane * 8;
                mbar_wait(after(p.zero, bar_h, adst, src), 0);
                const float4 pa = lds128f(sbase + SM_MISC), pb = lds128f(sbase + SM_MISC + 16), pc = lds128f(sbase + SM_MISC + 32), pd = lds128f(sbase + SM_MISC + 48);
                float mean_b, inv_den;
                ln_finish(((pa.y + pa.w) + (pb.y + pb.w)) + ((pc.y + pc.w) + (pd.y + pd.w)),
                          ((pa.x + pa.z) + (pb.x + pb.z)) + ((pc.x + pc.z) + (pd.x + pd.z)), mean_b, inv_den);
                float2 r[8];
#define S_(c) (((r[0].c + r[1].c) + (r[2].c + r[3].c)) + ((r[4].c + r[5].c) + (r[6].c + r[7].c)))
                asm volatile("bar.sync %0, 288;" ::"r"(after(p.zero, 8, inv_den, mean_b)) : "memory");
#pragma unroll
                for (int i = 0; i < 8; i++) r[i] = lds64f(src + i * 256);
                const float gate = bfr(fmaf(-mean_b, S_(y), S_(x)) * inv_den);
                const float silu = bfr(__fdividef(gate, 1.0f + ex2(-gate * L2E)));
                asm volatile("bar.sync %0, 288;" ::"r"(after(p.zero, 5, silu)) : "memory");
#pragma unroll
                for (int i = 0; i < 8; i++) r[i] = lds64f(src + 2048 + i * 256);
                const float act = silu * bfr(fmaf(-mean_b, S_(y), S_(x)) * inv_den);
#undef S_
                const float oth = __shfl_xor_sync(0xffffffffu, act, 4);
                in_st1(adst, __uint_as_float((lane & 4) ? pack_bf(act, oth) : pack_bf(oth, act)));
                if (lane == 0) LST(110);
            }
            if (is_out) {
                const int col = oq * 16 + (lane & 15);
                float res = 0.f;
                if (!oh) {
                    uint32_t u[NG], xv;
                    asm volatile("ld.global.nc.u16 %0, [%1];" : "=r"(xv) : "l"(p.x + col));
                    n = 0;
#pragma unroll 1
                    do {
#pragma unroll
                        for (int i = 0; i < NG; i++) u[i] = in_ld1(p.xa + xa_off(L_GATHER + rr % cfg::HCOPY * HCOPY_BYTES + (i * D_MODEL + (col & ~1)) * 2, sel));
                        if (++n > SPIN_LIMIT) __trap();
                    } while (__any_sync(0xffffffffu, max(max(max(u[0], u[1]), max(u[2], u[3])), max(u[4], u[5])) == SENT));
                    if (b == 0 && lane == 0) p.sc->epoch = tag;
#define F_(i) ((lane & 1) ? bf_hi(u[i]) : bf_lo(u[i]))
                    res = bfr(bf_lo(xv) + bfr(((F_(0) + F_(1)) + (F_(2) + F_(3))) + (F_(4) + F_(5))));
#undef F_
                }
                mma_bf16(c, z, p.zero, p.zero);
                mbar_wait(after(p.zero, bar_tail + 8 * NWP, c[0]), 0);
                mma_bf16(c, z, p.zero, p.zero);
                res += c[0];
                __nv_bfloat16* dst = p.out + (col & ~1);
                uint32_t src = sbase + SM_HN + (lane & 15) * 48;
                asm volatile("bar.sync %0, 288;" ::"r"(after(p.zero, 5, src, dst, res)) : "memory");
                const float4 ra = lds128f(src), rb = lds128f(src + 16);
                const float e = ((ra.x + ra.y) + (ra.z + ra.w)) + (((rb.x + rb.y) + (rb.z + rb.w)) + res);
                if (lane < 16) asm volatile("red.relaxed.gpu.global.add.noftz.bf16x2 [%0], %1;" ::"l"(dst), "r"((lane & 1) ? pack_bf(e, 0.f) : pack_bf(0.f, e)) : "memory");
                if (lane == 0) LST(96);
            }
        }
    } else {
        const int t = lane & 3, g = lane >> 2;
        const int arow = (lane & 7) + ((lane >> 4) << 3), ahalf = (lane >> 3) & 1;
        const int hcol = warp * 80 + min(lane, 4 * NUP - 1) * 4;
        uint32_t epoch0;
        uint2 xres;
        const char* xb = reinterpret_cast<const char*>(p.x);
        asm volatile("ld.relaxed.gpu.global.u32 %0, [%1];" : "=r"(epoch0) : "l"(&p.sc->epoch) : "memory");
        asm volatile("ld.global.nc.v2.u32 {%0, %1}, [%2];" : "=r"(xres.x), "=r"(xres.y) : "l"(xb + hcol * 2));
        uint64_t* q1dst = p.sc->q1 + ((head * 4 + (warp & 3)) * 4 + sp) * 48 + min(t, 2) * 16 + g;
        uint4* q2dst = p.sc->q2 + (head * 8 + sp * 2 + lane / 12) * 4 + t;
        if (warp == 7) {
            uint2 xu[5];
#pragma unroll
            for (int i = 0; i < 5; i++) asm volatile("ld.global.nc.v2.u32 {%0, %1}, [%2];" : "=r"(xu[i].x), "=r"(xu[i].y) : "l"(xb + i * 256 + lane * 8));
            float s1 = 0.f, s2 = 0.f, mean_b, inv_den;
#pragma unroll
            for (int i = 0; i < 5; i++) {
                const float a0 = bf_lo(xu[i].x), a1 = bf_hi(xu[i].x), a2 = bf_lo(xu[i].y), a3 = bf_hi(xu[i].y);
                s1 += (a0 + a1) + (a2 + a3);
                s2 = fmaf(a0, a0, fmaf(a1, a1, fmaf(a2, a2, fmaf(a3, a3, s2))));
            }
#pragma unroll
            for (int o = 16; o > 0; o >>= 1) { s1 += __shfl_xor_sync(0xffffffffu, s1, o); s2 += __shfl_xor_sync(0xffffffffu, s2, o); }
            ln_finish(s1, s2, mean_b, inv_den);
#define N_(v) (bfr((v) - mean_b) * inv_den)
#pragma unroll
            for (int i = 0; i < 5; i++)
                sts64(sbase + SM_HN + i * 256 + lane * 8, pack_bf(N_(bf_hi(xu[i].x)), N_(bf_lo(xu[i].x))), pack_bf(N_(bf_hi(xu[i].y)), N_(bf_lo(xu[i].y))));
#undef N_
        } else {
            if (warp < 4 && t < 3) { ll_st1(q1dst, 0.f, 0); ll_st1(q1dst + 8, 0.f, 0); }
            if (warp == 4 && lane < 24 && lane % 12 < 4) pkt_st(q2dst, 0, 0, 0, 0);
        }
        asm volatile("cp.async.wait_all;" ::: "memory");
        if (lane == 0) LST(80 + warp);
        asm volatile("bar.sync 2, 288;" ::: "memory");
        const uint32_t tag = epoch0 + 1;
        auto block = [&](int i) { const int unit = arow * 3 + (i >> 2); return sbase + SM_RING + unit * 128 + ((((i & 3) * 2 + ahalf) ^ (unit & 7)) << 4); };

        if (warp < 4) {
            {
                float c[3][4];
                uint32_t wa[3];
#pragma unroll
                for (int k = 0; k < 3; k++) { c[k][0] = c[k][1] = c[k][2] = c[k][3] = 0.f; wa[k] = block(warp * 3 + k) + QSLOT * TILE_BYTES; }
                const uint32_t xa = sbase + SM_HN + sp * 320 + t * 4;
#pragma unroll 2
                for (int ks = 0; ks < 2 * NQT; ks++) {
                    const uint32_t b0 = lds32(xa + ks * 32), b1 = lds32(xa + ks * 32 + 16);
#pragma unroll
                    for (int k = 0; k < 3; k++) { uint32_t a[4]; ldsm_x4_t(a, wa[k] + ks * (TILE_BYTES / 2)); mma_bf16(c[k], a, b0, b1); }
                }
                if (t < 3) {
                    ll_st1(q1dst, t == 0 ? c[0][0] : t == 1 ? c[1][0] : c[2][0], tag);
                    ll_st1(q1dst + 8, t == 0 ? c[0][2] : t == 1 ? c[1][2] : c[2][2], tag);
                }
                asm volatile("bar.sync 6, 128;" ::: "memory");
                if (tid < NQT) mbar_arrive(bar_empty + 8 * (QSLOT + tid));
                if (tid == 0) LST(90);
            }
            const uint32_t ta[3] = {block(0), block(4), block(8)};
            mbar_wait(bar_q, 0);
            if (tid == 0) LST(92);
#pragma unroll 1
            for (int h = warp; h < NHEAD; h += 4) {
                const int slot = (2 * h) & (NSLOT - 1);
                const uint32_t par = (h >> 3) & 1;
                uint32_t qf[24];
#pragma unroll
                for (int i = 0; i < 6; i++) { const uint4 v = lds128(sbase + SM_Q + h * ROW_BYTES + t * 96 + i * 16); qf[4 * i] = v.x; qf[4 * i + 1] = v.y; qf[4 * i + 2] = v.z; qf[4 * i + 3] = v.w; }
                uint32_t ad[12];
#pragma unroll
                for (int i = 0; i < 12; i++) ad[i] = (ta[i >> 2] + slot * TILE_BYTES) ^ ((i & 3) << 5);
                float sc[4][4];
#pragma unroll
                for (int j = 0; j < 4; j++) sc[j][0] = sc[j][1] = sc[j][2] = sc[j][3] = 0.f;
                mbar_wait(bar_full + 8 * slot, par);
#pragma unroll
                for (int i = 0; i < 12; i++) {
                    const uint32_t a[4] = {qf[2 * i], qf[2 * i], qf[2 * i + 1], qf[2 * i + 1]};
                    uint32_t k0[4], k1[4];
                    ldsm_x4(k0, ad[i]); ldsm_x4(k1, ad[i] + TILE_BYTES / 2);
                    mma_bf16(sc[0], a, k0[0], k0[1]); mma_bf16(sc[1], a, k0[2], k0[3]);
                    mma_bf16(sc[2], a, k1[0], k1[1]); mma_bf16(sc[3], a, k1[2], k1[3]);
                }
                const float scale = 0.07216878364870322f;
                float m = -INFINITY;
#pragma unroll
                for (int j = 0; j < 4; j++) { sc[j][0] = bfr(bfr(sc[j][0]) * scale); sc[j][1] = bfr(bfr(sc[j][1]) * scale); m = fmaxf(m, fmaxf(sc[j][0], sc[j][1])); }
                if (lane == 0) mbar_arrive(after(p.zero, bar_empty + 8 * slot, m));
                m = fmaxf(m, __shfl_xor_sync(0xffffffffu, m, 1));
                m = fmaxf(m, __shfl_xor_sync(0xffffffffu, m, 2));
                float l = 0.f;
                uint32_t pf[4];
#pragma unroll
                for (int j = 0; j < 4; j++) {
                    const float p0 = ex2((sc[j][0] - m) * L2E), p1 = ex2((sc[j][1] - m) * L2E);
                    l += p0 + p1;
                    const uint32_t hi = pack_bf(p1, p0);
                    pf[j] = (g & 1) ? pack_bf(p1 - bf_hi(hi), p0 - bf_lo(hi)) : hi;
                }
                l += __shfl_xor_sync(0xffffffffu, l, 1);
                l += __shfl_xor_sync(0xffffffffu, l, 2);
                const uint32_t meta = (__float_as_uint(m) & 0xffff0000u) | ((__float_as_uint(l) - 0x3f800000u + 0x800u) >> 10 & 0xfffcu) | (tag & 3);
                uint32_t pq[4][4];
#pragma unroll
                for (int q = 0; q < 4; q++)
#pragma unroll
                    for (int j = 0; j < 4; j++) pq[q][j] = (g >> 1) == q ? pf[j] : 0;
                float o[6][4];
#pragma unroll
                for (int k = 0; k < 6; k++) o[k][0] = o[k][1] = o[k][2] = o[k][3] = 0.f;
                uint4* dst = p.sc->part + ((h * 4 + t) * NCTA + b) * 8 + g;
                mbar_wait(after(p.zero, bar_full + 8 * slot + 8, meta, dst, pq[0][0], pq[1][1], pq[2][2], pq[3][3]), par);
#pragma unroll
                for (int i = 0; i < 12; i++) {
                    uint32_t v0[4], v1[4];
                    ldsm_x4_t(v0, ad[i] + TILE_BYTES); ldsm_x4_t(v1, ad[i] + TILE_BYTES + TILE_BYTES / 2);
                    mma_bf16(o[i % 3], v0, pq[i / 3][0], pq[i / 3][1]);
                    mma_bf16(o[3 + i % 3], v1, pq[i / 3][2], pq[i / 3][3]);
                }
                uint32_t w[3];
#pragma unroll
                for (int k = 0; k < 3; k++) w[k] = pack_bf((o[k][2] + o[k][3]) + (o[k + 3][2] + o[k + 3][3]), (o[k][0] + o[k][1]) + (o[k + 3][0] + o[k + 3][1]));
                pkt_st(dst, w[0], w[1], w[2], meta);
                if (lane == 0) {
                    mbar_arrive(after(p.zero, bar_empty + 8 * slot + 8, w[0], w[1], w[2]));
                    if (h == head) mbar_arrive(bar_part);
                }
            }
            if (tid == 96) LST(91);
        } else {
            const int u = tid - 128;
            uint32_t n = 0;
            if (warp == 4) {
                const uint4* src = reinterpret_cast<const uint4*>(p.sc->q1 + (head * 4 + sp) * 4 * 48) + min(lane, 23);
                uint4 v[4];
                __nanosleep(cfg::QDELAY);
#pragma unroll 1
                do {
                    if (n) __nanosleep(cfg::QSLEEP);
#pragma unroll
                    for (int i = 0; i < 4; i++) v[i] = ll_ld2(src + i * 24);
                    if (++n > SPIN_LIMIT) __trap();
                } while (__any_sync(0xffffffffu, ((v[0].y ^ tag) | (v[0].w ^ tag) | (v[1].y ^ tag) | (v[1].w ^ tag) | (v[2].y ^ tag) | (v[2].w ^ tag) | (v[3].y ^ tag) | (v[3].w ^ tag)) != 0));
#define F_(c) ((__uint_as_float(v[0].c) + __uint_as_float(v[1].c)) + (__uint_as_float(v[2].c) + __uint_as_float(v[3].c)))
                const uint32_t w0 = pack_bf(F_(z), F_(x));
#undef F_
                const uint32_t w1 = __shfl_down_sync(0xffffffffu, w0, 4), w2 = __shfl_down_sync(0xffffffffu, w0, 8);
                if (lane < 24 && lane % 12 < 4) pkt_st(q2dst, w0, w1, w2, tag);
            }
            asm volatile("bar.sync 7, 128;" ::: "memory");
            uint4 v[8];
            {
#pragma unroll
                for (int i = 0; i < 8; i++) v[i] = make_uint4(0, 0, 0, ~tag);
                __nanosleep(cfg::QDELAY2);
                n = 0;
                bool ok;
#pragma unroll 1
                do {
                    if (n) __nanosleep(cfg::QSLEEP);
#pragma unroll
                    for (int i = 0; i < 8; i++) pkt_ldp(p.sc->q2 + u + i * 128, v[i], v[i].w != tag);
                    ok = true;
#pragma unroll
                    for (int i = 0; i < 8; i++) ok &= v[i].w == tag;
                    if (++n > SPIN_LIMIT) __trap();
                } while (!__all_sync(0xffffffffu, ok));
                const uint32_t qd = sbase + SM_Q + (u >> 5) * ROW_BYTES + t * 96 + g * 12;
#pragma unroll
                for (int i = 0; i < 8; i++) {
                    sts32(qd + i * 4 * ROW_BYTES, __uint_as_float(v[i].x)); sts32(qd + i * 4 * ROW_BYTES + 4, __uint_as_float(v[i].y)); sts32(qd + i * 4 * ROW_BYTES + 8, __uint_as_float(v[i].z));
                }
                __syncwarp();
                if (lane == 0) mbar_arrive(bar_q);
            }
            {
                const uint4* src = p.sc->part + b * NCTA * 8 + u;
                const uint32_t rdst = sbase + SM_RED + (warp - 4) * 256 + min(lane >> 3, 2) * 64 + (lane & 7) * 4;
                const uint32_t lo = o_off(b * 48 + (min(lane, 23) >> 3) * 16) + (lane & 3) * 8 + (lane & 4);
                unsigned char *od0 = p.xa + xa_off(lo, 0), *od1 = p.xa + xa_off(lo, 1);
#pragma unroll
                for (int i = 0; i < 8; i++) v[i].w = ~tag;
                mbar_wait(bar_set, 0);
                mbar_wait(after(p.zero, bar_part, src, rdst, od0, od1), 0);
                {
                    const uint32_t at = now_q() + 4 * min(cfg::PDELAY, cfg::PDELAY_LAST + (NHEAD - 1 - head) * cfg::PDELAY_STEP);
                    sleep_until(at - 4 * 300);
                    wait_until(at);
                }
                n = 0;
                uint32_t bad;
#pragma unroll 1
                do {
                    if (n && head != NHEAD - 1) __nanosleep(cfg::QSLEEP);
#pragma unroll
                    for (int i = 0; i < 8; i++) pkt_ldp(src + i * 128, v[i], ((v[i].w ^ tag) & 3) != 0);
                    bad = 0;
#pragma unroll
                    for (int i = 0; i < 8; i++) bad |= v[i].w ^ tag;
                    if (++n > SPIN_LIMIT) __trap();
                } while (__any_sync(0xffffffffu, (bad & 3) != 0));
                if (u == 0) LST(119);
                float m = -INFINITY;
#pragma unroll
                for (int i = 0; i < 8; i++) m = fmaxf(m, bf_hi(v[i].w));
                m = fmaxf(m, __shfl_xor_sync(0xffffffffu, m, 8));
                m = fmaxf(m, __shfl_xor_sync(0xffffffffu, m, 16));
                float a[7] = {0.f, 0.f, 0.f, 0.f, 0.f, 0.f, 0.f};
#pragma unroll
                for (int i = 0; i < 8; i++) {
                    const float f = ex2((bf_hi(v[i].w) - m) * L2E);
                    a[0] = fmaf(f, bf_lo(v[i].x), a[0]); a[1] = fmaf(f, bf_hi(v[i].x), a[1]);
                    a[2] = fmaf(f, bf_lo(v[i].y), a[2]); a[3] = fmaf(f, bf_hi(v[i].y), a[3]);
                    a[4] = fmaf(f, bf_lo(v[i].z), a[4]); a[5] = fmaf(f, bf_hi(v[i].z), a[5]);
                    a[6] = fmaf(f, __uint_as_float(((v[i].w & 0xfffcu) << 10) + 0x3f800000u), a[6]);
                }
#pragma unroll
                for (int o = 8; o < 32; o <<= 1)
#pragma unroll
                    for (int i = 0; i < 7; i++) a[i] += __shfl_xor_sync(0xffffffffu, a[i], o);
                if (lane < 24) { sts32(rdst, lane < 8 ? a[0] : lane < 16 ? a[2] : a[4]); sts32(rdst + 32, lane < 8 ? a[1] : lane < 16 ? a[3] : a[5]); }
                if (lane == 24) sts64(rdst + 64, __float_as_uint(a[6]), __float_as_uint(m));
                asm volatile("bar.sync 7, 128;" ::: "memory");
                if (warp == 4) {
                    float2 st[4], r[4];
#pragma unroll
                    for (int i = 0; i < 4; i++) { st[i] = lds64f(sbase + SM_RED + i * 256 + 192); r[i] = lds64f(sbase + SM_RED + i * 256 + lane * 8); }
                    const float mm = fmaxf(fmaxf(st[0].y, st[1].y), fmaxf(st[2].y, st[3].y));
                    float den = 0.f, x0 = 0.f, x1 = 0.f;
#pragma unroll
                    for (int i = 0; i < 4; i++) { const float f = ex2((st[i].y - mm) * L2E); den = fmaf(f, st[i].x, den); x0 = fmaf(f, r[i].x, x0); x1 = fmaf(f, r[i].y, x1); }
                    const float inv = rcp_fast(den);
                    const float ow = __uint_as_float(pack_bf(x1 * inv, x0 * inv));
                    if (lane < 24) { in_st1(od0, ow); in_st1(od1, ow); }
                    if (lane == 0) LST(120);
                }
            }
        }
        mbar_wait(bar_pace, 0);
        const uint32_t msel = s_pace[2];
        cons_sync();
        if (is_wo) {
            uint32_t wa = sbase + (warp * 16 + arow) * 128 + ((ahalf ^ (lane & 7)) << 4);
            uint32_t pw = sbase + SM_RED + (warp * 64 + t * 16 + (lane >> 2)) * 4, pr = sbase + SM_RED + lane * 8;
            unsigned char* gdst = p.xa + xa_off(L_GATHER + (warp >> 1) % cfg::HCOPY * HCOPY_BYTES + (kg * D_MODEL + ng * 64 + lane * 2) * 2, warp & 1);
            const unsigned char* osrc = p.xa + xa_off(L_O + kg * 2048, msel) + warp * 32 + t * 8;
            uint2 ov[NWP];
#pragma unroll
            for (int j = 0; j < NWP; j++) ov[j] = make_uint2(SENT, SENT);
            auto gather = [&](int j0, int j1) {
                uint32_t n = 0;
#pragma unroll 1
                while (true) {
                    uint32_t mx = 0;
#pragma unroll
                    for (int j = j0; j < j1; j++) mx = max(mx, max(ov[j].x, ov[j].y));
                    if (!__any_sync(0xffffffffu, mx == SENT)) break;
#pragma unroll
                    for (int j = j0; j < j1; j++) in_ld2p(osrc + j * 256, ov[j], !in_ok(ov[j]));
                    if (++n > SPIN_LIMIT) __trap();
                }
            };
            float cw[4][4];
#pragma unroll
            for (int i = 0; i < 4; i++) cw[i][0] = cw[i][1] = cw[i][2] = cw[i][3] = 0.f;
            mbar_wait(after(p.zero, bar_tail + 8, osrc, wa, pw, pr, gdst), 0);
#pragma unroll
            for (int j = 0; j < NWP; j++) in_ld2p(osrc + j * 256, ov[j], true);
            gather(0, NWP - 1);
#pragma unroll
            for (int j = 0; j < NWP; j++) {
                if (j == NWP - 1) { gather(NWP - 1, NWP); if (tid == 224) LST(93); }
                mbar_wait(bar_tail + 8 * j, 0);
                if (j == NWP - 3) in_ld2p(osrc + (NWP - 1) * 256, ov[NWP - 1], !in_ok(ov[NWP - 1]));
                uint32_t a[4][4];
#pragma unroll
                for (int i = 0; i < 4; i++) ldsm_x4_t(a[i], (wa ^ (i << 5)) + j * WPIECE);
#pragma unroll
                for (int i = 0; i < 4; i++) mma_bf16(cw[i], a[i], ov[j].x, ov[j].y);
            }
#define SEL_(e) ((t & 2) ? ((t & 1) ? cw[3][e] : cw[2][e]) : ((t & 1) ? cw[1][e] : cw[0][e]))
            sts32(pw, SEL_(0)); sts32(pw + 32, SEL_(2));
#undef SEL_
            cons_sync();
            if (warp < 2 * cfg::HCOPY) {
                float2 r[8];
#pragma unroll
                for (int i = 0; i < 8; i++) r[i] = lds64f(pr + i * 256);
#define S_(c) (((r[0].c + r[1].c) + (r[2].c + r[3].c)) + ((r[4].c + r[5].c) + (r[6].c + r[7].c)))
                in_st1(gdst, __uint_as_float(pack_bf(S_(y), S_(x))));
#undef S_
            }
            if (tid == 0) LST(94);
        } else if (is_ffn) {
            uint32_t w13a = sbase + (warp * 16 + arow) * 64 + ((ahalf ^ (lane >> 1 & 3)) << 4);
            uint32_t red_dst = sbase + SM_RED + tid * 8;
            uint32_t stat = sbase + SM_MISC + warp * 8;
            uint32_t aw[NUP][4][4];
            auto load_w13 = [&](int i) {
                mbar_wait(bar_tail + 8 * i, 0);
#pragma unroll
                for (int k = 0; k < 4; k++) ldsm_x4_t(aw[i][k], (w13a ^ (k << 5 & 32)) + i * WPIECE + (k >> 1) * (WPIECE / 2));
            };
            uint32_t hp0, hp1;
            {
                const unsigned char* gsrc[NG];
                uint2 u[NG];
#pragma unroll
                for (int i = 0; i < NG; i++) { u[i] = make_uint2(0, 0); gsrc[i] = p.xa + xa_off(L_GATHER + rr % cfg::HCOPY * HCOPY_BYTES + (i * D_MODEL + hcol) * 2, msel); }
                const uint32_t at = after(p.zero, tail_time(cfg::T_HAT), gsrc[0], gsrc[1], gsrc[2], gsrc[3], gsrc[4], gsrc[5], w13a, red_dst, stat);
                sleep_until(at - 4 * 300);
                wait_until(at);
                LSC(0);
#pragma unroll
                for (int i = 0; i < NG; i++) in_ld2p(gsrc[i], u[i], lane < 4 * NUP);
                load_w13(0);
                LSCD(1, u[0].x ^ u[1].x ^ u[2].x ^ u[3].x ^ u[4].x ^ u[5].x);
                uint32_t n = 0;
#pragma unroll 1
                while (__any_sync(0xffffffffu, max(max(max(u[0].x, u[0].y), max(u[1].x, u[1].y)), max(max(max(u[2].x, u[2].y), max(u[3].x, u[3].y)),
                                                                                                    max(max(u[4].x, u[4].y), max(u[5].x, u[5].y)))) == SENT)) {
#pragma unroll
                    for (int i = 0; i < NG; i++) in_ld2p(gsrc[i], u[i], !in_ok(u[i]));
                    if (++n > SPIN_LIMIT) __trap();
                }
                if (tid == 96) LST(100);
                LSC(2);
#define F_(f, c) (f(xres.c) + bfr(((f(u[0].c) + f(u[1].c)) + (f(u[2].c) + f(u[3].c))) + (f(u[4].c) + f(u[5].c))))
                hp0 = pack_bf(F_(bf_hi, x), F_(bf_lo, x));
                hp1 = pack_bf(F_(bf_hi, y), F_(bf_lo, y));
#undef F_
            }
            {
                uint32_t b0[NUP], b1[NUP];
                float cf[4][4], cs[2][4];
#pragma unroll
                for (int e = 0; e < 4; e++) cf[0][e] = cf[1][e] = cf[2][e] = cf[3][e] = cs[0][e] = cs[1][e] = 0.f;
#pragma unroll
                for (int i = 0; i < NUP; i++) {
                    const uint32_t h0 = __shfl_sync(0xffffffffu, hp0, i * 4 + t), h1 = __shfl_sync(0xffffffffu, hp1, i * 4 + t);
                    b0[i] = (lane & 4) ? 0x3f803f80u : h0;
                    b1[i] = (lane & 4) ? 0x3f803f80u : h1;
                    const uint32_t sa[4] = {h0, h0, h1, h1};
                    mma_bf16(cs[i & 1], sa, b0[i], b1[i]);
                }
                auto mma_w13 = [&](int i) {
#pragma unroll
                    for (int k = 0; k < 4; k++) mma_bf16(cf[k], aw[i][k], b0[i], b1[i]);
                };
                if (lane == 0) sts64(stat, __float_as_uint(cs[0][0] + cs[1][0]), __float_as_uint(cs[0][1] + cs[1][1]));
                __syncwarp();
                if (lane == 0) mbar_arrive(bar_h);
                mma_w13(0);
                LSC(3);
#pragma unroll
                for (int i = 1; i < NUP - 1; i++) { load_w13(i); mma_w13(i); }
                LSC(4);
#define SEL_(k, e) ((t & 2) ? ((t & 1) ? cf[k + 1][e + 2] : cf[k + 1][e]) : ((t & 1) ? cf[k][e + 2] : cf[k][e]))
#pragma unroll
                for (int m = 0; m < 2; m++) {
                    mbar_wait(bar_tail + 8 * (NUP - 1 + m), 0);
#pragma unroll
                    for (int k = 2 * m; k < 2 * m + 2; k++) ldsm_x4_t(aw[NUP - 1][k], (w13a ^ (k << 5 & 32)) + (NUP - 1) * WPIECE + m * (WPIECE / 2));
#pragma unroll
                    for (int k = 2 * m; k < 2 * m + 2; k++) mma_bf16(cf[k], aw[NUP - 1][k], b0[NUP - 1], b1[NUP - 1]);
                    sts64(red_dst + m * 2048, __float_as_uint(SEL_(2 * m, 0)), __float_as_uint(SEL_(2 * m, 1)));
                    if (m == 0) asm volatile("bar.arrive 8, 288;" ::: "memory");
                }
                LSC(6);
#undef SEL_
            }
            LSC(7);
            asm volatile("bar.arrive 5, 288;" ::: "memory");
        }
        if (is_out) {
            uint32_t w2a = sbase + SM_W2 + (warp * 32 + arow) * 32 + ((ahalf ^ (lane >> 2 & 1)) << 4);
            uint32_t ydst = sbase + SM_HN + ((t & 1) * 8 + (lane >> 2)) * 48 + warp * 4;
            const unsigned char* asrc = p.xa + xa_off(L_ACT, msel) + oh * (NDP * 512) + warp * 64 + t * 16;
            const uint32_t bar_w2 = after(p.zero, bar_tail + 8 * NWP, w2a, ydst, asrc);
            uint32_t a[NDP][2][4];
            auto load_w2 = [&](int i) {
                mbar_wait(bar_w2 + 8 * i, 0);
                ldsm_x4_t(a[i][0], w2a + i * PIECE); ldsm_x4_t(a[i][1], w2a + i * PIECE + 512);
            };
#pragma unroll
            for (int i = 0; i < cfg::AGATE; i++) load_w2(i);
            uint4 u[NDP];
            LSC(0);
#pragma unroll
            for (int i = 0; i < NDP; i++) u[i] = in_ld4(asrc + i * 512);
            uint32_t n = 0;
#pragma unroll 1
            while (true) {
                uint32_t m[NDP];
#pragma unroll
                for (int i = 0; i < NDP; i++) m[i] = max(max(u[i].x, u[i].y), max(u[i].z, u[i].w));
                if (!__any_sync(0xffffffffu, max(max(m[0], m[1]), m[2]) == SENT)) break;
#pragma unroll
                for (int i = 0; i < NDP; i++) in_ld4p(asrc + i * 512, u[i], m[i] == SENT);
                if (++n > SPIN_LIMIT) __trap();
            }
            LSC(12);
            if (tid == 96) LST(118);
            float cy[2 * NDP][4];
#pragma unroll
            for (int i = 0; i < NDP; i++) {
#pragma unroll
                for (int e = 0; e < 4; e++) cy[2 * i][e] = cy[2 * i + 1][e] = 0.f;
                if (i >= cfg::AGATE) load_w2(i);
                mma_bf16(cy[2 * i], a[i][0], u[i].x, u[i].y);
                mma_bf16(cy[2 * i + 1], a[i][1], u[i].z, u[i].w);
            }
#define Y_(e) (((cy[0][e] + cy[1][e]) + (cy[2][e] + cy[3][e])) + (cy[4][e] + cy[5][e]))
            const float y = (t & 1) ? Y_(2) : Y_(0);
#undef Y_
            if (t < 2) sts32(ydst, y);
            LSC(13);
            asm volatile("bar.arrive 5, 288;" ::: "memory");
        }
    }
}

typedef CUresult (*EncodeTiledFn)(CUtensorMap*, CUtensorMapDataType, cuuint32_t, void*, const cuuint64_t*, const cuuint64_t*,
                                  const cuuint32_t*, const cuuint32_t*, CUtensorMapInterleave, CUtensorMapSwizzle,
                                  CUtensorMapL2promotion, CUtensorMapFloatOOBfill);

void make_map(EncodeTiledFn fn, CUtensorMap* tm, const void* w, const int (&d)[5], const int (&st)[4], const int (&bx)[5],
              CUtensorMapSwizzle sw, int promo) {
    cuuint64_t dims[5], strides[4];
    cuuint32_t box[5], estr[5];
    for (int i = 0; i < 5; i++) { dims[i] = (cuuint64_t)d[i]; box[i] = (cuuint32_t)bx[i]; estr[i] = 1; }
    for (int i = 0; i < 4; i++) strides[i] = (cuuint64_t)st[i];
    fn(tm, CU_TENSOR_MAP_DATA_TYPE_BFLOAT16, 5, const_cast<void*>(w), dims, strides, box, estr, CU_TENSOR_MAP_INTERLEAVE_NONE, sw,
       (CUtensorMapL2promotion)promo, CU_TENSOR_MAP_FLOAT_OOB_FILL_NONE);
}

}

extern "C" void kernel_launch(void* const* d_in, const int* in_sizes, int n_in, void* d_out, int out_size) {
    (void)in_sizes; (void)n_in; (void)out_size;
    static EncodeTiledFn encode = nullptr;
    static Scratch* scratch = nullptr;
    static unsigned char* xarea = nullptr;
    static double tscale = 1.0;
    if (!encode) {
        void* sp = nullptr;
        cudaGetSymbolAddress(&sp, g_scratch);
        scratch = reinterpret_cast<Scratch*>(sp);
        cudaGetSymbolAddress(&sp, g_xarea);
        xarea = reinterpret_cast<unsigned char*>((reinterpret_cast<uintptr_t>(sp) + XA_ALIGN - 1) / XA_ALIGN * XA_ALIGN);
        void* fn = nullptr;
        cudaDriverEntryPointQueryResult st;
        cudaGetDriverEntryPoint("cuTensorMapEncodeTiled", &fn, cudaEnableDefault, &st);
        encode = reinterpret_cast<EncodeTiledFn>(fn);
        int dev = 0, khz = 0, bits = 0;
        cudaGetDevice(&dev);
        cudaDeviceGetAttribute(&khz, cudaDevAttrMemoryClockRate, dev);
        cudaDeviceGetAttribute(&bits, cudaDevAttrGlobalMemoryBusWidth, dev);
        if (khz > 0 && bits > 0) tscale = (2619000.0 * 5120.0) / ((double)khz * bits);
        cudaFuncSetAttribute(fused_decode_kernel, cudaFuncAttributeMaxDynamicSharedMemorySize, SM_TOTAL);
    }
    KParams p;
    p.x = (const __nv_bfloat16*)d_in[0];
    p.wq = (const __nv_bfloat16*)d_in[3];
    p.out = (__nv_bfloat16*)d_out;
    p.sc = scratch;
    p.xa = xarea;
    p.zero = 0;
    p.t_first = (uint32_t)(4 * cfg::T_FIRST * tscale);
    p.t_step = (uint32_t)(cfg::T_STEP * tscale);
    p.t_smax = (uint32_t)(cfg::T_SMAX * tscale);
    p.t_lat = (uint32_t)(4 * (450 + (cfg::T_LAT - 450) * tscale));
    TMaps tm;
    constexpr int R1 = FF * 2, R2 = D_MODEL * 2;
    make_map(encode, &tm.k, d_in[1], {64, NHEAD * SK * 3, 1, 1, 1}, {128, 128, 128, 128}, {64, 96, 1, 1, 1}, CU_TENSOR_MAP_SWIZZLE_128B, cfg::PROMO_KV);
    make_map(encode, &tm.v, d_in[2], {64, NHEAD * SK * 3, 1, 1, 1}, {128, 128, 128, 128}, {64, 96, 1, 1, 1}, CU_TENSOR_MAP_SWIZZLE_128B, cfg::PROMO_KV);
    make_map(encode, &tm.wo, d_in[4], {D_MODEL, NHEAD * DH, 1, 1, 1}, {R2, R2, R2, R2}, {64, 128, 1, 1, 1}, CU_TENSOR_MAP_SWIZZLE_128B, cfg::PROMO_WO);
    make_map(encode, &tm.w1, d_in[6], {FF, 2, 20, 2, 8}, {R1, 4 * R1, 2 * R1, 80 * R1}, {32, 2, 4, 2, 8}, CU_TENSOR_MAP_SWIZZLE_64B, cfg::PROMO_W13);
    make_map(encode, &tm.w3, d_in[7], {FF, 2, 20, 2, 8}, {R1, 4 * R1, 2 * R1, 80 * R1}, {32, 2, 4, 2, 8}, CU_TENSOR_MAP_SWIZZLE_64B, cfg::PROMO_W13);
    make_map(encode, &tm.w2, d_in[8], {D_MODEL, FF, 1, 1, 1}, {R2, R2, R2, R2}, {16, 256, 1, 1, 1}, CU_TENSOR_MAP_SWIZZLE_32B, cfg::PROMO_W2);
    fused_decode_kernel<<<NCTA, NTHREADS, SM_TOTAL, cudaStreamPerThread>>>(p, tm);
}
```

```cpp
#include <cuda_runtime.h>
#include <cuda_bf16.h>
#include <cuda.h>
#include <stdint.h>
#include <math.h>

namespace {

constexpr int D_MODEL = 640;
constexpr int NHEAD = 32;
constexpr int DH = 192;
constexpr int SK = 32768;
constexpr int WIN = 4096;
constexpr int FF = 1536;

constexpr int NCTA = 128;
constexpr int NCONS = 256;
constexpr int NTHREADS = NCONS + 96;
constexpr int ROW_BYTES = DH * 2;
constexpr int TILE_BYTES = 32 * ROW_BYTES;
constexpr int NSLOT = 16;
constexpr int NQT = 5;
constexpr int QSLOT = NSLOT - NQT;
constexpr int NWO = 60;
constexpr int NG = 6;
constexpr int NFFN = 48;
constexpr int NWP = 8;
constexpr int NUP = 5;
constexpr int WPIECE = 16384;
constexpr int NDP = 3;
constexpr int PIECE = 8192;
constexpr int NTAIL = NWP + NDP;
constexpr int N_TAIL0 = 2 * NHEAD;

#define CFG(name, value) constexpr int name = value
#define CFG_OVERRIDE
namespace cfg_default {
CFG(T_FIRST, 1850);
CFG(T_STEP, 1906);
CFG(T_SMAX, 1940);
CFG(CAP, 5);
CFG(MA, 16);
CFG(MB, 40);
CFG(ADAPT, 58);
CFG(T_LAT, 1360);
CFG(T_WO, 296);
CFG(T_GAP, 130);
CFG(T_UP, 234);
CFG(T_UP2, 140);
CFG(T_W2AT, 1325);
CFG(T_W2, 200);
CFG(T_HAT, 1240);
CFG(T_RESAT, 1750);
CFG(AGATE, 2);
CFG(KEEP_AT, 7);
CFG(KEEP, 150);
CFG(HCOPY, 2);
CFG(QDELAY, 1200);
CFG(QDELAY2, 900);
CFG(QSLEEP, 400);
CFG(PDELAY, 2500);
CFG(PDELAY_LAST, 250);
CFG(PDELAY_STEP, 650);
CFG(PREPART, 3);
CFG(RBDELAY, 5000);
CFG(NPROBE, 10);
CFG(VOTES, 3);
CFG(PROMO_KV, 2);
CFG(PROMO_WO, 2);
CFG(PROMO_W13, 2);
CFG(PROMO_W2, 2);
CFG(BOUNDED_MBAR, 0);
}
namespace cfg { using namespace cfg_default; CFG_OVERRIDE }

constexpr int SM_RING = 0;
constexpr int SM_W2 = NWP * WPIECE;
constexpr int SM_Q = SM_RING + NSLOT * TILE_BYTES;
constexpr int SM_RED = SM_Q + NHEAD * ROW_BYTES;
constexpr int SM_HN = SM_RED + 4096;
constexpr int SM_MISC = SM_HN + D_MODEL * 2;
constexpr int SM_BAR = SM_MISC + 128;
constexpr int SM_TOTAL = SM_BAR + 512;
static_assert(SM_TOTAL <= 232448, "shared memory");

struct __align__(128) Scratch {
    uint4 part[NHEAD * 4 * NCTA * 8];
    uint64_t q1[NHEAD * 4 * DH];
    uint4 q2[NHEAD * 32];
    uint32_t epoch;
    uint32_t pad;
    unsigned long long pace[2];
};
__device__ Scratch g_scratch;
constexpr int XA_ALIGN = 1 << 20;
constexpr uint32_t SENT = 0xffffffffu;
constexpr int L_GATHER = 0;
constexpr int HCOPY_BYTES = NG * D_MODEL * 2;
constexpr int L_O = 9 * 4096;
constexpr int L_ACT = 30 * 4096;
constexpr int L_PROBE = 32 * 4096;
static_assert(2 * (L_PROBE + NCTA * 1024) <= XA_ALIGN, "");
__device__ unsigned char g_xarea[2 * XA_ALIGN];
__device__ __forceinline__ uint32_t xa_off(uint32_t l, uint32_t side) {
    const uint32_t k = l >> 12;
    return (2 * k + ((side ^ k ^ (k >> 3) ^ (k >> 4) ^ (k >> 6)) & 1)) * 4096 + (l & 4095);
}

__device__ __forceinline__ uint32_t o_off(uint32_t r) { return L_O + (r >> 7) % NG * 2048 + (r >> 7) / NG * 256 + (r & 127) * 2; }

#define LST(i) do { } while (0)
#define LSC(i) do { } while (0)
#define LSCD(i, v) do { } while (0)
constexpr uint32_t SPIN_LIMIT = cfg::BOUNDED_MBAR ? 1u << 14 : 1u << 22;

__device__ __forceinline__ uint32_t now_q() { uint32_t t; asm volatile("mov.u32 %0, %globaltimer_lo;" : "=r"(t)); return t * 4; }
__device__ __forceinline__ void wait_until(uint32_t due) {
#pragma unroll 1
    for (int n = 0; n < 4096 && (int)(now_q() - due) < 0; n++) { }
}
__device__ __forceinline__ void sleep_until(uint32_t due) {
#pragma unroll 1
    for (int n = 0; n < 4096 && (int)(now_q() - due) < 0; n++) __nanosleep(200);
}
__device__ __forceinline__ uint32_t smem_u32(const void* p) { return (uint32_t)__cvta_generic_to_shared(p); }
__device__ __forceinline__ void mbar_init(uint32_t bar, uint32_t cnt) {
    asm volatile("mbarrier.init.shared::cta.b64 [%0], %1;" ::"r"(bar), "r"(cnt) : "memory");
}
__device__ __forceinline__ void mbar_expect_tx(uint32_t bar, uint32_t bytes) {
    asm volatile("mbarrier.arrive.expect_tx.shared::cta.b64 _, [%0], %1;" ::"r"(bar), "r"(bytes) : "memory");
}
__device__ __forceinline__ void mbar_arrive(uint32_t bar) {
    asm volatile("mbarrier.arrive.shared::cta.b64 _, [%0];" ::"r"(bar) : "memory");
}
__device__ __forceinline__ bool mbar_test(uint32_t bar, uint32_t parity) {
    uint32_t ok;
    asm volatile("{\n.reg .pred p;\nmbarrier.test_wait.parity.shared::cta.b64 p, [%1], %2;\nselp.u32 %0, 1, 0, p;\n}"
                 : "=r"(ok) : "r"(bar), "r"(parity) : "memory");
    return ok;
}
__device__ __forceinline__ bool mbar_try(uint32_t bar, uint32_t parity) {
    uint32_t ok;
    asm volatile("{\n.reg .pred p;\nmbarrier.try_wait.parity.shared::cta.b64 p, [%1], %2;\nselp.u32 %0, 1, 0, p;\n}"
                 : "=r"(ok) : "r"(bar), "r"(parity) : "memory");
    return ok;
}
__device__ __forceinline__ void mbar_wait(uint32_t bar, uint32_t parity) {
    if (cfg::BOUNDED_MBAR) {
        uint32_t n = 0;
        while (!mbar_try(bar, parity)) if (++n > SPIN_LIMIT) __trap();
    } else {
        asm volatile("{\n.reg .pred p;\nW_%=:\nmbarrier.try_wait.parity.shared::cta.b64 p, [%0], %1;\n@!p bra W_%=;\n}" ::"r"(bar), "r"(parity) : "memory");
    }
}
__device__ __forceinline__ void tma_tile(uint32_t dst, const CUtensorMap* tm, int c1, uint32_t bar, uint64_t pol) {
    asm volatile("cp.async.bulk.tensor.5d.shared::cluster.global.mbarrier::complete_tx::bytes.L2::cache_hint [%0], [%1, {%4, %3, %4, %4, %4}], [%2], %5;"
                 ::"r"(dst), "l"(reinterpret_cast<uint64_t>(tm)), "r"(bar), "r"(c1), "r"(0), "l"(pol) : "memory");
}
__device__ __forceinline__ void tma_5d(uint32_t dst, const CUtensorMap* tm, int c0, int c1, int c2, int c4, uint32_t bar) {
    asm volatile("cp.async.bulk.tensor.5d.shared::cluster.global.mbarrier::complete_tx::bytes [%0], [%1, {%3, %4, %5, %7, %6}], [%2];"
                 ::"r"(dst), "l"(reinterpret_cast<uint64_t>(tm)), "r"(bar), "r"(c0), "r"(c1), "r"(c2), "r"(c4), "r"(0) : "memory");
}
__device__ __forceinline__ uint32_t bits(uint32_t v) { return v; }
__device__ __forceinline__ uint32_t bits(float v) { return __float_as_uint(v); }
__device__ __forceinline__ uint32_t bits(const void* v) { return (uint32_t)(uintptr_t)v ^ (uint32_t)((uintptr_t)v >> 32); }
template <class... T> __device__ __forceinline__ uint32_t after(uint32_t zero, uint32_t bar, T... v) { return bar | ((bits(v) ^ ...) & zero); }
__device__ __forceinline__ void sts32(uint32_t a, float v) { asm volatile("st.shared.f32 [%0], %1;" ::"r"(a), "f"(v) : "memory"); }
__device__ __forceinline__ void sts64(uint32_t a, uint32_t x, uint32_t y) { asm volatile("st.shared.v2.u32 [%0], {%1, %2};" ::"r"(a), "r"(x), "r"(y) : "memory"); }
__device__ __forceinline__ void cons_sync() { asm volatile("bar.sync 1, 256;" ::: "memory"); }

__device__ __forceinline__ uint4 lds128(uint32_t a) {
    uint4 v;
    asm volatile("ld.shared.v4.u32 {%0,%1,%2,%3}, [%4];" : "=r"(v.x), "=r"(v.y), "=r"(v.z), "=r"(v.w) : "r"(a));
    return v;
}
__device__ __forceinline__ float4 lds128f(uint32_t a) {
    float4 v;
    asm volatile("ld.shared.v4.f32 {%0,%1,%2,%3}, [%4];" : "=f"(v.x), "=f"(v.y), "=f"(v.z), "=f"(v.w) : "r"(a) : "memory");
    return v;
}
__device__ __forceinline__ float2 lds64f(uint32_t a) {
    float2 v;
    asm volatile("ld.shared.v2.f32 {%0,%1}, [%2];" : "=f"(v.x), "=f"(v.y) : "r"(a) : "memory");
    return v;
}
__device__ __forceinline__ uint32_t lds32(uint32_t a) {
    uint32_t v;
    asm volatile("ld.shared.u32 %0, [%1];" : "=r"(v) : "r"(a));
    return v;
}
__device__ __forceinline__ void ldsm_x4(uint32_t* r, uint32_t a) {
    asm volatile("ldmatrix.sync.aligned.m8n8.x4.shared.b16 {%0,%1,%2,%3}, [%4];"
                 : "=r"(r[0]), "=r"(r[1]), "=r"(r[2]), "=r"(r[3]) : "r"(a));
}
__device__ __forceinline__ void ldsm_x4_t(uint32_t* r, uint32_t a) {
    asm volatile("ldmatrix.sync.aligned.m8n8.x4.trans.shared.b16 {%0,%1,%2,%3}, [%4];"
                 : "=r"(r[0]), "=r"(r[1]), "=r"(r[2]), "=r"(r[3]) : "r"(a));
}
__device__ __forceinline__ void mma_bf16(float* c, const uint32_t* a, uint32_t b0, uint32_t b1) {
    asm volatile("mma.sync.aligned.m16n8k16.row.col.f32.bf16.bf16.f32 {%0,%1,%2,%3}, {%4,%5,%6,%7}, {%8,%9}, {%0,%1,%2,%3};"
                 : "+f"(c[0]), "+f"(c[1]), "+f"(c[2]), "+f"(c[3]) : "r"(a[0]), "r"(a[1]), "r"(a[2]), "r"(a[3]), "r"(b0), "r"(b1));
}
__device__ __forceinline__ float bf_lo(uint32_t u) { return __uint_as_float(u << 16); }
__device__ __forceinline__ float bf_hi(uint32_t u) { return __uint_as_float(u & 0xffff0000u); }
__device__ __forceinline__ uint32_t pack_bf(float hi, float lo) { uint32_t r; asm("cvt.rn.bf16x2.f32 %0, %1, %2;" : "=r"(r) : "f"(hi), "f"(lo)); return r; }
__device__ __forceinline__ float bfr(float x) { return __uint_as_float(pack_bf(x, 0.f)); }

__device__ __forceinline__ uint64_t pk(float v, uint32_t tag) { return ((uint64_t)tag << 32) | (uint64_t)__float_as_uint(v); }
__device__ __forceinline__ void ll_st1(uint64_t* p, float a, uint32_t tag) {
    asm volatile("st.relaxed.gpu.global.b64 [%0], %1;" ::"l"(p), "l"(pk(a, tag)) : "memory");
}
__device__ __forceinline__ uint4 ll_ld2(const uint4* p) {
    uint4 v;
    asm volatile("{\n.reg .b64 a, b;\nld.relaxed.gpu.global.v2.b64 {a, b}, [%4];\nmov.b64 {%0, %1}, a;\nmov.b64 {%2, %3}, b;\n}"
                 : "=r"(v.x), "=r"(v.y), "=r"(v.z), "=r"(v.w) : "l"(p) : "memory");
    return v;
}
__device__ __forceinline__ uint32_t in_word(float v) {
    uint32_t r;
    asm("min.u32 %0, %1, 0xfffffffe;" : "=r"(r) : "r"(__float_as_uint(v)));
    return r;
}
__device__ __forceinline__ void in_st1(void* p, float v) {
    asm volatile("st.relaxed.gpu.global.u32 [%0], %1;" ::"l"(p), "r"(in_word(v)) : "memory");
}
__device__ __forceinline__ void in_st4(void* p, uint32_t a, uint32_t b, uint32_t c, uint32_t d) {
    asm volatile("st.relaxed.gpu.global.v4.u32 [%0], {%1, %2, %3, %4};" ::"l"(p), "r"(a), "r"(b), "r"(c), "r"(d) : "memory");
}
__device__ __forceinline__ uint32_t in_ld1(const void* p) {
    uint32_t v;
    asm volatile("ld.relaxed.gpu.global.u32 %0, [%1];" : "=r"(v) : "l"(p) : "memory");
    return v;
}
__device__ __forceinline__ uint4 in_ld4(const void* p) {
    uint4 v;
    asm volatile("ld.relaxed.gpu.global.v4.u32 {%0, %1, %2, %3}, [%4];" : "=r"(v.x), "=r"(v.y), "=r"(v.z), "=r"(v.w) : "l"(p) : "memory");
    return v;
}
__device__ __forceinline__ void in_ld2p(const void* p, uint2& v, bool on) {
    asm volatile("{\n.reg .pred q;\nsetp.ne.u32 q, %3, 0;\n@q ld.relaxed.gpu.global.v2.u32 {%0, %1}, [%2];\n}"
                 : "+r"(v.x), "+r"(v.y) : "l"(p), "r"((uint32_t)on) : "memory");
}
__device__ __forceinline__ bool in_ok(const uint2& v) { return max(v.x, v.y) != SENT; }
__device__ __forceinline__ void in_ld4p(const void* p, uint4& v, bool on) {
    asm volatile("{\n.reg .pred q;\nsetp.ne.u32 q, %5, 0;\n@q ld.relaxed.gpu.global.v4.u32 {%0, %1, %2, %3}, [%4];\n}"
                 : "+r"(v.x), "+r"(v.y), "+r"(v.z), "+r"(v.w) : "l"(p), "r"((uint32_t)on) : "memory");
}
__device__ __forceinline__ void pkt_st(uint4* p, uint32_t x, uint32_t y, uint32_t z, uint32_t w) {
    asm volatile("{\n.reg .b128 t;\n.reg .b64 a, b;\nmov.b64 a, {%1, %2};\nmov.b64 b, {%3, %4};\nmov.b128 t, {a, b};\nst.relaxed.gpu.global.b128 [%0], t;\n}"
                 ::"l"(p), "r"(x), "r"(y), "r"(z), "r"(w) : "memory");
}
__device__ __forceinline__ void pkt_ldp(const uint4* p, uint4& v, bool on) {
    asm volatile("{\n.reg .pred q;\n.reg .b128 t;\n.reg .b64 a, b;\nsetp.ne.u32 q, %5, 0;\nmov.b64 a, {%0, %1};\nmov.b64 b, {%2, %3};\nmov.b128 t, {a, b};\n"
                 "@q ld.relaxed.gpu.global.b128 t, [%4];\nmov.b128 {a, b}, t;\nmov.b64 {%0, %1}, a;\nmov.b64 {%2, %3}, b;\n}"
                 : "+r"(v.x), "+r"(v.y), "+r"(v.z), "+r"(v.w) : "l"(p), "r"((uint32_t)on) : "memory");
}

__device__ __forceinline__ float sqrt_fast(float x) { float r; asm("sqrt.approx.ftz.f32 %0, %1;" : "=f"(r) : "f"(x)); return r; }
__device__ __forceinline__ float rcp_fast(float x) { float r; asm("rcp.approx.ftz.f32 %0, %1;" : "=f"(r) : "f"(x)); return r; }
__device__ __forceinline__ float ex2(float x) { float r; asm("ex2.approx.ftz.f32 %0, %1;" : "=f"(r) : "f"(x)); return r; }
constexpr float L2E = 1.4426950408889634f;
__device__ __forceinline__ void ln_finish(float s1, float s2, float& mean_b, float& inv_den) {
    const float mean = s1 * (1.0f / D_MODEL);
    const float var = fmaxf(fmaf(-mean, mean, s2 * (1.0f / D_MODEL)), 0.f);
    mean_b = bfr(mean);
    inv_den = rcp_fast(bfr(sqrt_fast(bfr(bfr(var) + 1e-5f))));
}

struct KParams {
    const __nv_bfloat16* wq;
    uint32_t t_first;
    uint32_t t_step;
    const __nv_bfloat16* x;
    Scratch* sc;
    unsigned char* xa;
    __nv_bfloat16* out;
    uint32_t t_smax;
    uint32_t t_lat;
    uint32_t zero;
};
struct TMaps { CUtensorMap k, v, wo, w1, w3, w2; };

__global__ void __launch_bounds__(NTHREADS, 1)
fused_decode_kernel(const KParams p, const __grid_constant__ TMaps tm) {
    extern __shared__ __align__(1024) unsigned char smem[];
    const uint32_t sbase = smem_u32(smem);
    const int tid = threadIdx.x;
    const int b = blockIdx.x;
    const int head = b >> 2, sp = b & 3;
    {
        if (tid < 192) {
            const uint32_t rg = tid / 24, ch = tid - rg * 24;
            const char* src = reinterpret_cast<const char*>(p.wq) + (uint32_t)(sp * 160 * (NHEAD * DH * 2) + head * ROW_BYTES + rg * (NHEAD * DH * 2) + ch * 16);
            uint32_t dst = sbase + SM_RING + QSLOT * TILE_BYTES + ((tid ^ (tid >> 3 & 7)) << 4);
#pragma unroll 4
            for (int i = 0; i < 20; i++) {
                asm volatile("cp.async.cg.shared.global [%0], [%1], 16;" ::"r"(dst), "l"(src) : "memory");
                dst += 8 * ROW_BYTES;
                src += (size_t)8 * (NHEAD * DH * 2);
            }
        }
    }
    const int warp = __shfl_sync(0xffffffffu, tid >> 5, 0), lane = tid & 31;
    const int rr = !(b & 1) ? b >> 1 : (b & 15) < 12 ? (b >> 4) * 6 + (b >> 1 & 7) : NFFN + (b >> 4) * 2 + (b >> 1 & 1);
    const bool is_wo = !(b & 1) && rr < NWO, is_ffn = (b & 1) && rr < NFFN, is_out = !is_ffn;
    const int og = (rr >> 2) + (b & 1) * 4, oh = og >= 10, oq = (og - 10 * oh) * 4 + (rr & 3);
    const int kg = min(rr / 10, NG - 1), ng = rr % 10;
    const uint32_t bar_full = sbase + SM_BAR;
    const uint32_t bar_empty = sbase + SM_BAR + 128;
    const uint32_t bar_tail = sbase + SM_BAR + 256;
    const uint32_t bar_h = bar_tail + 8 * NTAIL;
    const uint32_t bar_set = bar_h + 8;
    const uint32_t bar_pace = bar_h + 16;
    const uint32_t bar_q = bar_h + 24;
    const uint32_t bar_part = bar_h + 32;
    volatile uint32_t* s_pace = reinterpret_cast<volatile uint32_t*>(smem + SM_MISC + 64);
    auto tail_time = [&](int t) { return s_pace[0] + (s_pace[1] * (((N_TAIL0 - cfg::ADAPT) * 478 + NWP * cfg::T_WO + t) * 256 / 478) >> 8); };

    if (warp == 8) {
        const uint32_t c_start = now_q();
        if (lane >= 1 && lane <= 6) asm volatile("prefetch.tensormap [%0];" ::"l"(reinterpret_cast<uint64_t>(&tm.k + (lane - 1))) : "memory");
        uint64_t pol_stream;
        asm volatile("createpolicy.fractional.L2::evict_first.b64 %0, 1.0;" : "=l"(pol_stream));
        if (lane == 0) {
#pragma unroll 1
            for (int i = 0; i < NSLOT; i++) { mbar_init(bar_full + 8 * i, 1); mbar_init(bar_empty + 8 * i, 1); }
#pragma unroll 1
            for (int i = 0; i < NTAIL + 5; i++) mbar_init(bar_tail + 8 * i, i == NTAIL ? 8 : i == NTAIL + 3 ? 4 : 1);
            asm volatile("fence.mbarrier_init.release.cluster;" ::: "memory");
        }
        __syncwarp();
        asm volatile("bar.arrive 2, 288;" ::: "memory");
        asm volatile("bar.arrive 3, 64;" ::: "memory");
        asm volatile("bar.arrive 4, 64;" ::: "memory");
        if (lane == 0) {
            uint32_t due = c_start + p.t_first, step = p.t_step;
#pragma unroll 1
            for (int n = 0; n < N_TAIL0; n++) {
                const int slot = n & (NSLOT - 1);
                const int use = (n >> 4) + (slot >= QSLOT);
                if (n >= cfg::CAP) mbar_wait(bar_full + 8 * ((n - cfg::CAP) & (NSLOT - 1)), ((n - cfg::CAP) >> 4) & 1);
                if (use >= 1) mbar_wait(bar_empty + 8 * slot, (use - 1) & 1);
                if (n == cfg::ADAPT) { mbar_wait(bar_pace, 0); due = s_pace[0]; step = s_pace[1]; }
                const uint32_t full = bar_full + 8 * slot;
                mbar_expect_tx(full, TILE_BYTES);
                wait_until(due);
                LST(128 + n);
                tma_tile(sbase + SM_RING + slot * TILE_BYTES, &tm.k + (n & 1), ((n >> 1) * SK + (SK - WIN) + b * 32) * 3, full, pol_stream);
                due += step;
            }
            int rel = 0;
            auto released = [&](int end) {
#pragma unroll 1
                for (; rel * TILE_BYTES < end; rel++) mbar_wait(bar_empty + 8 * rel, rel < QSLOT);
            };
            const uint32_t t_wo = step * (cfg::T_WO * 4096 / 478) >> 12;
            if (is_wo) {
#pragma unroll 1
                for (int j = 0; j < NWP; j++) {
                    released((j + 1) * WPIECE);
                    mbar_expect_tx(bar_tail + 8 * j, WPIECE);
                    wait_until(due);
                    LST(128 + N_TAIL0 + j);
                    tma_5d(sbase + j * WPIECE, &tm.wo, ng * 64, j * (NG * 128) + kg * 128, 0, 0, bar_tail + 8 * j);
                    due += t_wo;
                }
            } else {
                due += NWP * t_wo;
            }
            due += 4 * cfg::T_GAP;
            if (is_out) {
                due += step * (cfg::T_W2AT * 4096 / 478) >> 12;
                released(SM_W2 + NDP * PIECE);
#pragma unroll
                for (int j = 0; j < NDP; j++) mbar_expect_tx(bar_tail + 8 * (NWP + j), PIECE);
                sleep_until(due - 4 * 400);
#pragma unroll
                for (int j = 0; j < NDP; j++) {
                    wait_until(due);
                    tma_5d(sbase + SM_W2 + j * PIECE, &tm.w2, oq * 16, (oh * NDP + j) * 256, 0, 0, bar_tail + 8 * (NWP + j));
                    LST(128 + N_TAIL0 + NWP + j);
                    due += step * (cfg::T_W2 * 4096 / 478) >> 12;
                }
            } else if (is_ffn) {
                released(NUP * WPIECE);
#pragma unroll
                for (int j = 0; j <= NUP; j++) mbar_expect_tx(bar_tail + 8 * j, j < NUP - 1 ? WPIECE : WPIECE / 2);
                sleep_until(due - 4 * 400);
#pragma unroll
                for (int j = 0; j <= NUP; j++) {
                    const uint32_t full = bar_tail + 8 * j;
                    const int i = min(j, NUP - 1);
                    wait_until(due);
                    if (j < NUP) tma_5d(sbase + i * WPIECE, &tm.w1, rr * 32, 0, i * 4, 0, full);
                    if (j != NUP - 1) tma_5d(sbase + i * WPIECE + WPIECE / 2, &tm.w3, rr * 32, 0, i * 4, 0, full);
                    LST(128 + N_TAIL0 + j);
                    due += step * ((j < NUP - 1 ? cfg::T_UP : cfg::T_UP2) * 4096 / 478) >> 12;
                }
            }
        }
    } else if (warp == 10) {
        asm volatile("bar.sync 4, 64;" ::: "memory");
        if (lane == 0) {
            uint32_t epoch0;
            asm volatile("ld.relaxed.gpu.global.u32 %0, [%1];" : "=r"(epoch0) : "l"(&p.sc->epoch) : "memory");
            constexpr int MN = 8;
            const uint32_t t0 = now_q();
            uint32_t sa = 0, sb = 0;
#pragma unroll 1
            for (int n = 0; n < cfg::MB + MN; n++) {
#pragma unroll 1
                for (int k = 0; k < 256 && !mbar_try(bar_full + 8 * (n & (NSLOT - 1)), (n >> 4) & 1); k++) { }
                const uint32_t t = now_q() - t0;
                LST(n);
                if ((uint32_t)(n - cfg::MA) < MN) sa += t;
                if (n >= cfg::MB) sb += t;
            }
            const uint32_t mb = t0 + sb / MN;
            unsigned long long* pace = p.sc->pace + ((epoch0 + 1) & 1);
            mbar_wait(bar_set, 0);
            asm volatile("red.relaxed.gpu.global.add.u64 [%0], %1;" ::"l"(pace), "l"((unsigned long long)mb << 32 | min((sb - sa) / (4 * MN), 0xffffu) << 8 | 1) : "memory");
            if (b == 0) p.sc->pace[epoch0 & 1] = 0;
            unsigned long long v;
            uint32_t n = 0, cnt;
#pragma unroll 1
            do {
                __nanosleep(n ? 200 : 1000);
                asm volatile("ld.relaxed.gpu.global.u64 %0, [%1];" : "=l"(v) : "l"(pace) : "memory");
                cnt = (uint32_t)v & 0xff;
                if (++n > SPIN_LIMIT) __trap();
            } while (cnt < NCTA);
            const uint32_t step = min(max(((uint32_t)v >> 8) / (NCTA / 4 * (cfg::MB - cfg::MA)), p.t_step), p.t_smax);
            s_pace[0] = mb + (int)((uint32_t)(v >> 32) - NCTA * mb) / NCTA + step * (2 * (cfg::ADAPT - cfg::MB) - (MN - 1)) / 2 - p.t_lat;
            s_pace[1] = step;
            mbar_arrive(bar_pace);
            LST(89);
        }
    } else if (warp == 9) {
        const uint32_t c_start = now_q();
        uint32_t epoch0;
        asm volatile("ld.relaxed.gpu.global.u32 %0, [%1];" : "=r"(epoch0) : "l"(&p.sc->epoch) : "memory");
        sleep_until(c_start + p.t_first);
        unsigned char* slot[2];
        slot[0] = p.xa + xa_off(o_off(b * 48 + (lane % 6) * 8), lane / 6 & 1);
        slot[1] = p.xa + (is_wo ? xa_off(L_GATHER + (lane >> 4) * HCOPY_BYTES + (kg * D_MODEL + ng * 64 + (lane & 7) * 8) * 2, lane >> 3 & 1)
                                : xa_off(L_ACT + rr * 64 + (lane & 3) * 16, lane >> 2 & 1));
        const int n2 = is_wo ? 16 * cfg::HCOPY : is_ffn ? 8 : 0;
#pragma unroll
        for (int i = 0; i < 2; i++) if (lane < (i ? n2 : 12)) in_st4(slot[i], SENT, SENT, SENT, SENT);
#pragma unroll
        for (int i = 1; i <= cfg::PREPART; i++) pkt_st(p.sc->part + (((NHEAD - i) * 4 + (lane & 3)) * NCTA + b) * 8 + (lane >> 2), 0, 0, 0, epoch0 & 3);
        unsigned char* probe = p.xa + xa_off(L_PROBE + b * 1024 + (lane >> 1 & 7) * 128 + (lane & 1) * 16, lane >> 4);
        in_st4(probe, SENT, SENT, SENT, SENT);
        const bool clr = is_out && !oh && lane < 2;
        if (clr) in_st4(p.out + oq * 16 + lane * 8, 0, 0, 0, 0);
        sleep_until(now_q() + 4 * cfg::RBDELAY + b * 60);
        uint32_t acc = SENT;
#pragma unroll
        for (int i = 0; i < 2; i++) if (lane < (i ? n2 : 12)) acc &= in_ld1(slot[i]);
        if (clr) acc &= ~in_ld1(p.out + oq * 16 + lane * 8);
        if (__any_sync(0xffffffffu, acc != SENT)) __trap();
        int vote = 0;
        uint32_t lat[2] = {0, 0};
#pragma unroll 1
        for (int r = 0; r <= cfg::NPROBE && abs(vote) < cfg::VOTES; r++) {
            __nanosleep(300);
            uint32_t d[2];
#pragma unroll
            for (int i = 0; i < 2; i++) {
                const uint32_t c0 = (uint32_t)clock();
                if (__any_sync(0xffffffffu, in_ld1(p.xa + xa_off(L_PROBE + b * 1024 + (lane & 7) * 128, i)) != SENT)) __trap();
                d[i] = (uint32_t)clock() - c0;
                if (r) lat[i] += min(d[i], 1500u);
            }
            if (r) vote = __shfl_sync(0xffffffffu, vote + (d[1] < d[0]) - (d[0] < d[1]), 0);
        }
        const uint32_t sel = vote ? vote > 0 : lat[1] < lat[0];
        const uint32_t tag = epoch0 + 1;
        asm volatile("bar.sync 3, 64;" ::: "memory");
        if (lane == 0) { s_pace[2] = sel; mbar_arrive(bar_set); }
        {
            mbar_wait(bar_pace, 0);
            sleep_until(s_pace[0] + cfg::KEEP_AT * s_pace[1]);
            const uint32_t t_res = tail_time(cfg::T_RESAT);
            float c[4] = {0.f, 0.f, 0.f, 0.f};
            const uint32_t z[4] = {p.zero, p.zero, p.zero, p.zero};
            uint32_t n = 0;
#pragma unroll 1
            do {
                mma_bf16(c, z, p.zero, p.zero);
                __nanosleep(cfg::KEEP);
                n += 1 + __float_as_uint(c[0]);
            } while (!__all_sync(0xffffffffu, is_ffn ? mbar_test(bar_tail + 8, 0) : (int)(now_q() - t_res) >= 0) && n < SPIN_LIMIT);
            if (is_ffn) {
                unsigned char* adst = p.xa + xa_off(L_ACT + rr * 64 + (lane >> 3) * 16 + (lane & 3) * 4, lane >> 2 & 1);
                uint32_t src = sbase + SM_RED + lane * 8;
                mbar_wait(after(p.zero, bar_h, adst, src), 0);
                const float4 pa = lds128f(sbase + SM_MISC), pb = lds128f(sbase + SM_MISC + 16), pc = lds128f(sbase + SM_MISC + 32), pd = lds128f(sbase + SM_MISC + 48);
                float mean_b, inv_den;
                ln_finish(((pa.y + pa.w) + (pb.y + pb.w)) + ((pc.y + pc.w) + (pd.y + pd.w)),
                          ((pa.x + pa.z) + (pb.x + pb.z)) + ((pc.x + pc.z) + (pd.x + pd.z)), mean_b, inv_den);
                float2 r[8];
#define S_(c) (((r[0].c + r[1].c) + (r[2].c + r[3].c)) + ((r[4].c + r[5].c) + (r[6].c + r[7].c)))
                asm volatile("bar.sync %0, 288;" ::"r"(after(p.zero, 8, inv_den, mean_b)) : "memory");
#pragma unroll
                for (int i = 0; i < 8; i++) r[i] = lds64f(src + i * 256);
                const float gate = bfr(fmaf(-mean_b, S_(y), S_(x)) * inv_den);
                const float silu = bfr(__fdividef(gate, 1.0f + ex2(-gate * L2E)));
                asm volatile("bar.sync %0, 288;" ::"r"(after(p.zero, 5, silu)) : "memory");
#pragma unroll
                for (int i = 0; i < 8; i++) r[i] = lds64f(src + 2048 + i * 256);
                const float act = silu * bfr(fmaf(-mean_b, S_(y), S_(x)) * inv_den);
#undef S_
                const float oth = __shfl_xor_sync(0xffffffffu, act, 4);
                in_st1(adst, __uint_as_float((lane & 4) ? pack_bf(act, oth) : pack_bf(oth, act)));
                if (lane == 0) LST(110);
            }
            if (is_out) {
                const int col = oq * 16 + (lane & 15);
                float res = 0.f;
                if (!oh) {
                    uint32_t u[NG], xv;
                    asm volatile("ld.global.nc.u16 %0, [%1];" : "=r"(xv) : "l"(p.x + col));
                    n = 0;
#pragma unroll 1
                    do {
#pragma unroll
                        for (int i = 0; i < NG; i++) u[i] = in_ld1(p.xa + xa_off(L_GATHER + rr % cfg::HCOPY * HCOPY_BYTES + (i * D_MODEL + (col & ~1)) * 2, sel));
                        if (++n > SPIN_LIMIT) __trap();
                    } while (__any_sync(0xffffffffu, max(max(max(u[0], u[1]), max(u[2], u[3])), max(u[4], u[5])) == SENT));
                    if (b == 0 && lane == 0) p.sc->epoch = tag;
#define F_(i) ((lane & 1) ? bf_hi(u[i]) : bf_lo(u[i]))
                    res = bfr(bf_lo(xv) + bfr(((F_(0) + F_(1)) + (F_(2) + F_(3))) + (F_(4) + F_(5))));
#undef F_
                }
                mma_bf16(c, z, p.zero, p.zero);
                mbar_wait(after(p.zero, bar_tail + 8 * NWP, c[0]), 0);
                mma_bf16(c, z, p.zero, p.zero);
                res += c[0];
                __nv_bfloat16* dst = p.out + (col & ~1);
                uint32_t src = sbase + SM_HN + (lane & 15) * 48;
                asm volatile("bar.sync %0, 288;" ::"r"(after(p.zero, 5, src, dst, res)) : "memory");
                const float4 ra = lds128f(src), rb = lds128f(src + 16);
                const float e = ((ra.x + ra.y) + (ra.z + ra.w)) + (((rb.x + rb.y) + (rb.z + rb.w)) + res);
                if (lane < 16) asm volatile("red.relaxed.gpu.global.add.noftz.bf16x2 [%0], %1;" ::"l"(dst), "r"((lane & 1) ? pack_bf(e, 0.f) : pack_bf(0.f, e)) : "memory");
                if (lane == 0) LST(96);
            }
        }
    } else {
        const int t = lane & 3, g = lane >> 2;
        const int arow = (lane & 7) + ((lane >> 4) << 3), ahalf = (lane >> 3) & 1;
        const int hcol = warp * 80 + min(lane, 4 * NUP - 1) * 4;
        uint32_t epoch0;
        uint2 xres;
        const char* xb = reinterpret_cast<const char*>(p.x);
        asm volatile("ld.relaxed.gpu.global.u32 %0, [%1];" : "=r"(epoch0) : "l"(&p.sc->epoch) : "memory");
        asm volatile("ld.global.nc.v2.u32 {%0, %1}, [%2];" : "=r"(xres.x), "=r"(xres.y) : "l"(xb + hcol * 2));
        uint64_t* q1dst = p.sc->q1 + ((head * 4 + (warp & 3)) * 4 + sp) * 48 + min(t, 2) * 16 + g;
        uint4* q2dst = p.sc->q2 + (head * 8 + sp * 2 + lane / 12) * 4 + t;
        if (warp == 7) {
            uint2 xu[5];
#pragma unroll
            for (int i = 0; i < 5; i++) asm volatile("ld.global.nc.v2.u32 {%0, %1}, [%2];" : "=r"(xu[i].x), "=r"(xu[i].y) : "l"(xb + i * 256 + lane * 8));
            float s1 = 0.f, s2 = 0.f, mean_b, inv_den;
#pragma unroll
            for (int i = 0; i < 5; i++) {
                const float a0 = bf_lo(xu[i].x), a1 = bf_hi(xu[i].x), a2 = bf_lo(xu[i].y), a3 = bf_hi(xu[i].y);
                s1 += (a0 + a1) + (a2 + a3);
                s2 = fmaf(a0, a0, fmaf(a1, a1, fmaf(a2, a2, fmaf(a3, a3, s2))));
            }
#pragma unroll
            for (int o = 16; o > 0; o >>= 1) { s1 += __shfl_xor_sync(0xffffffffu, s1, o); s2 += __shfl_xor_sync(0xffffffffu, s2, o); }
            ln_finish(s1, s2, mean_b, inv_den);
#define N_(v) (bfr((v) - mean_b) * inv_den)
#pragma unroll
            for (int i = 0; i < 5; i++)
                sts64(sbase + SM_HN + i * 256 + lane * 8, pack_bf(N_(bf_hi(xu[i].x)), N_(bf_lo(xu[i].x))), pack_bf(N_(bf_hi(xu[i].y)), N_(bf_lo(xu[i].y))));
#undef N_
        } else {
            if (warp < 4 && t < 3) { ll_st1(q1dst, 0.f, 0); ll_st1(q1dst + 8, 0.f, 0); }
            if (warp == 4 && lane < 24 && lane % 12 < 4) pkt_st(q2dst, 0, 0, 0, 0);
        }
        asm volatile("cp.async.wait_all;" ::: "memory");
        if (lane == 0) LST(80 + warp);
        asm volatile("bar.sync 2, 288;" ::: "memory");
        const uint32_t tag = epoch0 + 1;
        auto block = [&](int i) { const int unit = arow * 3 + (i >> 2); return sbase + SM_RING + unit * 128 + ((((i & 3) * 2 + ahalf) ^ (unit & 7)) << 4); };

        if (warp < 4) {
            {
                float c[3][4];
                uint32_t wa[3];
#pragma unroll
                for (int k = 0; k < 3; k++) { c[k][0] = c[k][1] = c[k][2] = c[k][3] = 0.f; wa[k] = block(warp * 3 + k) + QSLOT * TILE_BYTES; }
                const uint32_t xa = sbase + SM_HN + sp * 320 + t * 4;
#pragma unroll 2
                for (int ks = 0; ks < 2 * NQT; ks++) {
                    const uint32_t b0 = lds32(xa + ks * 32), b1 = lds32(xa + ks * 32 + 16);
#pragma unroll
                    for (int k = 0; k < 3; k++) { uint32_t a[4]; ldsm_x4_t(a, wa[k] + ks * (TILE_BYTES / 2)); mma_bf16(c[k], a, b0, b1); }
                }
                if (t < 3) {
                    ll_st1(q1dst, t == 0 ? c[0][0] : t == 1 ? c[1][0] : c[2][0], tag);
                    ll_st1(q1dst + 8, t == 0 ? c[0][2] : t == 1 ? c[1][2] : c[2][2], tag);
                }
                asm volatile("bar.sync 6, 128;" ::: "memory");
                if (tid < NQT) mbar_arrive(bar_empty + 8 * (QSLOT + tid));
                if (tid == 0) LST(90);
            }
            const uint32_t ta[3] = {block(0), block(4), block(8)};
            mbar_wait(bar_q, 0);
            if (tid == 0) LST(92);
#pragma unroll 1
            for (int h = warp; h < NHEAD; h += 4) {
                const int slot = (2 * h) & (NSLOT - 1);
                const uint32_t par = (h >> 3) & 1;
                uint32_t qf[24];
#pragma unroll
                for (int i = 0; i < 6; i++) { const uint4 v = lds128(sbase + SM_Q + h * ROW_BYTES + t * 96 + i * 16); qf[4 * i] = v.x; qf[4 * i + 1] = v.y; qf[4 * i + 2] = v.z; qf[4 * i + 3] = v.w; }
                uint32_t ad[12];
#pragma unroll
                for (int i = 0; i < 12; i++) ad[i] = (ta[i >> 2] + slot * TILE_BYTES) ^ ((i & 3) << 5);
                float sc[4][4];
#pragma unroll
                for (int j = 0; j < 4; j++) sc[j][0] = sc[j][1] = sc[j][2] = sc[j][3] = 0.f;
                mbar_wait(bar_full + 8 * slot, par);
#pragma unroll
                for (int i = 0; i < 12; i++) {
                    const uint32_t a[4] = {qf[2 * i], qf[2 * i], qf[2 * i + 1], qf[2 * i + 1]};
                    uint32_t k0[4], k1[4];
                    ldsm_x4(k0, ad[i]); ldsm_x4(k1, ad[i] + TILE_BYTES / 2);
                    mma_bf16(sc[0], a, k0[0], k0[1]); mma_bf16(sc[1], a, k0[2], k0[3]);
                    mma_bf16(sc[2], a, k1[0], k1[1]); mma_bf16(sc[3], a, k1[2], k1[3]);
                }
                const float scale = 0.07216878364870322f;
                float m = -INFINITY;
#pragma unroll
                for (int j = 0; j < 4; j++) { sc[j][0] = bfr(bfr(sc[j][0]) * scale); sc[j][1] = bfr(bfr(sc[j][1]) * scale); m = fmaxf(m, fmaxf(sc[j][0], sc[j][1])); }
                if (lane == 0) mbar_arrive(after(p.zero, bar_empty + 8 * slot, m));
                m = fmaxf(m, __shfl_xor_sync(0xffffffffu, m, 1));
                m = fmaxf(m, __shfl_xor_sync(0xffffffffu, m, 2));
                float l = 0.f;
                uint32_t pf[4];
#pragma unroll
                for (int j = 0; j < 4; j++) {
                    const float p0 = ex2((sc[j][0] - m) * L2E), p1 = ex2((sc[j][1] - m) * L2E);
                    l += p0 + p1;
                    const uint32_t hi = pack_bf(p1, p0);
                    pf[j] = (g & 1) ? pack_bf(p1 - bf_hi(hi), p0 - bf_lo(hi)) : hi;
                }
                l += __shfl_xor_sync(0xffffffffu, l, 1);
                l += __shfl_xor_sync(0xffffffffu, l, 2);
                const uint32_t meta = (__float_as_uint(m) & 0xffff0000u) | ((__float_as_uint(l) - 0x3f800000u + 0x800u) >> 10 & 0xfffcu) | (tag & 3);
                uint32_t pq[4][4];
#pragma unroll
                for (int q = 0; q < 4; q++)
#pragma unroll
                    for (int j = 0; j < 4; j++) pq[q][j] = (g >> 1) == q ? pf[j] : 0;
                float o[6][4];
#pragma unroll
                for (int k = 0; k < 6; k++) o[k][0] = o[k][1] = o[k][2] = o[k][3] = 0.f;
                uint4* dst = p.sc->part + ((h * 4 + t) * NCTA + b) * 8 + g;
                mbar_wait(after(p.zero, bar_full + 8 * slot + 8, meta, dst, pq[0][0], pq[1][1], pq[2][2], pq[3][3]), par);
#pragma unroll
                for (int i = 0; i < 12; i++) {
                    uint32_t v0[4], v1[4];
                    ldsm_x4_t(v0, ad[i] + TILE_BYTES); ldsm_x4_t(v1, ad[i] + TILE_BYTES + TILE_BYTES / 2);
                    mma_bf16(o[i % 3], v0, pq[i / 3][0], pq[i / 3][1]);
                    mma_bf16(o[3 + i % 3], v1, pq[i / 3][2], pq[i / 3][3]);
                }
                uint32_t w[3];
#pragma unroll
                for (int k = 0; k < 3; k++) w[k] = pack_bf((o[k][2] + o[k][3]) + (o[k + 3][2] + o[k + 3][3]), (o[k][0] + o[k][1]) + (o[k + 3][0] + o[k + 3][1]));
                pkt_st(dst, w[0], w[1], w[2], meta);
                if (lane == 0) {
                    mbar_arrive(after(p.zero, bar_empty + 8 * slot + 8, w[0], w[1], w[2]));
                    if (h == head) mbar_arrive(bar_part);
                }
            }
            if (tid == 96) LST(91);
        } else {
            const int u = tid - 128;
            uint32_t n = 0;
            if (warp == 4) {
                const uint4* src = reinterpret_cast<const uint4*>(p.sc->q1 + (head * 4 + sp) * 4 * 48) + min(lane, 23);
                uint4 v[4];
                sleep_until(now_q() + 4 * cfg::QDELAY);
#pragma unroll 1
                do {
                    if (n) __nanosleep(cfg::QSLEEP);
#pragma unroll
                    for (int i = 0; i < 4; i++) v[i] = ll_ld2(src + i * 24);
                    if (++n > SPIN_LIMIT) __trap();
                } while (__any_sync(0xffffffffu, ((v[0].y ^ tag) | (v[0].w ^ tag) | (v[1].y ^ tag) | (v[1].w ^ tag) | (v[2].y ^ tag) | (v[2].w ^ tag) | (v[3].y ^ tag) | (v[3].w ^ tag)) != 0));
#define F_(c) ((__uint_as_float(v[0].c) + __uint_as_float(v[1].c)) + (__uint_as_float(v[2].c) + __uint_as_float(v[3].c)))
                const uint32_t w0 = pack_bf(F_(z), F_(x));
#undef F_
                const uint32_t w1 = __shfl_down_sync(0xffffffffu, w0, 4), w2 = __shfl_down_sync(0xffffffffu, w0, 8);
                if (lane < 24 && lane % 12 < 4) pkt_st(q2dst, w0, w1, w2, tag);
            }
            asm volatile("bar.sync 7, 128;" ::: "memory");
            uint4 v[8];
            {
#pragma unroll
                for (int i = 0; i < 8; i++) v[i] = make_uint4(0, 0, 0, ~tag);
                sleep_until(now_q() + 4 * cfg::QDELAY2);
                n = 0;
                bool ok;
#pragma unroll 1
                do {
                    if (n) __nanosleep(cfg::QSLEEP);
#pragma unroll
                    for (int i = 0; i < 8; i++) pkt_ldp(p.sc->q2 + u + i * 128, v[i], v[i].w != tag);
                    ok = true;
#pragma unroll
                    for (int i = 0; i < 8; i++) ok &= v[i].w == tag;
                    if (++n > SPIN_LIMIT) __trap();
                } while (!__all_sync(0xffffffffu, ok));
                const uint32_t qd = sbase + SM_Q + (u >> 5) * ROW_BYTES + t * 96 + g * 12;
#pragma unroll
                for (int i = 0; i < 8; i++) {
                    sts32(qd + i * 4 * ROW_BYTES, __uint_as_float(v[i].x)); sts32(qd + i * 4 * ROW_BYTES + 4, __uint_as_float(v[i].y)); sts32(qd + i * 4 * ROW_BYTES + 8, __uint_as_float(v[i].z));
                }
                __syncwarp();
                if (lane == 0) mbar_arrive(bar_q);
            }
            {
                const uint4* src = p.sc->part + b * NCTA * 8 + u;
                const uint32_t rdst = sbase + SM_RED + (warp - 4) * 256 + min(lane >> 3, 2) * 64 + (lane & 7) * 4;
                const uint32_t lo = o_off(b * 48 + (min(lane, 23) >> 3) * 16) + (lane & 3) * 8 + (lane & 4);
                unsigned char *od0 = p.xa + xa_off(lo, 0), *od1 = p.xa + xa_off(lo, 1);
#pragma unroll
                for (int i = 0; i < 8; i++) v[i].w = ~tag;
                mbar_wait(bar_set, 0);
                mbar_wait(after(p.zero, bar_part, src, rdst, od0, od1), 0);
                {
                    const uint32_t at = now_q() + 4 * min(cfg::PDELAY, cfg::PDELAY_LAST + (NHEAD - 1 - head) * cfg::PDELAY_STEP);
                    sleep_until(at - 4 * 300);
                    wait_until(at);
                }
                n = 0;
                uint32_t bad;
#pragma unroll 1
                do {
                    if (n && head != NHEAD - 1) __nanosleep(cfg::QSLEEP);
#pragma unroll
                    for (int i = 0; i < 8; i++) pkt_ldp(src + i * 128, v[i], ((v[i].w ^ tag) & 3) != 0);
                    bad = 0;
#pragma unroll
                    for (int i = 0; i < 8; i++) bad |= v[i].w ^ tag;
                    if (++n > SPIN_LIMIT) __trap();
                } while (__any_sync(0xffffffffu, (bad & 3) != 0));
                if (u == 0) LST(119);
                float m = -INFINITY;
#pragma unroll
                for (int i = 0; i < 8; i++) m = fmaxf(m, bf_hi(v[i].w));
                m = fmaxf(m, __shfl_xor_sync(0xffffffffu, m, 8));
                m = fmaxf(m, __shfl_xor_sync(0xffffffffu, m, 16));
                float a[7] = {0.f, 0.f, 0.f, 0.f, 0.f, 0.f, 0.f};
#pragma unroll
                for (int i = 0; i < 8; i++) {
                    const float f = ex2((bf_hi(v[i].w) - m) * L2E);
                    a[0] = fmaf(f, bf_lo(v[i].x), a[0]); a[1] = fmaf(f, bf_hi(v[i].x), a[1]);
                    a[2] = fmaf(f, bf_lo(v[i].y), a[2]); a[3] = fmaf(f, bf_hi(v[i].y), a[3]);
                    a[4] = fmaf(f, bf_lo(v[i].z), a[4]); a[5] = fmaf(f, bf_hi(v[i].z), a[5]);
                    a[6] = fmaf(f, __uint_as_float(((v[i].w & 0xfffcu) << 10) + 0x3f800000u), a[6]);
                }
#pragma unroll
                for (int o = 8; o < 32; o <<= 1)
#pragma unroll
                    for (int i = 0; i < 7; i++) a[i] += __shfl_xor_sync(0xffffffffu, a[i], o);
                if (lane < 24) { sts32(rdst, lane < 8 ? a[0] : lane < 16 ? a[2] : a[4]); sts32(rdst + 32, lane < 8 ? a[1] : lane < 16 ? a[3] : a[5]); }
                if (lane == 24) sts64(rdst + 64, __float_as_uint(a[6]), __float_as_uint(m));
                asm volatile("bar.sync 7, 128;" ::: "memory");
                if (warp == 4) {
                    float2 st[4], r[4];
#pragma unroll
                    for (int i = 0; i < 4; i++) { st[i] = lds64f(sbase + SM_RED + i * 256 + 192); r[i] = lds64f(sbase + SM_RED + i * 256 + lane * 8); }
                    const float mm = fmaxf(fmaxf(st[0].y, st[1].y), fmaxf(st[2].y, st[3].y));
                    float den = 0.f, x0 = 0.f, x1 = 0.f;
#pragma unroll
                    for (int i = 0; i < 4; i++) { const float f = ex2((st[i].y - mm) * L2E); den = fmaf(f, st[i].x, den); x0 = fmaf(f, r[i].x, x0); x1 = fmaf(f, r[i].y, x1); }
                    const float inv = rcp_fast(den);
                    const float ow = __uint_as_float(pack_bf(x1 * inv, x0 * inv));
                    if (lane < 24) { in_st1(od0, ow); in_st1(od1, ow); }
                    if (lane == 0) LST(120);
                }
            }
        }
        mbar_wait(bar_pace, 0);
        const uint32_t msel = s_pace[2];
        cons_sync();
        if (is_wo) {
            uint32_t wa = sbase + (warp * 16 + arow) * 128 + ((ahalf ^ (lane & 7)) << 4);
            uint32_t pw = sbase + SM_RED + (warp * 64 + t * 16 + (lane >> 2)) * 4, pr = sbase + SM_RED + lane * 8;
            unsigned char* gdst = p.xa + xa_off(L_GATHER + (warp >> 1) % cfg::HCOPY * HCOPY_BYTES + (kg * D_MODEL + ng * 64 + lane * 2) * 2, warp & 1);
            const unsigned char* osrc = p.xa + xa_off(L_O + kg * 2048, msel) + warp * 32 + t * 8;
            uint2 ov[NWP];
#pragma unroll
            for (int j = 0; j < NWP; j++) ov[j] = make_uint2(SENT, SENT);
            auto gather = [&](int j0, int j1) {
                uint32_t n = 0;
#pragma unroll 1
                while (true) {
                    uint32_t mx = 0;
#pragma unroll
                    for (int j = j0; j < j1; j++) mx = max(mx, max(ov[j].x, ov[j].y));
                    if (!__any_sync(0xffffffffu, mx == SENT)) break;
#pragma unroll
                    for (int j = j0; j < j1; j++) in_ld2p(osrc + j * 256, ov[j], !in_ok(ov[j]));
                    if (++n > SPIN_LIMIT) __trap();
                }
            };
            float cw[4][4];
#pragma unroll
            for (int i = 0; i < 4; i++) cw[i][0] = cw[i][1] = cw[i][2] = cw[i][3] = 0.f;
            mbar_wait(after(p.zero, bar_tail + 8, osrc, wa, pw, pr, gdst), 0);
#pragma unroll
            for (int j = 0; j < NWP; j++) in_ld2p(osrc + j * 256, ov[j], true);
            gather(0, NWP - 1);
#pragma unroll
            for (int j = 0; j < NWP; j++) {
                if (j == NWP - 1) { gather(NWP - 1, NWP); if (tid == 224) LST(93); }
                mbar_wait(bar_tail + 8 * j, 0);
                if (j == NWP - 3) in_ld2p(osrc + (NWP - 1) * 256, ov[NWP - 1], !in_ok(ov[NWP - 1]));
                uint32_t a[4][4];
#pragma unroll
                for (int i = 0; i < 4; i++) ldsm_x4_t(a[i], (wa ^ (i << 5)) + j * WPIECE);
#pragma unroll
                for (int i = 0; i < 4; i++) mma_bf16(cw[i], a[i], ov[j].x, ov[j].y);
            }
#define SEL_(e) ((t & 2) ? ((t & 1) ? cw[3][e] : cw[2][e]) : ((t & 1) ? cw[1][e] : cw[0][e]))
            sts32(pw, SEL_(0)); sts32(pw + 32, SEL_(2));
#undef SEL_
            cons_sync();
            if (warp < 2 * cfg::HCOPY) {
                float2 r[8];
#pragma unroll
                for (int i = 0; i < 8; i++) r[i] = lds64f(pr + i * 256);
#define S_(c) (((r[0].c + r[1].c) + (r[2].c + r[3].c)) + ((r[4].c + r[5].c) + (r[6].c + r[7].c)))
                in_st1(gdst, __uint_as_float(pack_bf(S_(y), S_(x))));
#undef S_
            }
            if (tid == 0) LST(94);
        } else if (is_ffn) {
            uint32_t w13a = sbase + (warp * 16 + arow) * 64 + ((ahalf ^ (lane >> 1 & 3)) << 4);
            uint32_t red_dst = sbase + SM_RED + tid * 8;
            uint32_t stat = sbase + SM_MISC + warp * 8;
            uint32_t aw[NUP][4][4];
            auto load_w13 = [&](int i) {
                mbar_wait(bar_tail + 8 * i, 0);
#pragma unroll
                for (int k = 0; k < 4; k++) ldsm_x4_t(aw[i][k], (w13a ^ (k << 5 & 32)) + i * WPIECE + (k >> 1) * (WPIECE / 2));
            };
            uint32_t hp0, hp1;
            {
                const unsigned char* gsrc[NG];
                uint2 u[NG];
#pragma unroll
                for (int i = 0; i < NG; i++) { u[i] = make_uint2(0, 0); gsrc[i] = p.xa + xa_off(L_GATHER + rr % cfg::HCOPY * HCOPY_BYTES + (i * D_MODEL + hcol) * 2, msel); }
                const uint32_t at = after(p.zero, tail_time(cfg::T_HAT), gsrc[0], gsrc[1], gsrc[2], gsrc[3], gsrc[4], gsrc[5], w13a, red_dst, stat);
                sleep_until(at - 4 * 300);
                wait_until(at);
                LSC(0);
#pragma unroll
                for (int i = 0; i < NG; i++) in_ld2p(gsrc[i], u[i], lane < 4 * NUP);
                load_w13(0);
                LSCD(1, u[0].x ^ u[1].x ^ u[2].x ^ u[3].x ^ u[4].x ^ u[5].x);
                uint32_t n = 0;
#pragma unroll 1
                while (__any_sync(0xffffffffu, max(max(max(u[0].x, u[0].y), max(u[1].x, u[1].y)), max(max(max(u[2].x, u[2].y), max(u[3].x, u[3].y)),
                                                                                                    max(max(u[4].x, u[4].y), max(u[5].x, u[5].y)))) == SENT)) {
#pragma unroll
                    for (int i = 0; i < NG; i++) in_ld2p(gsrc[i], u[i], !in_ok(u[i]));
                    if (++n > SPIN_LIMIT) __trap();
                }
                if (tid == 96) LST(100);
                LSC(2);
#define F_(f, c) (f(xres.c) + bfr(((f(u[0].c) + f(u[1].c)) + (f(u[2].c) + f(u[3].c))) + (f(u[4].c) + f(u[5].c))))
                hp0 = pack_bf(F_(bf_hi, x), F_(bf_lo, x));
                hp1 = pack_bf(F_(bf_hi, y), F_(bf_lo, y));
#undef F_
            }
            {
                uint32_t b0[NUP], b1[NUP];
                float cf[4][4], cs[2][4];
#pragma unroll
                for (int e = 0; e < 4; e++) cf[0][e] = cf[1][e] = cf[2][e] = cf[3][e] = cs[0][e] = cs[1][e] = 0.f;
#pragma unroll
                for (int i = 0; i < NUP; i++) {
                    const uint32_t h0 = __shfl_sync(0xffffffffu, hp0, i * 4 + t), h1 = __shfl_sync(0xffffffffu, hp1, i * 4 + t);
                    b0[i] = (lane & 4) ? 0x3f803f80u : h0;
                    b1[i] = (lane & 4) ? 0x3f803f80u : h1;
                    const uint32_t sa[4] = {h0, h0, h1, h1};
                    mma_bf16(cs[i & 1], sa, b0[i], b1[i]);
                }
                auto mma_w13 = [&](int i) {
#pragma unroll
                    for (int k = 0; k < 4; k++) mma_bf16(cf[k], aw[i][k], b0[i], b1[i]);
                };
                if (lane == 0) sts64(stat, __float_as_uint(cs[0][0] + cs[1][0]), __float_as_uint(cs[0][1] + cs[1][1]));
                __syncwarp();
                if (lane == 0) mbar_arrive(bar_h);
                mma_w13(0);
                LSC(3);
#pragma unroll
                for (int i = 1; i < NUP - 1; i++) { load_w13(i); mma_w13(i); }
                LSC(4);
#define SEL_(k, e) ((t & 2) ? ((t & 1) ? cf[k + 1][e + 2] : cf[k + 1][e]) : ((t & 1) ? cf[k][e + 2] : cf[k][e]))
#pragma unroll
                for (int m = 0; m < 2; m++) {
                    mbar_wait(bar_tail + 8 * (NUP - 1 + m), 0);
#pragma unroll
                    for (int k = 2 * m; k < 2 * m + 2; k++) ldsm_x4_t(aw[NUP - 1][k], (w13a ^ (k << 5 & 32)) + (NUP - 1) * WPIECE + m * (WPIECE / 2));
#pragma unroll
                    for (int k = 2 * m; k < 2 * m + 2; k++) mma_bf16(cf[k], aw[NUP - 1][k], b0[NUP - 1], b1[NUP - 1]);
                    sts64(red_dst + m * 2048, __float_as_uint(SEL_(2 * m, 0)), __float_as_uint(SEL_(2 * m, 1)));
                    if (m == 0) asm volatile("bar.arrive 8, 288;" ::: "memory");
                }
                LSC(6);
#undef SEL_
            }
            LSC(7);
            asm volatile("bar.arrive 5, 288;" ::: "memory");
        }
        if (is_out) {
            uint32_t w2a = sbase + SM_W2 + (warp * 32 + arow) * 32 + ((ahalf ^ (lane >> 2 & 1)) << 4);
            uint32_t ydst = sbase + SM_HN + ((t & 1) * 8 + (lane >> 2)) * 48 + warp * 4;
            const unsigned char* asrc = p.xa + xa_off(L_ACT, msel) + oh * (NDP * 512) + warp * 64 + t * 16;
            uint32_t a[NDP][2][4];
            auto load_w2 = [&](int i) {
                mbar_wait(i ? bar_tail + 8 * (NWP + i) : after(p.zero, bar_tail + 8 * NWP, w2a, ydst, asrc), 0);
                ldsm_x4_t(a[i][0], w2a + i * PIECE); ldsm_x4_t(a[i][1], w2a + i * PIECE + 512);
            };
#pragma unroll
            for (int i = 0; i < cfg::AGATE; i++) load_w2(i);
            uint4 u[NDP];
            LSC(0);
#pragma unroll
            for (int i = 0; i < NDP; i++) u[i] = in_ld4(asrc + i * 512);
            uint32_t n = 0;
#pragma unroll 1
            while (true) {
                uint32_t m[NDP];
#pragma unroll
                for (int i = 0; i < NDP; i++) m[i] = max(max(u[i].x, u[i].y), max(u[i].z, u[i].w));
                if (!__any_sync(0xffffffffu, max(max(m[0], m[1]), m[2]) == SENT)) break;
#pragma unroll
                for (int i = 0; i < NDP; i++) in_ld4p(asrc + i * 512, u[i], m[i] == SENT);
                if (++n > SPIN_LIMIT) __trap();
            }
            LSC(12);
            if (tid == 96) LST(118);
            float cy[2 * NDP][4];
#pragma unroll
            for (int i = 0; i < NDP; i++) {
#pragma unroll
                for (int e = 0; e < 4; e++) cy[2 * i][e] = cy[2 * i + 1][e] = 0.f;
                if (i >= cfg::AGATE) load_w2(i);
                mma_bf16(cy[2 * i], a[i][0], u[i].x, u[i].y);
                mma_bf16(cy[2 * i + 1], a[i][1], u[i].z, u[i].w);
            }
#define Y_(e) (((cy[0][e] + cy[1][e]) + (cy[2][e] + cy[3][e])) + (cy[4][e] + cy[5][e]))
            const float y = (t & 1) ? Y_(2) : Y_(0);
#undef Y_
            if (t < 2) sts32(ydst, y);
            LSC(13);
            asm volatile("bar.arrive 5, 288;" ::: "memory");
        }
    }
}

typedef CUresult (*EncodeTiledFn)(CUtensorMap*, CUtensorMapDataType, cuuint32_t, void*, const cuuint64_t*, const cuuint64_t*,
                                  const cuuint32_t*, const cuuint32_t*, CUtensorMapInterleave, CUtensorMapSwizzle,
                                  CUtensorMapL2promotion, CUtensorMapFloatOOBfill);

void make_map(EncodeTiledFn fn, CUtensorMap* tm, const void* w, const int (&d)[5], const int (&st)[4], const int (&bx)[5],
              CUtensorMapSwizzle sw, int promo) {
    cuuint64_t dims[5], strides[4];
    cuuint32_t box[5], estr[5];
    for (int i = 0; i < 5; i++) { dims[i] = (cuuint64_t)d[i]; box[i] = (cuuint32_t)bx[i]; estr[i] = 1; }
    for (int i = 0; i < 4; i++) strides[i] = (cuuint64_t)st[i];
    fn(tm, CU_TENSOR_MAP_DATA_TYPE_BFLOAT16, 5, const_cast<void*>(w), dims, strides, box, estr, CU_TENSOR_MAP_INTERLEAVE_NONE, sw,
       (CUtensorMapL2promotion)promo, CU_TENSOR_MAP_FLOAT_OOB_FILL_NONE);
}

}

extern "C" void kernel_launch(void* const* d_in, const int* in_sizes, int n_in, void* d_out, int out_size) {
    (void)in_sizes; (void)n_in; (void)out_size;
    static EncodeTiledFn encode = nullptr;
    static Scratch* scratch = nullptr;
    static unsigned char* xarea = nullptr;
    static double tscale = 1.0;
    if (!encode) {
        void* sp = nullptr;
        cudaGetSymbolAddress(&sp, g_scratch);
        scratch = reinterpret_cast<Scratch*>(sp);
        cudaGetSymbolAddress(&sp, g_xarea);
        xarea = reinterpret_cast<unsigned char*>((reinterpret_cast<uintptr_t>(sp) + XA_ALIGN - 1) / XA_ALIGN * XA_ALIGN);
        void* fn = nullptr;
        cudaDriverEntryPointQueryResult st;
        cudaGetDriverEntryPoint("cuTensorMapEncodeTiled", &fn, cudaEnableDefault, &st);
        encode = reinterpret_cast<EncodeTiledFn>(fn);
        int dev = 0, khz = 0, bits = 0;
        cudaGetDevice(&dev);
        cudaDeviceGetAttribute(&khz, cudaDevAttrMemoryClockRate, dev);
        cudaDeviceGetAttribute(&bits, cudaDevAttrGlobalMemoryBusWidth, dev);
        if (khz > 0 && bits > 0) tscale = (2619000.0 * 5120.0) / ((double)khz * bits);
        cudaFuncSetAttribute(fused_decode_kernel, cudaFuncAttributeMaxDynamicSharedMemorySize, SM_TOTAL);
    }
    KParams p;
    p.x = (const __nv_bfloat16*)d_in[0];
    p.wq = (const __nv_bfloat16*)d_in[3];
    p.out = (__nv_bfloat16*)d_out;
    p.sc = scratch;
    p.xa = xarea;
    p.zero = 0;
    p.t_first = (uint32_t)(4 * cfg::T_FIRST * tscale);
    p.t_step = (uint32_t)(cfg::T_STEP * tscale);
    p.t_smax = (uint32_t)(cfg::T_SMAX * tscale);
    p.t_lat = (uint32_t)(4 * (450 + (cfg::T_LAT - 450) * tscale));
    TMaps tm;
    constexpr int R1 = FF * 2, R2 = D_MODEL * 2;
    make_map(encode, &tm.k, d_in[1], {64, NHEAD * SK * 3, 1, 1, 1}, {128, 128, 128, 128}, {64, 96, 1, 1, 1}, CU_TENSOR_MAP_SWIZZLE_128B, cfg::PROMO_KV);
    make_map(encode, &tm.v, d_in[2], {64, NHEAD * SK * 3, 1, 1, 1}, {128, 128, 128, 128}, {64, 96, 1, 1, 1}, CU_TENSOR_MAP_SWIZZLE_128B, cfg::PROMO_KV);
    make_map(encode, &tm.wo, d_in[4], {D_MODEL, NHEAD * DH, 1, 1, 1}, {R2, R2, R2, R2}, {64, 128, 1, 1, 1}, CU_TENSOR_MAP_SWIZZLE_128B, cfg::PROMO_WO);
    make_map(encode, &tm.w1, d_in[6], {FF, 2, 20, 2, 8}, {R1, 4 * R1, 2 * R1, 80 * R1}, {32, 2, 4, 2, 8}, CU_TENSOR_MAP_SWIZZLE_64B, cfg::PROMO_W13);
    make_map(encode, &tm.w3, d_in[7], {FF, 2, 20, 2, 8}, {R1, 4 * R1, 2 * R1, 80 * R1}, {32, 2, 4, 2, 8}, CU_TENSOR_MAP_SWIZZLE_64B, cfg::PROMO_W13);
    make_map(encode, &tm.w2, d_in[8], {D_MODEL, FF, 1, 1, 1}, {R2, R2, R2, R2}, {16, 256, 1, 1, 1}, CU_TENSOR_MAP_SWIZZLE_32B, cfg::PROMO_W2);
    fused_decode_kernel<<<NCTA, NTHREADS, SM_TOTAL, cudaStreamPerThread>>>(p, tm);
}
```

```cpp
#include <cuda_runtime.h>
#include <cuda_bf16.h>
#include <cuda.h>
#include <stdint.h>
#include <math.h>

namespace {

constexpr int D_MODEL = 640;
constexpr int NHEAD = 32;
constexpr int DH = 192;
constexpr int SK = 32768;
constexpr int WIN = 4096;
constexpr int FF = 1536;

constexpr int NCTA = 128;
constexpr int NCONS = 256;
constexpr int NTHREADS = NCONS + 96;
constexpr int ROW_BYTES = DH * 2;
constexpr int TILE_BYTES = 32 * ROW_BYTES;
constexpr int NSLOT = 16;
constexpr int NQT = 5;
constexpr int QSLOT = NSLOT - NQT;
constexpr int NWO = 60;
constexpr int NG = 6;
constexpr int NFFN = 48;
constexpr int NWP = 8;
constexpr int NUP = 5;
constexpr int WPIECE = 16384;
constexpr int NDP = 3;
constexpr int PIECE = 8192;
constexpr int NTAIL = NWP + NDP;
constexpr int N_TAIL0 = 2 * NHEAD;

#define CFG(name, value) constexpr int name = value
#define CFG_OVERRIDE
namespace cfg_default {
CFG(T_FIRST, 1850);
CFG(T_STEP, 1906);
CFG(T_SMAX, 1940);
CFG(CAP, 5);
CFG(MN, 12);
CFG(MA, 4);
CFG(MB, 40);
CFG(ADAPT, 60);
CFG(T_LAT, 1320);
CFG(T_WO, 296);
CFG(T_GAP, 130);
CFG(T_UP, 234);
CFG(T_UP2, 140);
CFG(T_W2AT, 1325);
CFG(T_W2, 200);
CFG(T_HAT, 1240);
CFG(T_RESAT, 1750);
CFG(AGATE, 2);
CFG(KEEP_AT, 65);
CFG(KEEP, 150);
CFG(HCOPY, 2);
CFG(QDELAY, 1200);
CFG(QDELAY2, 900);
CFG(QSLEEP, 400);
CFG(PDELAY, 2500);
CFG(PDELAY_LAST, 250);
CFG(PDELAY_STEP, 650);
CFG(PREPART, 3);
CFG(RBDELAY, 5000);
CFG(NPROBE, 10);
CFG(VOTES, 3);
CFG(PROMO_KV, 2);
CFG(PROMO_WO, 2);
CFG(PROMO_W13, 2);
CFG(PROMO_W2, 2);
CFG(BOUNDED_MBAR, 0);
}
namespace cfg { using namespace cfg_default; CFG_OVERRIDE }

constexpr int SM_RING = 0;
constexpr int SM_W2 = NWP * WPIECE;
constexpr int SM_Q = SM_RING + NSLOT * TILE_BYTES;
constexpr int SM_RED = SM_Q + NHEAD * ROW_BYTES;
constexpr int SM_HN = SM_RED + 4096;
constexpr int SM_MISC = SM_HN + D_MODEL * 2;
constexpr int SM_BAR = SM_MISC + 128;
constexpr int SM_TOTAL = SM_BAR + 512;
static_assert(SM_TOTAL <= 232448, "shared memory");

struct __align__(128) Scratch {
    uint4 part[NHEAD * 4 * NCTA * 8];
    uint64_t q1[NHEAD * 4 * DH];
    uint4 q2[NHEAD * 32];
    uint32_t epoch;
    uint32_t pad;
    unsigned long long pace[2];
};
__device__ Scratch g_scratch;
constexpr int XA_ALIGN = 1 << 20;
constexpr uint32_t SENT = 0xffffffffu;
constexpr int L_GATHER = 0;
constexpr int HCOPY_BYTES = NG * D_MODEL * 2;
constexpr int L_O = 9 * 4096;
constexpr int L_ACT = 30 * 4096;
constexpr int L_PROBE = 32 * 4096;
static_assert(2 * (L_PROBE + NCTA * 1024) <= XA_ALIGN, "");
__device__ unsigned char g_xarea[2 * XA_ALIGN];
__device__ __forceinline__ uint32_t xa_off(uint32_t l, uint32_t side) {
    const uint32_t k = l >> 12;
    return (2 * k + ((side ^ k ^ (k >> 3) ^ (k >> 4) ^ (k >> 6)) & 1)) * 4096 + (l & 4095);
}

__device__ __forceinline__ uint32_t o_off(uint32_t r) { return L_O + (r >> 7) % NG * 2048 + (r >> 7) / NG * 256 + (r & 127) * 2; }

#define LST(i) do { } while (0)
#define LSC(i) do { } while (0)
#define LSCD(i, v) do { } while (0)
constexpr uint32_t SPIN_LIMIT = cfg::BOUNDED_MBAR ? 1u << 14 : 1u << 22;

__device__ __forceinline__ uint32_t now_q() { uint32_t t; asm volatile("mov.u32 %0, %globaltimer_lo;" : "=r"(t)); return t * 4; }
__device__ __forceinline__ void wait_until(uint32_t due) {
#pragma unroll 1
    for (int n = 0; n < 4096 && (int)(now_q() - due) < 0; n++) { }
}
__device__ __forceinline__ void sleep_until(uint32_t due) {
#pragma unroll 1
    for (int n = 0; n < 4096 && (int)(now_q() - due) < 0; n++) __nanosleep(200);
}
__device__ __forceinline__ uint32_t smem_u32(const void* p) { return (uint32_t)__cvta_generic_to_shared(p); }
__device__ __forceinline__ void mbar_init(uint32_t bar, uint32_t cnt) {
    asm volatile("mbarrier.init.shared::cta.b64 [%0], %1;" ::"r"(bar), "r"(cnt) : "memory");
}
__device__ __forceinline__ void mbar_expect_tx(uint32_t bar, uint32_t bytes) {
    asm volatile("mbarrier.arrive.expect_tx.shared::cta.b64 _, [%0], %1;" ::"r"(bar), "r"(bytes) : "memory");
}
__device__ __forceinline__ void mbar_arrive(uint32_t bar) {
    asm volatile("mbarrier.arrive.shared::cta.b64 _, [%0];" ::"r"(bar) : "memory");
}
__device__ __forceinline__ bool mbar_test(uint32_t bar, uint32_t parity) {
    uint32_t ok;
    asm volatile("{\n.reg .pred p;\nmbarrier.test_wait.parity.shared::cta.b64 p, [%1], %2;\nselp.u32 %0, 1, 0, p;\n}"
                 : "=r"(ok) : "r"(bar), "r"(parity) : "memory");
    return ok;
}
__device__ __forceinline__ bool mbar_try(uint32_t bar, uint32_t parity) {
    uint32_t ok;
    asm volatile("{\n.reg .pred p;\nmbarrier.try_wait.parity.shared::cta.b64 p, [%1], %2;\nselp.u32 %0, 1, 0, p;\n}"
                 : "=r"(ok) : "r"(bar), "r"(parity) : "memory");
    return ok;
}
__device__ __forceinline__ void mbar_wait(uint32_t bar, uint32_t parity) {
    if (cfg::BOUNDED_MBAR) {
        uint32_t n = 0;
        while (!mbar_try(bar, parity)) if (++n > SPIN_LIMIT) __trap();
    } else {
        asm volatile("{\n.reg .pred p;\nW_%=:\nmbarrier.try_wait.parity.shared::cta.b64 p, [%0], %1;\n@!p bra W_%=;\n}" ::"r"(bar), "r"(parity) : "memory");
    }
}
__device__ __forceinline__ void tma_tile(uint32_t dst, const CUtensorMap* tm, int c1, uint32_t bar, uint64_t pol) {
    asm volatile("cp.async.bulk.tensor.5d.shared::cluster.global.mbarrier::complete_tx::bytes.L2::cache_hint [%0], [%1, {%4, %3, %4, %4, %4}], [%2], %5;"
                 ::"r"(dst), "l"(reinterpret_cast<uint64_t>(tm)), "r"(bar), "r"(c1), "r"(0), "l"(pol) : "memory");
}
__device__ __forceinline__ void tma_5d(uint32_t dst, const CUtensorMap* tm, int c0, int c1, int c2, int c4, uint32_t bar) {
    asm volatile("cp.async.bulk.tensor.5d.shared::cluster.global.mbarrier::complete_tx::bytes [%0], [%1, {%3, %4, %5, %7, %6}], [%2];"
                 ::"r"(dst), "l"(reinterpret_cast<uint64_t>(tm)), "r"(bar), "r"(c0), "r"(c1), "r"(c2), "r"(c4), "r"(0) : "memory");
}
__device__ __forceinline__ uint32_t bits(uint32_t v) { return v; }
__device__ __forceinline__ uint32_t bits(float v) { return __float_as_uint(v); }
__device__ __forceinline__ uint32_t bits(const void* v) { return (uint32_t)(uintptr_t)v ^ (uint32_t)((uintptr_t)v >> 32); }
template <class... T> __device__ __forceinline__ uint32_t after(uint32_t zero, uint32_t bar, T... v) { return bar | ((bits(v) ^ ...) & zero); }
__device__ __forceinline__ void sts32(uint32_t a, float v) { asm volatile("st.shared.f32 [%0], %1;" ::"r"(a), "f"(v) : "memory"); }
__device__ __forceinline__ void sts64(uint32_t a, uint32_t x, uint32_t y) { asm volatile("st.shared.v2.u32 [%0], {%1, %2};" ::"r"(a), "r"(x), "r"(y) : "memory"); }
__device__ __forceinline__ void cons_sync() { asm volatile("bar.sync 1, 256;" ::: "memory"); }

__device__ __forceinline__ uint4 lds128(uint32_t a) {
    uint4 v;
    asm volatile("ld.shared.v4.u32 {%0,%1,%2,%3}, [%4];" : "=r"(v.x), "=r"(v.y), "=r"(v.z), "=r"(v.w) : "r"(a));
    return v;
}
__device__ __forceinline__ float4 lds128f(uint32_t a) {
    float4 v;
    asm volatile("ld.shared.v4.f32 {%0,%1,%2,%3}, [%4];" : "=f"(v.x), "=f"(v.y), "=f"(v.z), "=f"(v.w) : "r"(a) : "memory");
    return v;
}
__device__ __forceinline__ float2 lds64f(uint32_t a) {
    float2 v;
    asm volatile("ld.shared.v2.f32 {%0,%1}, [%2];" : "=f"(v.x), "=f"(v.y) : "r"(a) : "memory");
    return v;
}
__device__ __forceinline__ uint32_t lds32(uint32_t a) {
    uint32_t v;
    asm volatile("ld.shared.u32 %0, [%1];" : "=r"(v) : "r"(a));
    return v;
}
__device__ __forceinline__ void ldsm_x4(uint32_t* r, uint32_t a) {
    asm volatile("ldmatrix.sync.aligned.m8n8.x4.shared.b16 {%0,%1,%2,%3}, [%4];"
                 : "=r"(r[0]), "=r"(r[1]), "=r"(r[2]), "=r"(r[3]) : "r"(a));
}
__device__ __forceinline__ void ldsm_x4_t(uint32_t* r, uint32_t a) {
    asm volatile("ldmatrix.sync.aligned.m8n8.x4.trans.shared.b16 {%0,%1,%2,%3}, [%4];"
                 : "=r"(r[0]), "=r"(r[1]), "=r"(r[2]), "=r"(r[3]) : "r"(a));
}
__device__ __forceinline__ void mma_bf16(float* c, const uint32_t* a, uint32_t b0, uint32_t b1) {
    asm volatile("mma.sync.aligned.m16n8k16.row.col.f32.bf16.bf16.f32 {%0,%1,%2,%3}, {%4,%5,%6,%7}, {%8,%9}, {%0,%1,%2,%3};"
                 : "+f"(c[0]), "+f"(c[1]), "+f"(c[2]), "+f"(c[3]) : "r"(a[0]), "r"(a[1]), "r"(a[2]), "r"(a[3]), "r"(b0), "r"(b1));
}
__device__ __forceinline__ float bf_lo(uint32_t u) { return __uint_as_float(u << 16); }
__device__ __forceinline__ float bf_hi(uint32_t u) { return __uint_as_float(u & 0xffff0000u); }
__device__ __forceinline__ uint32_t pack_bf(float hi, float lo) { uint32_t r; asm("cvt.rn.bf16x2.f32 %0, %1, %2;" : "=r"(r) : "f"(hi), "f"(lo)); return r; }
__device__ __forceinline__ float bfr(float x) { return __uint_as_float(pack_bf(x, 0.f)); }

__device__ __forceinline__ uint64_t pk(float v, uint32_t tag) { return ((uint64_t)tag << 32) | (uint64_t)__float_as_uint(v); }
__device__ __forceinline__ void ll_st1(uint64_t* p, float a, uint32_t tag) {
    asm volatile("st.relaxed.gpu.global.b64 [%0], %1;" ::"l"(p), "l"(pk(a, tag)) : "memory");
}
__device__ __forceinline__ uint4 ll_ld2(const uint4* p) {
    uint4 v;
    asm volatile("{\n.reg .b64 a, b;\nld.relaxed.gpu.global.v2.b64 {a, b}, [%4];\nmov.b64 {%0, %1}, a;\nmov.b64 {%2, %3}, b;\n}"
                 : "=r"(v.x), "=r"(v.y), "=r"(v.z), "=r"(v.w) : "l"(p) : "memory");
    return v;
}
__device__ __forceinline__ uint32_t in_word(float v) {
    uint32_t r;
    asm("min.u32 %0, %1, 0xfffffffe;" : "=r"(r) : "r"(__float_as_uint(v)));
    return r;
}
__device__ __forceinline__ void in_st1(void* p, float v) {
    asm volatile("st.relaxed.gpu.global.u32 [%0], %1;" ::"l"(p), "r"(in_word(v)) : "memory");
}
__device__ __forceinline__ void in_st4(void* p, uint32_t a, uint32_t b, uint32_t c, uint32_t d) {
    asm volatile("st.relaxed.gpu.global.v4.u32 [%0], {%1, %2, %3, %4};" ::"l"(p), "r"(a), "r"(b), "r"(c), "r"(d) : "memory");
}
__device__ __forceinline__ uint32_t in_ld1(const void* p) {
    uint32_t v;
    asm volatile("ld.relaxed.gpu.global.u32 %0, [%1];" : "=r"(v) : "l"(p) : "memory");
    return v;
}
__device__ __forceinline__ uint4 in_ld4(const void* p) {
    uint4 v;
    asm volatile("ld.relaxed.gpu.global.v4.u32 {%0, %1, %2, %3}, [%4];" : "=r"(v.x), "=r"(v.y), "=r"(v.z), "=r"(v.w) : "l"(p) : "memory");
    return v;
}
__device__ __forceinline__ void in_ld2p(const void* p, uint2& v, bool on) {
    asm volatile("{\n.reg .pred q;\nsetp.ne.u32 q, %3, 0;\n@q ld.relaxed.gpu.global.v2.u32 {%0, %1}, [%2];\n}"
                 : "+r"(v.x), "+r"(v.y) : "l"(p), "r"((uint32_t)on) : "memory");
}
__device__ __forceinline__ bool in_ok(const uint2& v) { return max(v.x, v.y) != SENT; }
__device__ __forceinline__ void in_ld4p(const void* p, uint4& v, bool on) {
    asm volatile("{\n.reg .pred q;\nsetp.ne.u32 q, %5, 0;\n@q ld.relaxed.gpu.global.v4.u32 {%0, %1, %2, %3}, [%4];\n}"
                 : "+r"(v.x), "+r"(v.y), "+r"(v.z), "+r"(v.w) : "l"(p), "r"((uint32_t)on) : "memory");
}
__device__ __forceinline__ void pkt_st(uint4* p, uint32_t x, uint32_t y, uint32_t z, uint32_t w) {
    asm volatile("{\n.reg .b128 t;\n.reg .b64 a, b;\nmov.b64 a, {%1, %2};\nmov.b64 b, {%3, %4};\nmov.b128 t, {a, b};\nst.relaxed.gpu.global.b128 [%0], t;\n}"
                 ::"l"(p), "r"(x), "r"(y), "r"(z), "r"(w) : "memory");
}
__device__ __forceinline__ void pkt_ldp(const uint4* p, uint4& v, bool on) {
    asm volatile("{\n.reg .pred q;\n.reg .b128 t;\n.reg .b64 a, b;\nsetp.ne.u32 q, %5, 0;\nmov.b64 a, {%0, %1};\nmov.b64 b, {%2, %3};\nmov.b128 t, {a, b};\n"
                 "@q ld.relaxed.gpu.global.b128 t, [%4];\nmov.b128 {a, b}, t;\nmov.b64 {%0, %1}, a;\nmov.b64 {%2, %3}, b;\n}"
                 : "+r"(v.x), "+r"(v.y), "+r"(v.z), "+r"(v.w) : "l"(p), "r"((uint32_t)on) : "memory");
}

__device__ __forceinline__ float sqrt_fast(float x) { float r; asm("sqrt.approx.ftz.f32 %0, %1;" : "=f"(r) : "f"(x)); return r; }
__device__ __forceinline__ float rcp_fast(float x) { float r; asm("rcp.approx.ftz.f32 %0, %1;" : "=f"(r) : "f"(x)); return r; }
__device__ __forceinline__ float ex2(float x) { float r; asm("ex2.approx.ftz.f32 %0, %1;" : "=f"(r) : "f"(x)); return r; }
constexpr float L2E = 1.4426950408889634f;
__device__ __forceinline__ void ln_finish(float s1, float s2, float& mean_b, float& inv_den) {
    const float mean = s1 * (1.0f / D_MODEL);
    const float var = fmaxf(fmaf(-mean, mean, s2 * (1.0f / D_MODEL)), 0.f);
    mean_b = bfr(mean);
    inv_den = rcp_fast(bfr(sqrt_fast(bfr(bfr(var) + 1e-5f))));
}

struct KParams {
    const __nv_bfloat16* wq;
    uint32_t t_first;
    uint32_t t_step;
    const __nv_bfloat16* x;
    Scratch* sc;
    unsigned char* xa;
    __nv_bfloat16* out;
    uint32_t t_smax;
    uint32_t t_lat;
    uint32_t zero;
};
struct TMaps { CUtensorMap k, v, wo, w1, w3, w2; };

__global__ void __launch_bounds__(NTHREADS, 1)
fused_decode_kernel(const KParams p, const __grid_constant__ TMaps tm) {
    extern __shared__ __align__(1024) unsigned char smem[];
    const uint32_t sbase = smem_u32(smem);
    const int tid = threadIdx.x;
    const int b = blockIdx.x;
    const int head = b >> 2, sp = b & 3;
    {
        if (tid < 192) {
            const uint32_t rg = tid / 24, ch = tid - rg * 24;
            const char* src = reinterpret_cast<const char*>(p.wq) + (uint32_t)(sp * 160 * (NHEAD * DH * 2) + head * ROW_BYTES + rg * (NHEAD * DH * 2) + ch * 16);
            uint32_t dst = sbase + SM_RING + QSLOT * TILE_BYTES + ((tid ^ (tid >> 3 & 7)) << 4);
#pragma unroll 4
            for (int i = 0; i < 20; i++) {
                asm volatile("cp.async.cg.shared.global [%0], [%1], 16;" ::"r"(dst), "l"(src) : "memory");
                dst += 8 * ROW_BYTES;
                src += (size_t)8 * (NHEAD * DH * 2);
            }
        }
    }
    const int warp = __shfl_sync(0xffffffffu, tid >> 5, 0), lane = tid & 31;
    const int rr = !(b & 1) ? b >> 1 : (b & 15) < 12 ? (b >> 4) * 6 + (b >> 1 & 7) : NFFN + (b >> 4) * 2 + (b >> 1 & 1);
    const bool is_wo = !(b & 1) && rr < NWO, is_ffn = (b & 1) && rr < NFFN, is_out = !is_ffn;
    const int og = (rr >> 2) + (b & 1) * 4, oh = og >= 10, oq = (og - 10 * oh) * 4 + (rr & 3);
    const int kg = min(rr / 10, NG - 1), ng = rr % 10;
    const uint32_t bar_full = sbase + SM_BAR;
    const uint32_t bar_empty = sbase + SM_BAR + 128;
    const uint32_t bar_tail = sbase + SM_BAR + 256;
    const uint32_t bar_h = bar_tail + 8 * NTAIL;
    const uint32_t bar_set = bar_h + 8;
    const uint32_t bar_pace = bar_h + 16;
    const uint32_t bar_q = bar_h + 24;
    const uint32_t bar_part = bar_h + 32;
    volatile uint32_t* s_pace = reinterpret_cast<volatile uint32_t*>(smem + SM_MISC + 64);
    auto tail_time = [&](int t) { return s_pace[0] + (s_pace[1] * (((N_TAIL0 - cfg::ADAPT) * 478 + NWP * cfg::T_WO + t) * 256 / 478) >> 8); };

    if (warp == 8) {
        const uint32_t c_start = now_q();
        if (lane >= 1 && lane <= 6) asm volatile("prefetch.tensormap [%0];" ::"l"(reinterpret_cast<uint64_t>(&tm.k + (lane - 1))) : "memory");
        uint64_t pol_stream;
        asm volatile("createpolicy.fractional.L2::evict_first.b64 %0, 1.0;" : "=l"(pol_stream));
        if (lane == 0) {
#pragma unroll 1
            for (int i = 0; i < NSLOT; i++) { mbar_init(bar_full + 8 * i, 1); mbar_init(bar_empty + 8 * i, 1); }
#pragma unroll 1
            for (int i = 0; i < NTAIL + 5; i++) mbar_init(bar_tail + 8 * i, i == NTAIL ? 8 : i == NTAIL + 3 ? 4 : 1);
            asm volatile("fence.mbarrier_init.release.cluster;" ::: "memory");
        }
        __syncwarp();
        asm volatile("bar.arrive 2, 288;" ::: "memory");
        asm volatile("bar.arrive 3, 64;" ::: "memory");
        asm volatile("bar.arrive 4, 64;" ::: "memory");
        if (lane == 0) {
            uint32_t due = c_start + p.t_first, step = p.t_step;
#pragma unroll 1
            for (int n = 0; n < N_TAIL0; n++) {
                const int slot = n & (NSLOT - 1);
                const int use = (n >> 4) + (slot >= QSLOT);
                if (n >= cfg::CAP) mbar_wait(bar_full + 8 * ((n - cfg::CAP) & (NSLOT - 1)), ((n - cfg::CAP) >> 4) & 1);
                if (use >= 1) mbar_wait(bar_empty + 8 * slot, (use - 1) & 1);
                if (n == cfg::ADAPT) { mbar_wait(bar_pace, 0); due = s_pace[0]; step = s_pace[1]; }
                const uint32_t full = bar_full + 8 * slot;
                mbar_expect_tx(full, TILE_BYTES);
                wait_until(due);
                LST(128 + n);
                tma_tile(sbase + SM_RING + slot * TILE_BYTES, &tm.k + (n & 1), ((n >> 1) * SK + (SK - WIN) + b * 32) * 3, full, pol_stream);
                due += step;
            }
            int rel = 0;
            auto released = [&](int end) {
#pragma unroll 1
                for (; rel * TILE_BYTES < end; rel++) mbar_wait(bar_empty + 8 * rel, rel < QSLOT);
            };
            const uint32_t t_wo = step * (cfg::T_WO * 4096 / 478) >> 12;
            if (is_wo) {
#pragma unroll 1
                for (int j = 0; j < NWP; j++) {
                    released((j + 1) * WPIECE);
                    mbar_expect_tx(bar_tail + 8 * j, WPIECE);
                    wait_until(due);
                    LST(128 + N_TAIL0 + j);
                    tma_5d(sbase + j * WPIECE, &tm.wo, ng * 64, j * (NG * 128) + kg * 128, 0, 0, bar_tail + 8 * j);
                    due += t_wo;
                }
            } else {
                due += NWP * t_wo;
            }
            due += 4 * cfg::T_GAP;
            if (is_out) {
                due += step * (cfg::T_W2AT * 4096 / 478) >> 12;
                released(SM_W2 + NDP * PIECE);
#pragma unroll
                for (int j = 0; j < NDP; j++) mbar_expect_tx(bar_tail + 8 * (NWP + j), PIECE);
                sleep_until(due - 4 * 400);
#pragma unroll
                for (int j = 0; j < NDP; j++) {
                    wait_until(due);
                    tma_5d(sbase + SM_W2 + j * PIECE, &tm.w2, oq * 16, (oh * NDP + j) * 256, 0, 0, bar_tail + 8 * (NWP + j));
                    LST(128 + N_TAIL0 + NWP + j);
                    due += step * (cfg::T_W2 * 4096 / 478) >> 12;
                }
            } else if (is_ffn) {
                released(NUP * WPIECE);
#pragma unroll
                for (int j = 0; j <= NUP; j++) mbar_expect_tx(bar_tail + 8 * j, j < NUP - 1 ? WPIECE : WPIECE / 2);
                sleep_until(due - 4 * 400);
#pragma unroll
                for (int j = 0; j <= NUP; j++) {
                    const uint32_t full = bar_tail + 8 * j;
                    const int i = min(j, NUP - 1);
                    wait_until(due);
                    if (j < NUP) tma_5d(sbase + i * WPIECE, &tm.w1, rr * 32, 0, i * 4, 0, full);
                    if (j != NUP - 1) tma_5d(sbase + i * WPIECE + WPIECE / 2, &tm.w3, rr * 32, 0, i * 4, 0, full);
                    LST(128 + N_TAIL0 + j);
                    due += step * ((j < NUP - 1 ? cfg::T_UP : cfg::T_UP2) * 4096 / 478) >> 12;
                }
            }
        }
    } else if (warp == 10) {
        asm volatile("bar.sync 4, 64;" ::: "memory");
        if (lane == 0) {
            uint32_t epoch0;
            asm volatile("ld.relaxed.gpu.global.u32 %0, [%1];" : "=r"(epoch0) : "l"(&p.sc->epoch) : "memory");
            constexpr int MN = cfg::MN;
            const uint32_t t0 = now_q();
            uint32_t sa = 0, sb = 0;
#pragma unroll 1
            for (int n = 0; n < cfg::MB + MN; n++) {
#pragma unroll 1
                for (int k = 0; k < 256 && !mbar_try(bar_full + 8 * (n & (NSLOT - 1)), (n >> 4) & 1); k++) { }
                const uint32_t t = now_q() - t0;
                LST(n);
                if ((uint32_t)(n - cfg::MA) < MN) sa += t;
                if (n >= cfg::MB) sb += t;
            }
            const uint32_t mb = t0 + sb / MN;
            unsigned long long* pace = p.sc->pace + ((epoch0 + 1) & 1);
            mbar_wait(bar_set, 0);
            asm volatile("red.relaxed.gpu.global.add.u64 [%0], %1;" ::"l"(pace), "l"((unsigned long long)mb << 32 | min((sb - sa) / (4 * MN), 0xffffu) << 8 | 1) : "memory");
            if (b == 0) p.sc->pace[epoch0 & 1] = 0;
            unsigned long long v;
            uint32_t n = 0, cnt;
#pragma unroll 1
            do {
                __nanosleep(n ? 200 : 1000);
                asm volatile("ld.relaxed.gpu.global.u64 %0, [%1];" : "=l"(v) : "l"(pace) : "memory");
                cnt = (uint32_t)v & 0xff;
                if (++n > SPIN_LIMIT) __trap();
            } while (cnt < NCTA);
            const uint32_t step = min(max(((uint32_t)v >> 8) / (NCTA / 4 * (cfg::MB - cfg::MA)), p.t_step), p.t_smax);
            s_pace[0] = mb + (int)((uint32_t)(v >> 32) - NCTA * mb) / NCTA + step * (2 * (cfg::ADAPT - cfg::MB) - (MN - 1)) / 2 - p.t_lat;
            s_pace[1] = step;
            mbar_arrive(bar_pace);
            LST(89);
        }
    } else if (warp == 9) {
        const uint32_t c_start = now_q();
        uint32_t epoch0;
        asm volatile("ld.relaxed.gpu.global.u32 %0, [%1];" : "=r"(epoch0) : "l"(&p.sc->epoch) : "memory");
        sleep_until(c_start + p.t_first);
        unsigned char* slot[2];
        slot[0] = p.xa + xa_off(o_off(b * 48 + (lane % 6) * 8), lane / 6 & 1);
        slot[1] = p.xa + (is_wo ? xa_off(L_GATHER + (lane >> 4) * HCOPY_BYTES + (kg * D_MODEL + ng * 64 + (lane & 7) * 8) * 2, lane >> 3 & 1)
                                : xa_off(L_ACT + rr * 64 + (lane & 3) * 16, lane >> 2 & 1));
        const int n2 = is_wo ? 16 * cfg::HCOPY : is_ffn ? 8 : 0;
#pragma unroll
        for (int i = 0; i < 2; i++) if (lane < (i ? n2 : 12)) in_st4(slot[i], SENT, SENT, SENT, SENT);
#pragma unroll
        for (int i = 1; i <= cfg::PREPART; i++) pkt_st(p.sc->part + (((NHEAD - i) * 4 + (lane & 3)) * NCTA + b) * 8 + (lane >> 2), 0, 0, 0, epoch0 & 3);
        unsigned char* probe = p.xa + xa_off(L_PROBE + b * 1024 + (lane >> 1 & 7) * 128 + (lane & 1) * 16, lane >> 4);
        in_st4(probe, SENT, SENT, SENT, SENT);
        const bool clr = is_out && !oh && lane < 2;
        if (clr) in_st4(p.out + oq * 16 + lane * 8, 0, 0, 0, 0);
        sleep_until(now_q() + 4 * cfg::RBDELAY + b * 60);
        uint32_t acc = SENT;
#pragma unroll
        for (int i = 0; i < 2; i++) if (lane < (i ? n2 : 12)) acc &= in_ld1(slot[i]);
        if (clr) acc &= ~in_ld1(p.out + oq * 16 + lane * 8);
        if (__any_sync(0xffffffffu, acc != SENT)) __trap();
        int vote = 0;
        uint32_t lat[2] = {0, 0};
#pragma unroll 1
        for (int r = 0; r <= cfg::NPROBE && abs(vote) < cfg::VOTES; r++) {
            __nanosleep(300);
            uint32_t d[2];
#pragma unroll
            for (int i = 0; i < 2; i++) {
                const uint32_t c0 = (uint32_t)clock();
                if (__any_sync(0xffffffffu, in_ld1(p.xa + xa_off(L_PROBE + b * 1024 + (lane & 7) * 128, i)) != SENT)) __trap();
                d[i] = (uint32_t)clock() - c0;
                if (r) lat[i] += min(d[i], 1500u);
            }
            if (r) vote = __shfl_sync(0xffffffffu, vote + (d[1] < d[0]) - (d[0] < d[1]), 0);
        }
        const uint32_t sel = vote ? vote > 0 : lat[1] < lat[0];
        const uint32_t tag = epoch0 + 1;
        asm volatile("bar.sync 3, 64;" ::: "memory");
        if (lane == 0) { s_pace[2] = sel; mbar_arrive(bar_set); }
        {
            mbar_wait(bar_pace, 0);
            sleep_until(s_pace[0] + (cfg::KEEP_AT - cfg::ADAPT) * s_pace[1]);
            const uint32_t t_res = tail_time(cfg::T_RESAT);
            float c[4] = {0.f, 0.f, 0.f, 0.f};
            const uint32_t z[4] = {p.zero, p.zero, p.zero, p.zero};
            uint32_t n = 0;
#pragma unroll 1
            do {
                mma_bf16(c, z, p.zero, p.zero);
                __nanosleep(cfg::KEEP);
                n += 1 + __float_as_uint(c[0]);
            } while (!__all_sync(0xffffffffu, is_ffn ? mbar_test(bar_tail + 8, 0) : (int)(now_q() - t_res) >= 0) && n < SPIN_LIMIT);
            if (is_ffn) {
                unsigned char* adst = p.xa + xa_off(L_ACT + rr * 64 + (lane >> 3) * 16 + (lane & 3) * 4, lane >> 2 & 1);
                uint32_t src = sbase + SM_RED + lane * 8;
                mbar_wait(after(p.zero, bar_h, adst, src), 0);
                const float4 pa = lds128f(sbase + SM_MISC), pb = lds128f(sbase + SM_MISC + 16), pc = lds128f(sbase + SM_MISC + 32), pd = lds128f(sbase + SM_MISC + 48);
                float mean_b, inv_den;
                ln_finish(((pa.y + pa.w) + (pb.y + pb.w)) + ((pc.y + pc.w) + (pd.y + pd.w)),
                          ((pa.x + pa.z) + (pb.x + pb.z)) + ((pc.x + pc.z) + (pd.x + pd.z)), mean_b, inv_den);
                float2 r[8];
#define S_(c) (((r[0].c + r[1].c) + (r[2].c + r[3].c)) + ((r[4].c + r[5].c) + (r[6].c + r[7].c)))
                asm volatile("bar.sync %0, 288;" ::"r"(after(p.zero, 8, inv_den, mean_b)) : "memory");
#pragma unroll
                for (int i = 0; i < 8; i++) r[i] = lds64f(src + i * 256);
                const float gate = bfr(fmaf(-mean_b, S_(y), S_(x)) * inv_den);
                const float silu = bfr(__fdividef(gate, 1.0f + ex2(-gate * L2E)));
                asm volatile("bar.sync %0, 288;" ::"r"(after(p.zero, 5, silu)) : "memory");
#pragma unroll
                for (int i = 0; i < 8; i++) r[i] = lds64f(src + 2048 + i * 256);
                const float act = silu * bfr(fmaf(-mean_b, S_(y), S_(x)) * inv_den);
#undef S_
                const float oth = __shfl_xor_sync(0xffffffffu, act, 4);
                in_st1(adst, __uint_as_float((lane & 4) ? pack_bf(act, oth) : pack_bf(oth, act)));
                if (lane == 0) LST(110);
            }
            if (is_out) {
                const int col = oq * 16 + (lane & 15);
                float res = 0.f;
                if (!oh) {
                    uint32_t u[NG], xv;
                    asm volatile("ld.global.nc.u16 %0, [%1];" : "=r"(xv) : "l"(p.x + col));
                    n = 0;
#pragma unroll 1
                    do {
#pragma unroll
                        for (int i = 0; i < NG; i++) u[i] = in_ld1(p.xa + xa_off(L_GATHER + rr % cfg::HCOPY * HCOPY_BYTES + (i * D_MODEL + (col & ~1)) * 2, sel));
                        if (++n > SPIN_LIMIT) __trap();
                    } while (__any_sync(0xffffffffu, max(max(max(u[0], u[1]), max(u[2], u[3])), max(u[4], u[5])) == SENT));
                    if (b == 0 && lane == 0) p.sc->epoch = tag;
#define F_(i) ((lane & 1) ? bf_hi(u[i]) : bf_lo(u[i]))
                    res = bfr(bf_lo(xv) + bfr(((F_(0) + F_(1)) + (F_(2) + F_(3))) + (F_(4) + F_(5))));
#undef F_
                }
                mma_bf16(c, z, p.zero, p.zero);
                mbar_wait(after(p.zero, bar_tail + 8 * NWP, c[0]), 0);
                mma_bf16(c, z, p.zero, p.zero);
                res += c[0];
                __nv_bfloat16* dst = p.out + (col & ~1);
                uint32_t src = sbase + SM_HN + (lane & 15) * 48;
                asm volatile("bar.sync %0, 288;" ::"r"(after(p.zero, 5, src, dst, res)) : "memory");
                const float4 ra = lds128f(src), rb = lds128f(src + 16);
                const float e = ((ra.x + ra.y) + (ra.z + ra.w)) + (((rb.x + rb.y) + (rb.z + rb.w)) + res);
                if (lane < 16) asm volatile("red.relaxed.gpu.global.add.noftz.bf16x2 [%0], %1;" ::"l"(dst), "r"((lane & 1) ? pack_bf(e, 0.f) : pack_bf(0.f, e)) : "memory");
                if (lane == 0) LST(96);
            }
        }
    } else {
        const int t = lane & 3, g = lane >> 2;
        const int arow = (lane & 7) + ((lane >> 4) << 3), ahalf = (lane >> 3) & 1;
        const int hcol = warp * 80 + min(lane, 4 * NUP - 1) * 4;
        uint32_t epoch0;
        uint2 xres;
        const char* xb = reinterpret_cast<const char*>(p.x);
        asm volatile("ld.relaxed.gpu.global.u32 %0, [%1];" : "=r"(epoch0) : "l"(&p.sc->epoch) : "memory");
        asm volatile("ld.global.nc.v2.u32 {%0, %1}, [%2];" : "=r"(xres.x), "=r"(xres.y) : "l"(xb + hcol * 2));
        uint64_t* q1dst = p.sc->q1 + ((head * 4 + (warp & 3)) * 4 + sp) * 48 + min(t, 2) * 16 + g;
        uint4* q2dst = p.sc->q2 + (head * 8 + sp * 2 + lane / 12) * 4 + t;
        if (warp == 7) {
            uint2 xu[5];
#pragma unroll
            for (int i = 0; i < 5; i++) asm volatile("ld.global.nc.v2.u32 {%0, %1}, [%2];" : "=r"(xu[i].x), "=r"(xu[i].y) : "l"(xb + i * 256 + lane * 8));
            float s1 = 0.f, s2 = 0.f, mean_b, inv_den;
#pragma unroll
            for (int i = 0; i < 5; i++) {
                const float a0 = bf_lo(xu[i].x), a1 = bf_hi(xu[i].x), a2 = bf_lo(xu[i].y), a3 = bf_hi(xu[i].y);
                s1 += (a0 + a1) + (a2 + a3);
                s2 = fmaf(a0, a0, fmaf(a1, a1, fmaf(a2, a2, fmaf(a3, a3, s2))));
            }
#pragma unroll
            for (int o = 16; o > 0; o >>= 1) { s1 += __shfl_xor_sync(0xffffffffu, s1, o); s2 += __shfl_xor_sync(0xffffffffu, s2, o); }
            ln_finish(s1, s2, mean_b, inv_den);
#define N_(v) (bfr((v) - mean_b) * inv_den)
#pragma unroll
            for (int i = 0; i < 5; i++)
                sts64(sbase + SM_HN + i * 256 + lane * 8, pack_bf(N_(bf_hi(xu[i].x)), N_(bf_lo(xu[i].x))), pack_bf(N_(bf_hi(xu[i].y)), N_(bf_lo(xu[i].y))));
#undef N_
        } else {
            if (warp < 4 && t < 3) { ll_st1(q1dst, 0.f, 0); ll_st1(q1dst + 8, 0.f, 0); }
            if (warp == 4 && lane < 24 && lane % 12 < 4) pkt_st(q2dst, 0, 0, 0, 0);
        }
        asm volatile("cp.async.wait_all;" ::: "memory");
        if (lane == 0) LST(80 + warp);
        asm volatile("bar.sync 2, 288;" ::: "memory");
        const uint32_t tag = epoch0 + 1;
        auto block = [&](int i) { const int unit = arow * 3 + (i >> 2); return sbase + SM_RING + unit * 128 + ((((i & 3) * 2 + ahalf) ^ (unit & 7)) << 4); };

        if (warp < 4) {
            {
                float c[3][4];
                uint32_t wa[3];
#pragma unroll
                for (int k = 0; k < 3; k++) { c[k][0] = c[k][1] = c[k][2] = c[k][3] = 0.f; wa[k] = block(warp * 3 + k) + QSLOT * TILE_BYTES; }
                const uint32_t xa = sbase + SM_HN + sp * 320 + t * 4;
#pragma unroll 2
                for (int ks = 0; ks < 2 * NQT; ks++) {
                    const uint32_t b0 = lds32(xa + ks * 32), b1 = lds32(xa + ks * 32 + 16);
#pragma unroll
                    for (int k = 0; k < 3; k++) { uint32_t a[4]; ldsm_x4_t(a, wa[k] + ks * (TILE_BYTES / 2)); mma_bf16(c[k], a, b0, b1); }
                }
                if (t < 3) {
                    ll_st1(q1dst, t == 0 ? c[0][0] : t == 1 ? c[1][0] : c[2][0], tag);
                    ll_st1(q1dst + 8, t == 0 ? c[0][2] : t == 1 ? c[1][2] : c[2][2], tag);
                }
                asm volatile("bar.sync 6, 128;" ::: "memory");
                if (tid < NQT) mbar_arrive(bar_empty + 8 * (QSLOT + tid));
                if (tid == 0) LST(90);
            }
            const uint32_t ta[3] = {block(0), block(4), block(8)};
            mbar_wait(bar_q, 0);
            if (tid == 0) LST(92);
#pragma unroll 1
            for (int h = warp; h < NHEAD; h += 4) {
                const int slot = (2 * h) & (NSLOT - 1);
                const uint32_t par = (h >> 3) & 1;
                uint32_t qf[24];
#pragma unroll
                for (int i = 0; i < 6; i++) { const uint4 v = lds128(sbase + SM_Q + h * ROW_BYTES + t * 96 + i * 16); qf[4 * i] = v.x; qf[4 * i + 1] = v.y; qf[4 * i + 2] = v.z; qf[4 * i + 3] = v.w; }
                uint32_t ad[12];
#pragma unroll
                for (int i = 0; i < 12; i++) ad[i] = (ta[i >> 2] + slot * TILE_BYTES) ^ ((i & 3) << 5);
                float sc[4][4];
#pragma unroll
                for (int j = 0; j < 4; j++) sc[j][0] = sc[j][1] = sc[j][2] = sc[j][3] = 0.f;
                mbar_wait(bar_full + 8 * slot, par);
#pragma unroll
                for (int i = 0; i < 12; i++) {
                    const uint32_t a[4] = {qf[2 * i], qf[2 * i], qf[2 * i + 1], qf[2 * i + 1]};
                    uint32_t k0[4], k1[4];
                    ldsm_x4(k0, ad[i]); ldsm_x4(k1, ad[i] + TILE_BYTES / 2);
                    mma_bf16(sc[0], a, k0[0], k0[1]); mma_bf16(sc[1], a, k0[2], k0[3]);
                    mma_bf16(sc[2], a, k1[0], k1[1]); mma_bf16(sc[3], a, k1[2], k1[3]);
                }
                const float scale = 0.07216878364870322f;
                float m = -INFINITY;
#pragma unroll
                for (int j = 0; j < 4; j++) { sc[j][0] = bfr(bfr(sc[j][0]) * scale); sc[j][1] = bfr(bfr(sc[j][1]) * scale); m = fmaxf(m, fmaxf(sc[j][0], sc[j][1])); }
                if (lane == 0) mbar_arrive(after(p.zero, bar_empty + 8 * slot, m));
                m = fmaxf(m, __shfl_xor_sync(0xffffffffu, m, 1));
                m = fmaxf(m, __shfl_xor_sync(0xffffffffu, m, 2));
                float l = 0.f;
                uint32_t pf[4];
#pragma unroll
                for (int j = 0; j < 4; j++) {
                    const float p0 = ex2((sc[j][0] - m) * L2E), p1 = ex2((sc[j][1] - m) * L2E);
                    l += p0 + p1;
                    const uint32_t hi = pack_bf(p1, p0);
                    pf[j] = (g & 1) ? pack_bf(p1 - bf_hi(hi), p0 - bf_lo(hi)) : hi;
                }
                l += __shfl_xor_sync(0xffffffffu, l, 1);
                l += __shfl_xor_sync(0xffffffffu, l, 2);
                const uint32_t meta = (__float_as_uint(m) & 0xffff0000u) | ((__float_as_uint(l) - 0x3f800000u + 0x800u) >> 10 & 0xfffcu) | (tag & 3);
                uint32_t pq[4][4];
#pragma unroll
                for (int q = 0; q < 4; q++)
#pragma unroll
                    for (int j = 0; j < 4; j++) pq[q][j] = (g >> 1) == q ? pf[j] : 0;
                float o[6][4];
#pragma unroll
                for (int k = 0; k < 6; k++) o[k][0] = o[k][1] = o[k][2] = o[k][3] = 0.f;
                uint4* dst = p.sc->part + ((h * 4 + t) * NCTA + b) * 8 + g;
                mbar_wait(after(p.zero, bar_full + 8 * slot + 8, meta, dst, pq[0][0], pq[1][1], pq[2][2], pq[3][3]), par);
#pragma unroll
                for (int i = 0; i < 12; i++) {
                    uint32_t v0[4], v1[4];
                    ldsm_x4_t(v0, ad[i] + TILE_BYTES); ldsm_x4_t(v1, ad[i] + TILE_BYTES + TILE_BYTES / 2);
                    mma_bf16(o[i % 3], v0, pq[i / 3][0], pq[i / 3][1]);
                    mma_bf16(o[3 + i % 3], v1, pq[i / 3][2], pq[i / 3][3]);
                }
                uint32_t w[3];
#pragma unroll
                for (int k = 0; k < 3; k++) w[k] = pack_bf((o[k][2] + o[k][3]) + (o[k + 3][2] + o[k + 3][3]), (o[k][0] + o[k][1]) + (o[k + 3][0] + o[k + 3][1]));
                pkt_st(dst, w[0], w[1], w[2], meta);
                if (lane == 0) {
                    mbar_arrive(after(p.zero, bar_empty + 8 * slot + 8, w[0], w[1], w[2]));
                    if (h == head) mbar_arrive(bar_part);
                }
            }
            if (tid == 96) LST(91);
        } else {
            const int u = tid - 128;
            uint32_t n = 0;
            if (warp == 4) {
                const uint4* src = reinterpret_cast<const uint4*>(p.sc->q1 + (head * 4 + sp) * 4 * 48) + min(lane, 23);
                uint4 v[4];
                sleep_until(now_q() + 4 * cfg::QDELAY);
#pragma unroll 1
                do {
                    if (n) __nanosleep(cfg::QSLEEP);
#pragma unroll
                    for (int i = 0; i < 4; i++) v[i] = ll_ld2(src + i * 24);
                    if (++n > SPIN_LIMIT) __trap();
                } while (__any_sync(0xffffffffu, ((v[0].y ^ tag) | (v[0].w ^ tag) | (v[1].y ^ tag) | (v[1].w ^ tag) | (v[2].y ^ tag) | (v[2].w ^ tag) | (v[3].y ^ tag) | (v[3].w ^ tag)) != 0));
#define F_(c) ((__uint_as_float(v[0].c) + __uint_as_float(v[1].c)) + (__uint_as_float(v[2].c) + __uint_as_float(v[3].c)))
                const uint32_t w0 = pack_bf(F_(z), F_(x));
#undef F_
                const uint32_t w1 = __shfl_down_sync(0xffffffffu, w0, 4), w2 = __shfl_down_sync(0xffffffffu, w0, 8);
                if (lane < 24 && lane % 12 < 4) pkt_st(q2dst, w0, w1, w2, tag);
            }
            asm volatile("bar.sync 7, 128;" ::: "memory");
            uint4 v[8];
            {
#pragma unroll
                for (int i = 0; i < 8; i++) v[i] = make_uint4(0, 0, 0, ~tag);
                sleep_until(now_q() + 4 * cfg::QDELAY2);
                n = 0;
                bool ok;
#pragma unroll 1
                do {
                    if (n) __nanosleep(cfg::QSLEEP);
#pragma unroll
                    for (int i = 0; i < 8; i++) pkt_ldp(p.sc->q2 + u + i * 128, v[i], v[i].w != tag);
                    ok = true;
#pragma unroll
                    for (int i = 0; i < 8; i++) ok &= v[i].w == tag;
                    if (++n > SPIN_LIMIT) __trap();
                } while (!__all_sync(0xffffffffu, ok));
                const uint32_t qd = sbase + SM_Q + (u >> 5) * ROW_BYTES + t * 96 + g * 12;
#pragma unroll
                for (int i = 0; i < 8; i++) {
                    sts32(qd + i * 4 * ROW_BYTES, __uint_as_float(v[i].x)); sts32(qd + i * 4 * ROW_BYTES + 4, __uint_as_float(v[i].y)); sts32(qd + i * 4 * ROW_BYTES + 8, __uint_as_float(v[i].z));
                }
                __syncwarp();
                if (lane == 0) mbar_arrive(bar_q);
            }
            {
                const uint4* src = p.sc->part + b * NCTA * 8 + u;
                const uint32_t rdst = sbase + SM_RED + (warp - 4) * 256 + min(lane >> 3, 2) * 64 + (lane & 7) * 4;
                const uint32_t lo = o_off(b * 48 + (min(lane, 23) >> 3) * 16) + (lane & 3) * 8 + (lane & 4);
                unsigned char *od0 = p.xa + xa_off(lo, 0), *od1 = p.xa + xa_off(lo, 1);
#pragma unroll
                for (int i = 0; i < 8; i++) v[i].w = ~tag;
                mbar_wait(bar_set, 0);
                mbar_wait(after(p.zero, bar_part, src, rdst, od0, od1), 0);
                {
                    const uint32_t at = now_q() + 4 * min(cfg::PDELAY, cfg::PDELAY_LAST + (NHEAD - 1 - head) * cfg::PDELAY_STEP);
                    sleep_until(at - 4 * 300);
                    wait_until(at);
                }
                n = 0;
                uint32_t bad;
#pragma unroll 1
                do {
                    if (n && head != NHEAD - 1) __nanosleep(cfg::QSLEEP);
#pragma unroll
                    for (int i = 0; i < 8; i++) pkt_ldp(src + i * 128, v[i], ((v[i].w ^ tag) & 3) != 0);
                    bad = 0;
#pragma unroll
                    for (int i = 0; i < 8; i++) bad |= v[i].w ^ tag;
                    if (++n > SPIN_LIMIT) __trap();
                } while (__any_sync(0xffffffffu, (bad & 3) != 0));
                if (u == 0) LST(119);
                float m = -INFINITY;
#pragma unroll
                for (int i = 0; i < 8; i++) m = fmaxf(m, bf_hi(v[i].w));
                m = fmaxf(m, __shfl_xor_sync(0xffffffffu, m, 8));
                m = fmaxf(m, __shfl_xor_sync(0xffffffffu, m, 16));
                float a[7] = {0.f, 0.f, 0.f, 0.f, 0.f, 0.f, 0.f};
#pragma unroll
                for (int i = 0; i < 8; i++) {
                    const float f = ex2((bf_hi(v[i].w) - m) * L2E);
                    a[0] = fmaf(f, bf_lo(v[i].x), a[0]); a[1] = fmaf(f, bf_hi(v[i].x), a[1]);
                    a[2] = fmaf(f, bf_lo(v[i].y), a[2]); a[3] = fmaf(f, bf_hi(v[i].y), a[3]);
                    a[4] = fmaf(f, bf_lo(v[i].z), a[4]); a[5] = fmaf(f, bf_hi(v[i].z), a[5]);
                    a[6] = fmaf(f, __uint_as_float(((v[i].w & 0xfffcu) << 10) + 0x3f800000u), a[6]);
                }
#pragma unroll
                for (int o = 8; o < 32; o <<= 1)
#pragma unroll
                    for (int i = 0; i < 7; i++) a[i] += __shfl_xor_sync(0xffffffffu, a[i], o);
                if (lane < 24) { sts32(rdst, lane < 8 ? a[0] : lane < 16 ? a[2] : a[4]); sts32(rdst + 32, lane < 8 ? a[1] : lane < 16 ? a[3] : a[5]); }
                if (lane == 24) sts64(rdst + 64, __float_as_uint(a[6]), __float_as_uint(m));
                asm volatile("bar.sync 7, 128;" ::: "memory");
                if (warp == 4) {
                    float2 st[4], r[4];
#pragma unroll
                    for (int i = 0; i < 4; i++) { st[i] = lds64f(sbase + SM_RED + i * 256 + 192); r[i] = lds64f(sbase + SM_RED + i * 256 + lane * 8); }
                    const float mm = fmaxf(fmaxf(st[0].y, st[1].y), fmaxf(st[2].y, st[3].y));
                    float den = 0.f, x0 = 0.f, x1 = 0.f;
#pragma unroll
                    for (int i = 0; i < 4; i++) { const float f = ex2((st[i].y - mm) * L2E); den = fmaf(f, st[i].x, den); x0 = fmaf(f, r[i].x, x0); x1 = fmaf(f, r[i].y, x1); }
                    const float inv = rcp_fast(den);
                    const float ow = __uint_as_float(pack_bf(x1 * inv, x0 * inv));
                    if (lane < 24) { in_st1(od0, ow); in_st1(od1, ow); }
                    if (lane == 0) LST(120);
                }
            }
        }
        mbar_wait(bar_pace, 0);
        const uint32_t msel = s_pace[2];
        cons_sync();
        if (is_wo) {
            uint32_t wa = sbase + (warp * 16 + arow) * 128 + ((ahalf ^ (lane & 7)) << 4);
            uint32_t pw = sbase + SM_RED + (warp * 64 + t * 16 + (lane >> 2)) * 4, pr = sbase + SM_RED + lane * 8;
            unsigned char* gdst = p.xa + xa_off(L_GATHER + (warp >> 1) % cfg::HCOPY * HCOPY_BYTES + (kg * D_MODEL + ng * 64 + lane * 2) * 2, warp & 1);
            const unsigned char* osrc = p.xa + xa_off(L_O + kg * 2048, msel) + warp * 32 + t * 8;
            uint2 ov[NWP];
#pragma unroll
            for (int j = 0; j < NWP; j++) ov[j] = make_uint2(SENT, SENT);
            auto gather = [&](int j0, int j1) {
                uint32_t n = 0;
#pragma unroll 1
                while (true) {
                    uint32_t mx = 0;
#pragma unroll
                    for (int j = j0; j < j1; j++) mx = max(mx, max(ov[j].x, ov[j].y));
                    if (!__any_sync(0xffffffffu, mx == SENT)) break;
#pragma unroll
                    for (int j = j0; j < j1; j++) in_ld2p(osrc + j * 256, ov[j], !in_ok(ov[j]));
                    if (++n > SPIN_LIMIT) __trap();
                }
            };
            float cw[4][4];
#pragma unroll
            for (int i = 0; i < 4; i++) cw[i][0] = cw[i][1] = cw[i][2] = cw[i][3] = 0.f;
            mbar_wait(after(p.zero, bar_tail + 8, osrc, wa, pw, pr, gdst), 0);
#pragma unroll
            for (int j = 0; j < NWP; j++) in_ld2p(osrc + j * 256, ov[j], true);
            gather(0, NWP - 1);
#pragma unroll
            for (int j = 0; j < NWP; j++) {
                if (j == NWP - 1) { gather(NWP - 1, NWP); if (tid == 224) LST(93); }
                mbar_wait(bar_tail + 8 * j, 0);
                if (j == NWP - 3) in_ld2p(osrc + (NWP - 1) * 256, ov[NWP - 1], !in_ok(ov[NWP - 1]));
                uint32_t a[4][4];
#pragma unroll
                for (int i = 0; i < 4; i++) ldsm_x4_t(a[i], (wa ^ (i << 5)) + j * WPIECE);
#pragma unroll
                for (int i = 0; i < 4; i++) mma_bf16(cw[i], a[i], ov[j].x, ov[j].y);
            }
#define SEL_(e) ((t & 2) ? ((t & 1) ? cw[3][e] : cw[2][e]) : ((t & 1) ? cw[1][e] : cw[0][e]))
            sts32(pw, SEL_(0)); sts32(pw + 32, SEL_(2));
#undef SEL_
            cons_sync();
            if (warp < 2 * cfg::HCOPY) {
                float2 r[8];
#pragma unroll
                for (int i = 0; i < 8; i++) r[i] = lds64f(pr + i * 256);
#define S_(c) (((r[0].c + r[1].c) + (r[2].c + r[3].c)) + ((r[4].c + r[5].c) + (r[6].c + r[7].c)))
                in_st1(gdst, __uint_as_float(pack_bf(S_(y), S_(x))));
#undef S_
            }
            if (tid == 0) LST(94);
        } else if (is_ffn) {
            uint32_t w13a = sbase + (warp * 16 + arow) * 64 + ((ahalf ^ (lane >> 1 & 3)) << 4);
            uint32_t red_dst = sbase + SM_RED + tid * 8;
            uint32_t stat = sbase + SM_MISC + warp * 8;
            uint32_t aw[NUP][4][4];
            auto load_w13 = [&](int i) {
                mbar_wait(bar_tail + 8 * i, 0);
#pragma unroll
                for (int k = 0; k < 4; k++) ldsm_x4_t(aw[i][k], (w13a ^ (k << 5 & 32)) + i * WPIECE + (k >> 1) * (WPIECE / 2));
            };
            uint32_t hp0, hp1;
            {
                const unsigned char* gsrc[NG];
                uint2 u[NG];
#pragma unroll
                for (int i = 0; i < NG; i++) { u[i] = make_uint2(0, 0); gsrc[i] = p.xa + xa_off(L_GATHER + rr % cfg::HCOPY * HCOPY_BYTES + (i * D_MODEL + hcol) * 2, msel); }
                const uint32_t at = after(p.zero, tail_time(cfg::T_HAT), gsrc[0], gsrc[1], gsrc[2], gsrc[3], gsrc[4], gsrc[5], w13a, red_dst, stat);
                sleep_until(at - 4 * 300);
                wait_until(at);
                LSC(0);
#pragma unroll
                for (int i = 0; i < NG; i++) in_ld2p(gsrc[i], u[i], lane < 4 * NUP);
                load_w13(0);
                LSCD(1, u[0].x ^ u[1].x ^ u[2].x ^ u[3].x ^ u[4].x ^ u[5].x);
                uint32_t n = 0;
#pragma unroll 1
                while (__any_sync(0xffffffffu, max(max(max(u[0].x, u[0].y), max(u[1].x, u[1].y)), max(max(max(u[2].x, u[2].y), max(u[3].x, u[3].y)),
                                                                                                    max(max(u[4].x, u[4].y), max(u[5].x, u[5].y)))) == SENT)) {
#pragma unroll
                    for (int i = 0; i < NG; i++) in_ld2p(gsrc[i], u[i], !in_ok(u[i]));
                    if (++n > SPIN_LIMIT) __trap();
                }
                if (tid == 96) LST(100);
                LSC(2);
#define F_(f, c) (f(xres.c) + bfr(((f(u[0].c) + f(u[1].c)) + (f(u[2].c) + f(u[3].c))) + (f(u[4].c) + f(u[5].c))))
                hp0 = pack_bf(F_(bf_hi, x), F_(bf_lo, x));
                hp1 = pack_bf(F_(bf_hi, y), F_(bf_lo, y));
#undef F_
            }
            {
                uint32_t b0[NUP], b1[NUP];
                float cf[4][4], cs[2][4];
#pragma unroll
                for (int e = 0; e < 4; e++) cf[0][e] = cf[1][e] = cf[2][e] = cf[3][e] = cs[0][e] = cs[1][e] = 0.f;
#pragma unroll
                for (int i = 0; i < NUP; i++) {
                    const uint32_t h0 = __shfl_sync(0xffffffffu, hp0, i * 4 + t), h1 = __shfl_sync(0xffffffffu, hp1, i * 4 + t);
                    b0[i] = (lane & 4) ? 0x3f803f80u : h0;
                    b1[i] = (lane & 4) ? 0x3f803f80u : h1;
                    const uint32_t sa[4] = {h0, h0, h1, h1};
                    mma_bf16(cs[i & 1], sa, b0[i], b1[i]);
                }
                auto mma_w13 = [&](int i) {
#pragma unroll
                    for (int k = 0; k < 4; k++) mma_bf16(cf[k], aw[i][k], b0[i], b1[i]);
                };
                if (lane == 0) sts64(stat, __float_as_uint(cs[0][0] + cs[1][0]), __float_as_uint(cs[0][1] + cs[1][1]));
                __syncwarp();
                if (lane == 0) mbar_arrive(bar_h);
                mma_w13(0);
                LSC(3);
#pragma unroll
                for (int i = 1; i < NUP - 1; i++) { load_w13(i); mma_w13(i); }
                LSC(4);
#define SEL_(k, e) ((t & 2) ? ((t & 1) ? cf[k + 1][e + 2] : cf[k + 1][e]) : ((t & 1) ? cf[k][e + 2] : cf[k][e]))
#pragma unroll
                for (int m = 0; m < 2; m++) {
                    mbar_wait(bar_tail + 8 * (NUP - 1 + m), 0);
#pragma unroll
                    for (int k = 2 * m; k < 2 * m + 2; k++) ldsm_x4_t(aw[NUP - 1][k], (w13a ^ (k << 5 & 32)) + (NUP - 1) * WPIECE + m * (WPIECE / 2));
#pragma unroll
                    for (int k = 2 * m; k < 2 * m + 2; k++) mma_bf16(cf[k], aw[NUP - 1][k], b0[NUP - 1], b1[NUP - 1]);
                    sts64(red_dst + m * 2048, __float_as_uint(SEL_(2 * m, 0)), __float_as_uint(SEL_(2 * m, 1)));
                    if (m == 0) asm volatile("bar.arrive 8, 288;" ::: "memory");
                }
                LSC(6);
#undef SEL_
            }
            LSC(7);
            asm volatile("bar.arrive 5, 288;" ::: "memory");
        }
        if (is_out) {
            uint32_t w2a = sbase + SM_W2 + (warp * 32 + arow) * 32 + ((ahalf ^ (lane >> 2 & 1)) << 4);
            uint32_t ydst = sbase + SM_HN + ((t & 1) * 8 + (lane >> 2)) * 48 + warp * 4;
            const unsigned char* asrc = p.xa + xa_off(L_ACT, msel) + oh * (NDP * 512) + warp * 64 + t * 16;
            uint32_t a[NDP][2][4];
            auto load_w2 = [&](int i) {
                mbar_wait(i ? bar_tail + 8 * (NWP + i) : after(p.zero, bar_tail + 8 * NWP, w2a, ydst, asrc), 0);
                ldsm_x4_t(a[i][0], w2a + i * PIECE); ldsm_x4_t(a[i][1], w2a + i * PIECE + 512);
            };
#pragma unroll
            for (int i = 0; i < cfg::AGATE; i++) load_w2(i);
            uint4 u[NDP];
            LSC(0);
#pragma unroll
            for (int i = 0; i < NDP; i++) u[i] = in_ld4(asrc + i * 512);
            uint32_t n = 0;
#pragma unroll 1
            while (true) {
                uint32_t m[NDP];
#pragma unroll
                for (int i = 0; i < NDP; i++) m[i] = max(max(u[i].x, u[i].y), max(u[i].z, u[i].w));
                if (!__any_sync(0xffffffffu, max(max(m[0], m[1]), m[2]) == SENT)) break;
#pragma unroll
                for (int i = 0; i < NDP; i++) in_ld4p(asrc + i * 512, u[i], m[i] == SENT);
                if (++n > SPIN_LIMIT) __trap();
            }
            LSC(12);
            if (tid == 96) LST(118);
            float cy[2 * NDP][4];
#pragma unroll
            for (int i = 0; i < NDP; i++) {
#pragma unroll
                for (int e = 0; e < 4; e++) cy[2 * i][e] = cy[2 * i + 1][e] = 0.f;
                if (i >= cfg::AGATE) load_w2(i);
                mma_bf16(cy[2 * i], a[i][0], u[i].x, u[i].y);
                mma_bf16(cy[2 * i + 1], a[i][1], u[i].z, u[i].w);
            }
#define Y_(e) (((cy[0][e] + cy[1][e]) + (cy[2][e] + cy[3][e])) + (cy[4][e] + cy[5][e]))
            const float y = (t & 1) ? Y_(2) : Y_(0);
#undef Y_
            if (t < 2) sts32(ydst, y);
            LSC(13);
            asm volatile("bar.arrive 5, 288;" ::: "memory");
        }
    }
}

typedef CUresult (*EncodeTiledFn)(CUtensorMap*, CUtensorMapDataType, cuuint32_t, void*, const cuuint64_t*, const cuuint64_t*,
                                  const cuuint32_t*, const cuuint32_t*, CUtensorMapInterleave, CUtensorMapSwizzle,
                                  CUtensorMapL2promotion, CUtensorMapFloatOOBfill);

void make_map(EncodeTiledFn fn, CUtensorMap* tm, const void* w, const int (&d)[5], const int (&st)[4], const int (&bx)[5],
              CUtensorMapSwizzle sw, int promo) {
    cuuint64_t dims[5], strides[4];
    cuuint32_t box[5], estr[5];
    for (int i = 0; i < 5; i++) { dims[i] = (cuuint64_t)d[i]; box[i] = (cuuint32_t)bx[i]; estr[i] = 1; }
    for (int i = 0; i < 4; i++) strides[i] = (cuuint64_t)st[i];
    fn(tm, CU_TENSOR_MAP_DATA_TYPE_BFLOAT16, 5, const_cast<void*>(w), dims, strides, box, estr, CU_TENSOR_MAP_INTERLEAVE_NONE, sw,
       (CUtensorMapL2promotion)promo, CU_TENSOR_MAP_FLOAT_OOB_FILL_NONE);
}

}

extern "C" void kernel_launch(void* const* d_in, const int* in_sizes, int n_in, void* d_out, int out_size) {
    (void)in_sizes; (void)n_in; (void)out_size;
    static EncodeTiledFn encode = nullptr;
    static Scratch* scratch = nullptr;
    static unsigned char* xarea = nullptr;
    static double tscale = 1.0;
    if (!encode) {
        void* sp = nullptr;
        cudaGetSymbolAddress(&sp, g_scratch);
        scratch = reinterpret_cast<Scratch*>(sp);
        cudaGetSymbolAddress(&sp, g_xarea);
        xarea = reinterpret_cast<unsigned char*>((reinterpret_cast<uintptr_t>(sp) + XA_ALIGN - 1) / XA_ALIGN * XA_ALIGN);
        void* fn = nullptr;
        cudaDriverEntryPointQueryResult st;
        cudaGetDriverEntryPoint("cuTensorMapEncodeTiled", &fn, cudaEnableDefault, &st);
        encode = reinterpret_cast<EncodeTiledFn>(fn);
        int dev = 0, khz = 0, bits = 0;
        cudaGetDevice(&dev);
        cudaDeviceGetAttribute(&khz, cudaDevAttrMemoryClockRate, dev);
        cudaDeviceGetAttribute(&bits, cudaDevAttrGlobalMemoryBusWidth, dev);
        if (khz > 0 && bits > 0) tscale = (2619000.0 * 5120.0) / ((double)khz * bits);
        cudaFuncSetAttribute(fused_decode_kernel, cudaFuncAttributeMaxDynamicSharedMemorySize, SM_TOTAL);
    }
    KParams p;
    p.x = (const __nv_bfloat16*)d_in[0];
    p.wq = (const __nv_bfloat16*)d_in[3];
    p.out = (__nv_bfloat16*)d_out;
    p.sc = scratch;
    p.xa = xarea;
    p.zero = 0;
    p.t_first = (uint32_t)(4 * cfg::T_FIRST * tscale);
    p.t_step = (uint32_t)(cfg::T_STEP * tscale);
    p.t_smax = (uint32_t)(cfg::T_SMAX * tscale);
    p.t_lat = (uint32_t)(4 * (450 + (cfg::T_LAT - 450) * tscale));
    TMaps tm;
    constexpr int R1 = FF * 2, R2 = D_MODEL * 2;
    make_map(encode, &tm.k, d_in[1], {64, NHEAD * SK * 3, 1, 1, 1}, {128, 128, 128, 128}, {64, 96, 1, 1, 1}, CU_TENSOR_MAP_SWIZZLE_128B, cfg::PROMO_KV);
    make_map(encode, &tm.v, d_in[2], {64, NHEAD * SK * 3, 1, 1, 1}, {128, 128, 128, 128}, {64, 96, 1, 1, 1}, CU_TENSOR_MAP_SWIZZLE_128B, cfg::PROMO_KV);
    make_map(encode, &tm.wo, d_in[4], {D_MODEL, NHEAD * DH, 1, 1, 1}, {R2, R2, R2, R2}, {64, 128, 1, 1, 1}, CU_TENSOR_MAP_SWIZZLE_128B, cfg::PROMO_WO);
    make_map(encode, &tm.w1, d_in[6], {FF, 2, 20, 2, 8}, {R1, 4 * R1, 2 * R1, 80 * R1}, {32, 2, 4, 2, 8}, CU_TENSOR_MAP_SWIZZLE_64B, cfg::PROMO_W13);
    make_map(encode, &tm.w3, d_in[7], {FF, 2, 20, 2, 8}, {R1, 4 * R1, 2 * R1, 80 * R1}, {32, 2, 4, 2, 8}, CU_TENSOR_MAP_SWIZZLE_64B, cfg::PROMO_W13);
    make_map(encode, &tm.w2, d_in[8], {D_MODEL, FF, 1, 1, 1}, {R2, R2, R2, R2}, {16, 256, 1, 1, 1}, CU_TENSOR_MAP_SWIZZLE_32B, cfg::PROMO_W2);
    fused_decode_kernel<<<NCTA, NTHREADS, SM_TOTAL, cudaStreamPerThread>>>(p, tm);
}
```

```cpp
#include <cuda_runtime.h>
#include <cuda_bf16.h>
#include <cuda.h>
#include <stdint.h>
#include <math.h>

namespace {

constexpr int D_MODEL = 640;
constexpr int NHEAD = 32;
constexpr int DH = 192;
constexpr int SK = 32768;
constexpr int WIN = 4096;
constexpr int FF = 1536;

constexpr int NCTA = 128;
constexpr int NCONS = 256;
constexpr int NTHREADS = NCONS + 256;
constexpr int ROW_BYTES = DH * 2;
constexpr int TILE_BYTES = 32 * ROW_BYTES;
constexpr int NSLOT = 16;
constexpr int NQT = 5;
constexpr int QSLOT = NSLOT - NQT;
constexpr int NWO = 60;
constexpr int NG = 6;
constexpr int NFFN = 48;
constexpr int NWP = 8;
constexpr int NUP = 5;
constexpr int WPIECE = 16384;
constexpr int NDP = 3;
constexpr int PIECE = 8192;
constexpr int NTAIL = NWP + NDP;
constexpr int N_TAIL0 = 2 * NHEAD;

#define CFG(name, value) constexpr int name = value
#define CFG_OVERRIDE
namespace cfg_default {
CFG(T_FIRST, 1850);
CFG(T_STEP, 1906);
CFG(T_SMAX, 1940);
CFG(CAP, 5);
CFG(MN, 12);
CFG(MA, 4);
CFG(MB, 40);
CFG(ADAPT, 60);
CFG(T_LAT, 1250);
CFG(T_WO, 296);
CFG(T_GAP, 115);
CFG(T_UP, 234);
CFG(T_UP2, 140);
CFG(T_W2AT, 1300);
CFG(T_W2, 200);
CFG(T_HAT, 1160);
CFG(T_RESAT, 1750);
CFG(AGATE, 2);
CFG(KEEP_AT, 65);
CFG(KEEP, 150);
CFG(HCOPY, 1);
CFG(QDELAY, 1200);
CFG(QDELAY2, 900);
CFG(QSLEEP, 400);
CFG(PDELAY, 2500);
CFG(PDELAY_LAST, 250);
CFG(PDELAY_STEP, 650);
CFG(PREPART, 3);
CFG(RBDELAY, 5000);
CFG(NPROBE, 10);
CFG(VOTES, 3);
CFG(PROMO_KV, 2);
CFG(PROMO_WO, 2);
CFG(PROMO_W13, 2);
CFG(PROMO_W2, 2);
CFG(HPRE, 3);
CFG(BOUNDED_MBAR, 0);
}
namespace cfg { using namespace cfg_default; CFG_OVERRIDE }

constexpr int SM_RING = 0;
constexpr int SM_W2 = NWP * WPIECE;
constexpr int SM_Q = SM_RING + NSLOT * TILE_BYTES;
constexpr int SM_RED = SM_Q + NHEAD * ROW_BYTES;
constexpr int SM_HN = SM_RED + 4096;
constexpr int SM_MISC = SM_HN + D_MODEL * 2;
constexpr int SM_BAR = SM_MISC + 128;
constexpr int SM_TOTAL = SM_BAR + 512;
static_assert(SM_TOTAL <= 232448, "shared memory");

struct __align__(128) Scratch {
    uint4 part[NHEAD * 4 * NCTA * 8];
    uint64_t q1[NHEAD * 4 * DH];
    uint4 q2[NHEAD * 32];
    uint32_t epoch;
    uint32_t pad;
    unsigned long long pace[2];
};
__device__ Scratch g_scratch;
constexpr int XA_ALIGN = 1 << 20;
constexpr uint32_t SENT = 0xffffffffu;
constexpr int L_GATHER = 0;
constexpr int HCOPY_BYTES = NG * D_MODEL * 2;
constexpr int L_O = 9 * 4096;
constexpr int L_ACT = 30 * 4096;
constexpr int L_PROBE = 32 * 4096;
static_assert(2 * (L_PROBE + NCTA * 1024) <= XA_ALIGN, "");
__device__ unsigned char g_xarea[2 * XA_ALIGN];
__device__ __forceinline__ uint32_t xa_off(uint32_t l, uint32_t side) {
    const uint32_t k = l >> 12;
    return (2 * k + ((side ^ k ^ (k >> 3) ^ (k >> 4) ^ (k >> 6)) & 1)) * 4096 + (l & 4095);
}

__device__ __forceinline__ uint32_t o_off(uint32_t r) { return L_O + (r >> 7) % NG * 2048 + (r >> 7) / NG * 256 + (r & 127) * 2; }

#define LST(i) do { } while (0)
#define LSC(i) do { } while (0)
#define LSCD(i, v) do { } while (0)
constexpr uint32_t SPIN_LIMIT = cfg::BOUNDED_MBAR ? 1u << 14 : 1u << 22;

__device__ __forceinline__ uint32_t now_q() { uint32_t t; asm volatile("mov.u32 %0, %globaltimer_lo;" : "=r"(t)); return t * 4; }
__device__ __forceinline__ void wait_until(uint32_t due) {
#pragma unroll 1
    for (int n = 0; n < 4096 && (int)(now_q() - due) < 0; n++) { }
}
__device__ __forceinline__ void sleep_until(uint32_t due) {
#pragma unroll 1
    for (int n = 0; n < 4096 && (int)(now_q() - due) < 0; n++) __nanosleep(200);
}
__device__ __forceinline__ uint32_t smem_u32(const void* p) { return (uint32_t)__cvta_generic_to_shared(p); }
__device__ __forceinline__ void mbar_init(uint32_t bar, uint32_t cnt) {
    asm volatile("mbarrier.init.shared::cta.b64 [%0], %1;" ::"r"(bar), "r"(cnt) : "memory");
}
__device__ __forceinline__ void mbar_expect_tx(uint32_t bar, uint32_t bytes) {
    asm volatile("mbarrier.arrive.expect_tx.shared::cta.b64 _, [%0], %1;" ::"r"(bar), "r"(bytes) : "memory");
}
__device__ __forceinline__ void mbar_arrive(uint32_t bar) {
    asm volatile("mbarrier.arrive.shared::cta.b64 _, [%0];" ::"r"(bar) : "memory");
}
__device__ __forceinline__ bool mbar_test(uint32_t bar, uint32_t parity) {
    uint32_t ok;
    asm volatile("{\n.reg .pred p;\nmbarrier.test_wait.parity.shared::cta.b64 p, [%1], %2;\nselp.u32 %0, 1, 0, p;\n}"
                 : "=r"(ok) : "r"(bar), "r"(parity) : "memory");
    return ok;
}
__device__ __forceinline__ bool mbar_try(uint32_t bar, uint32_t parity) {
    uint32_t ok;
    asm volatile("{\n.reg .pred p;\nmbarrier.try_wait.parity.shared::cta.b64 p, [%1], %2;\nselp.u32 %0, 1, 0, p;\n}"
                 : "=r"(ok) : "r"(bar), "r"(parity) : "memory");
    return ok;
}
__device__ __forceinline__ void mbar_wait(uint32_t bar, uint32_t parity) {
    if (cfg::BOUNDED_MBAR) {
        uint32_t n = 0;
        while (!mbar_try(bar, parity)) if (++n > SPIN_LIMIT) __trap();
    } else {
        asm volatile("{\n.reg .pred p;\nW_%=:\nmbarrier.try_wait.parity.shared::cta.b64 p, [%0], %1;\n@!p bra W_%=;\n}" ::"r"(bar), "r"(parity) : "memory");
    }
}
__device__ __forceinline__ void tma_tile(uint32_t dst, const CUtensorMap* tm, int c1, uint32_t bar, uint64_t pol) {
    asm volatile("cp.async.bulk.tensor.5d.shared::cluster.global.mbarrier::complete_tx::bytes.L2::cache_hint [%0], [%1, {%4, %3, %4, %4, %4}], [%2], %5;"
                 ::"r"(dst), "l"(reinterpret_cast<uint64_t>(tm)), "r"(bar), "r"(c1), "r"(0), "l"(pol) : "memory");
}
__device__ __forceinline__ void tma_5d(uint32_t dst, const CUtensorMap* tm, int c0, int c1, int c2, int c4, uint32_t bar) {
    asm volatile("cp.async.bulk.tensor.5d.shared::cluster.global.mbarrier::complete_tx::bytes [%0], [%1, {%3, %4, %5, %7, %6}], [%2];"
                 ::"r"(dst), "l"(reinterpret_cast<uint64_t>(tm)), "r"(bar), "r"(c0), "r"(c1), "r"(c2), "r"(c4), "r"(0) : "memory");
}
__device__ __forceinline__ uint32_t bits(uint32_t v) { return v; }
__device__ __forceinline__ uint32_t bits(float v) { return __float_as_uint(v); }
__device__ __forceinline__ uint32_t bits(const void* v) { return (uint32_t)(uintptr_t)v ^ (uint32_t)((uintptr_t)v >> 32); }
template <class... T> __device__ __forceinline__ uint32_t after(uint32_t zero, uint32_t bar, T... v) { return bar | ((bits(v) ^ ...) & zero); }
__device__ __forceinline__ void sts32(uint32_t a, float v) { asm volatile("st.shared.f32 [%0], %1;" ::"r"(a), "f"(v) : "memory"); }
__device__ __forceinline__ void sts64(uint32_t a, uint32_t x, uint32_t y) { asm volatile("st.shared.v2.u32 [%0], {%1, %2};" ::"r"(a), "r"(x), "r"(y) : "memory"); }
__device__ __forceinline__ void cons_sync() { asm volatile("bar.sync 1, 256;" ::: "memory"); }

__device__ __forceinline__ uint4 lds128(uint32_t a) {
    uint4 v;
    asm volatile("ld.shared.v4.u32 {%0,%1,%2,%3}, [%4];" : "=r"(v.x), "=r"(v.y), "=r"(v.z), "=r"(v.w) : "r"(a));
    return v;
}
__device__ __forceinline__ float4 lds128f(uint32_t a) {
    float4 v;
    asm volatile("ld.shared.v4.f32 {%0,%1,%2,%3}, [%4];" : "=f"(v.x), "=f"(v.y), "=f"(v.z), "=f"(v.w) : "r"(a) : "memory");
    return v;
}
__device__ __forceinline__ float2 lds64f(uint32_t a) {
    float2 v;
    asm volatile("ld.shared.v2.f32 {%0,%1}, [%2];" : "=f"(v.x), "=f"(v.y) : "r"(a) : "memory");
    return v;
}
__device__ __forceinline__ uint32_t lds32(uint32_t a) {
    uint32_t v;
    asm volatile("ld.shared.u32 %0, [%1];" : "=r"(v) : "r"(a));
    return v;
}
__device__ __forceinline__ void ldsm_x4(uint32_t* r, uint32_t a) {
    asm volatile("ldmatrix.sync.aligned.m8n8.x4.shared.b16 {%0,%1,%2,%3}, [%4];"
                 : "=r"(r[0]), "=r"(r[1]), "=r"(r[2]), "=r"(r[3]) : "r"(a));
}
__device__ __forceinline__ void ldsm_x4_t(uint32_t* r, uint32_t a) {
    asm volatile("ldmatrix.sync.aligned.m8n8.x4.trans.shared.b16 {%0,%1,%2,%3}, [%4];"
                 : "=r"(r[0]), "=r"(r[1]), "=r"(r[2]), "=r"(r[3]) : "r"(a));
}
__device__ __forceinline__ void mma_bf16(float* c, const uint32_t* a, uint32_t b0, uint32_t b1) {
    asm volatile("mma.sync.aligned.m16n8k16.row.col.f32.bf16.bf16.f32 {%0,%1,%2,%3}, {%4,%5,%6,%7}, {%8,%9}, {%0,%1,%2,%3};"
                 : "+f"(c[0]), "+f"(c[1]), "+f"(c[2]), "+f"(c[3]) : "r"(a[0]), "r"(a[1]), "r"(a[2]), "r"(a[3]), "r"(b0), "r"(b1));
}
__device__ __forceinline__ float bf_lo(uint32_t u) { return __uint_as_float(u << 16); }
__device__ __forceinline__ float bf_hi(uint32_t u) { return __uint_as_float(u & 0xffff0000u); }
__device__ __forceinline__ uint32_t pack_bf(float hi, float lo) { uint32_t r; asm("cvt.rn.bf16x2.f32 %0, %1, %2;" : "=r"(r) : "f"(hi), "f"(lo)); return r; }
__device__ __forceinline__ float bfr(float x) { return __uint_as_float(pack_bf(x, 0.f)); }

__device__ __forceinline__ uint64_t pk(float v, uint32_t tag) { return ((uint64_t)tag << 32) | (uint64_t)__float_as_uint(v); }
__device__ __forceinline__ void ll_st1(uint64_t* p, float a, uint32_t tag) {
    asm volatile("st.relaxed.gpu.global.b64 [%0], %1;" ::"l"(p), "l"(pk(a, tag)) : "memory");
}
__device__ __forceinline__ uint4 ll_ld2(const uint4* p) {
    uint4 v;
    asm volatile("{\n.reg .b64 a, b;\nld.relaxed.gpu.global.v2.b64 {a, b}, [%4];\nmov.b64 {%0, %1}, a;\nmov.b64 {%2, %3}, b;\n}"
                 : "=r"(v.x), "=r"(v.y), "=r"(v.z), "=r"(v.w) : "l"(p) : "memory");
    return v;
}
__device__ __forceinline__ uint32_t in_word(float v) {
    uint32_t r;
    asm("min.u32 %0, %1, 0xfffffffe;" : "=r"(r) : "r"(__float_as_uint(v)));
    return r;
}
__device__ __forceinline__ void in_st1(void* p, float v) {
    asm volatile("st.relaxed.gpu.global.u32 [%0], %1;" ::"l"(p), "r"(in_word(v)) : "memory");
}
__device__ __forceinline__ void in_st4(void* p, uint32_t a, uint32_t b, uint32_t c, uint32_t d) {
    asm volatile("st.relaxed.gpu.global.v4.u32 [%0], {%1, %2, %3, %4};" ::"l"(p), "r"(a), "r"(b), "r"(c), "r"(d) : "memory");
}
__device__ __forceinline__ uint32_t in_ld1(const void* p) {
    uint32_t v;
    asm volatile("ld.relaxed.gpu.global.u32 %0, [%1];" : "=r"(v) : "l"(p) : "memory");
    return v;
}
__device__ __forceinline__ uint4 in_ld4(const void* p) {
    uint4 v;
    asm volatile("ld.relaxed.gpu.global.v4.u32 {%0, %1, %2, %3}, [%4];" : "=r"(v.x), "=r"(v.y), "=r"(v.z), "=r"(v.w) : "l"(p) : "memory");
    return v;
}
__device__ __forceinline__ void in_ld2p(const void* p, uint2& v, bool on) {
    asm volatile("{\n.reg .pred q;\nsetp.ne.u32 q, %3, 0;\n@q ld.relaxed.gpu.global.v2.u32 {%0, %1}, [%2];\n}"
                 : "+r"(v.x), "+r"(v.y) : "l"(p), "r"((uint32_t)on) : "memory");
}
__device__ __forceinline__ bool in_ok(const uint2& v) { return max(v.x, v.y) != SENT; }
__device__ __forceinline__ void in_ld4p(const void* p, uint4& v, bool on) {
    asm volatile("{\n.reg .pred q;\nsetp.ne.u32 q, %5, 0;\n@q ld.relaxed.gpu.global.v4.u32 {%0, %1, %2, %3}, [%4];\n}"
                 : "+r"(v.x), "+r"(v.y), "+r"(v.z), "+r"(v.w) : "l"(p), "r"((uint32_t)on) : "memory");
}
__device__ __forceinline__ void pkt_st(uint4* p, uint32_t x, uint32_t y, uint32_t z, uint32_t w) {
    asm volatile("{\n.reg .b128 t;\n.reg .b64 a, b;\nmov.b64 a, {%1, %2};\nmov.b64 b, {%3, %4};\nmov.b128 t, {a, b};\nst.relaxed.gpu.global.b128 [%0], t;\n}"
                 ::"l"(p), "r"(x), "r"(y), "r"(z), "r"(w) : "memory");
}
__device__ __forceinline__ void pkt_ldp(const uint4* p, uint4& v, bool on) {
    asm volatile("{\n.reg .pred q;\n.reg .b128 t;\n.reg .b64 a, b;\nsetp.ne.u32 q, %5, 0;\nmov.b64 a, {%0, %1};\nmov.b64 b, {%2, %3};\nmov.b128 t, {a, b};\n"
                 "@q ld.relaxed.gpu.global.b128 t, [%4];\nmov.b128 {a, b}, t;\nmov.b64 {%0, %1}, a;\nmov.b64 {%2, %3}, b;\n}"
                 : "+r"(v.x), "+r"(v.y), "+r"(v.z), "+r"(v.w) : "l"(p), "r"((uint32_t)on) : "memory");
}

__device__ __forceinline__ float sqrt_fast(float x) { float r; asm("sqrt.approx.ftz.f32 %0, %1;" : "=f"(r) : "f"(x)); return r; }
__device__ __forceinline__ float rcp_fast(float x) { float r; asm("rcp.approx.ftz.f32 %0, %1;" : "=f"(r) : "f"(x)); return r; }
__device__ __forceinline__ float ex2(float x) { float r; asm("ex2.approx.ftz.f32 %0, %1;" : "=f"(r) : "f"(x)); return r; }
constexpr float L2E = 1.4426950408889634f;
__device__ __forceinline__ void ln_stats(const uint2* v, float& mean_b, float& inv_den) {
    float s1[5], s2[5];
#pragma unroll
    for (int i = 0; i < 5; i++) {
        const float a0 = bf_lo(v[i].x), a1 = bf_hi(v[i].x), a2 = bf_lo(v[i].y), a3 = bf_hi(v[i].y);
        s1[i] = (a0 + a1) + (a2 + a3);
        s2[i] = fmaf(a0, a0, a1 * a1) + fmaf(a2, a2, a3 * a3);
    }
    float t1 = ((s1[0] + s1[1]) + (s1[2] + s1[3])) + s1[4], t2 = ((s2[0] + s2[1]) + (s2[2] + s2[3])) + s2[4];
#pragma unroll
    for (int o = 16; o > 0; o >>= 1) { t1 += __shfl_xor_sync(0xffffffffu, t1, o); t2 += __shfl_xor_sync(0xffffffffu, t2, o); }
    const float mean = t1 * (1.0f / D_MODEL);
    const float var = fmaxf(fmaf(-mean, mean, t2 * (1.0f / D_MODEL)), 0.f);
    mean_b = bfr(mean);
    inv_den = rcp_fast(bfr(sqrt_fast(bfr(bfr(var) + 1e-5f))));
}

struct KParams {
    const __nv_bfloat16* wq;
    uint32_t t_first;
    uint32_t t_step;
    const __nv_bfloat16* x;
    Scratch* sc;
    unsigned char* xa;
    __nv_bfloat16* out;
    uint32_t t_smax;
    uint32_t t_lat;
    uint32_t zero;
};
struct TMaps { CUtensorMap k, v, wo, w1, w3, w2; };

__global__ void __launch_bounds__(NTHREADS, 1)
fused_decode_kernel(const KParams p, const __grid_constant__ TMaps tm) {
    extern __shared__ __align__(1024) unsigned char smem[];
    const uint32_t sbase = smem_u32(smem);
    const int tid = threadIdx.x;
    const int b = blockIdx.x;
    const int head = b >> 2, sp = b & 3;
    {
        if (tid < 192) {
            const uint32_t rg = tid / 24, ch = tid - rg * 24;
            const char* src = reinterpret_cast<const char*>(p.wq) + (uint32_t)(sp * 160 * (NHEAD * DH * 2) + head * ROW_BYTES + rg * (NHEAD * DH * 2) + ch * 16);
            uint32_t dst = sbase + SM_RING + QSLOT * TILE_BYTES + ((tid ^ (tid >> 3 & 7)) << 4);
#pragma unroll 4
            for (int i = 0; i < 20; i++) {
                asm volatile("cp.async.cg.shared.global [%0], [%1], 16;" ::"r"(dst), "l"(src) : "memory");
                dst += 8 * ROW_BYTES;
                src += (size_t)8 * (NHEAD * DH * 2);
            }
        }
    }
    const int warp = __shfl_sync(0xffffffffu, tid >> 5, 0), lane = tid & 31;
    const int rr = !(b & 1) ? b >> 1 : (b & 15) < 12 ? (b >> 4) * 6 + (b >> 1 & 7) : NFFN + (b >> 4) * 2 + (b >> 1 & 1);
    const bool is_wo = !(b & 1) && rr < NWO, is_ffn = (b & 1) && rr < NFFN, is_out = !is_ffn;
    const int og = (rr >> 2) + (b & 1) * 4, oh = og >= 10, oq = (og - 10 * oh) * 4 + (rr & 3);
    const int kg = min(rr / 10, NG - 1), ng = rr % 10;
    const uint32_t bar_full = sbase + SM_BAR;
    const uint32_t bar_empty = sbase + SM_BAR + 128;
    const uint32_t bar_tail = sbase + SM_BAR + 256;
    const uint32_t bar_set = bar_tail + 8 * NTAIL;
    const uint32_t bar_pace = bar_set + 8;
    const uint32_t bar_q = bar_set + 16;
    const uint32_t bar_part = bar_set + 24;
    volatile uint32_t* s_pace = reinterpret_cast<volatile uint32_t*>(smem + SM_MISC + 64);
    auto tail_time = [&](int t) { return s_pace[0] + (s_pace[1] * (((N_TAIL0 - cfg::ADAPT) * 478 + NWP * cfg::T_WO + t) * 256 / 478) >> 8); };

    if (warp == 8) {
        const uint32_t c_start = now_q();
        if (lane >= 1 && lane <= 6) asm volatile("prefetch.tensormap [%0];" ::"l"(reinterpret_cast<uint64_t>(&tm.k + (lane - 1))) : "memory");
        uint64_t pol_stream;
        asm volatile("createpolicy.fractional.L2::evict_first.b64 %0, 1.0;" : "=l"(pol_stream));
        if (lane == 0) {
#pragma unroll 1
            for (int i = 0; i < NSLOT; i++) { mbar_init(bar_full + 8 * i, 1); mbar_init(bar_empty + 8 * i, 1); }
#pragma unroll 1
            for (int i = 0; i < NTAIL + 4; i++) mbar_init(bar_tail + 8 * i, i == NTAIL + 2 ? 4 : 1);
            asm volatile("fence.mbarrier_init.release.cluster;" ::: "memory");
        }
        __syncwarp();
        asm volatile("bar.arrive 2, 288;" ::: "memory");
        asm volatile("bar.arrive 3, 64;" ::: "memory");
        asm volatile("bar.arrive 4, 64;" ::: "memory");
        if (is_ffn) asm volatile("bar.arrive 10, 192;" ::: "memory");
        if (lane == 0) {
            uint32_t due = c_start + p.t_first, step = p.t_step;
#pragma unroll 1
            for (int n = 0; n < N_TAIL0; n++) {
                const int slot = n & (NSLOT - 1);
                const int use = (n >> 4) + (slot >= QSLOT);
                if (n >= cfg::CAP) mbar_wait(bar_full + 8 * ((n - cfg::CAP) & (NSLOT - 1)), ((n - cfg::CAP) >> 4) & 1);
                if (use >= 1) mbar_wait(bar_empty + 8 * slot, (use - 1) & 1);
                if (n == cfg::ADAPT) { mbar_wait(bar_pace, 0); due = s_pace[0]; step = s_pace[1]; }
                const uint32_t full = bar_full + 8 * slot;
                mbar_expect_tx(full, TILE_BYTES);
                wait_until(due);
                LST(128 + n);
                tma_tile(sbase + SM_RING + slot * TILE_BYTES, &tm.k + (n & 1), ((n >> 1) * SK + (SK - WIN) + b * 32) * 3, full, pol_stream);
                due += step;
            }
            int rel = 0;
            auto released = [&](int end) {
#pragma unroll 1
                for (; rel * TILE_BYTES < end; rel++) mbar_wait(bar_empty + 8 * rel, rel < QSLOT);
            };
            const uint32_t t_wo = step * (cfg::T_WO * 4096 / 478) >> 12;
            if (is_wo) {
#pragma unroll 1
                for (int j = 0; j < NWP; j++) {
                    released((j + 1) * WPIECE);
                    mbar_expect_tx(bar_tail + 8 * j, WPIECE);
                    wait_until(due);
                    LST(128 + N_TAIL0 + j);
                    tma_5d(sbase + j * WPIECE, &tm.wo, ng * 64, j * (NG * 128) + kg * 128, 0, 0, bar_tail + 8 * j);
                    due += t_wo;
                }
            } else {
                due += NWP * t_wo;
            }
            due += 4 * cfg::T_GAP;
            if (is_out) {
                due += step * (cfg::T_W2AT * 4096 / 478) >> 12;
                released(SM_W2 + NDP * PIECE);
#pragma unroll
                for (int j = 0; j < NDP; j++) mbar_expect_tx(bar_tail + 8 * (NWP + j), PIECE);
                sleep_until(due - 4 * 400);
#pragma unroll
                for (int j = 0; j < NDP; j++) {
                    wait_until(due);
                    tma_5d(sbase + SM_W2 + j * PIECE, &tm.w2, oq * 16, (oh * NDP + j) * 256, 0, 0, bar_tail + 8 * (NWP + j));
                    LST(128 + N_TAIL0 + NWP + j);
                    due += step * (cfg::T_W2 * 4096 / 478) >> 12;
                }
            } else if (is_ffn) {
                released(NUP * WPIECE);
#pragma unroll
                for (int j = 0; j <= NUP; j++) mbar_expect_tx(bar_tail + 8 * j, j < NUP - 1 ? WPIECE : WPIECE / 2);
                sleep_until(due - 4 * 400);
#pragma unroll
                for (int j = 0; j <= NUP; j++) {
                    const uint32_t full = bar_tail + 8 * j;
                    const int i = min(j, NUP - 1);
                    wait_until(due);
                    if (j < NUP) tma_5d(sbase + i * WPIECE, &tm.w1, rr * 32, 0, 0, i * 8, full);
                    if (j != NUP - 1) tma_5d(sbase + i * WPIECE + WPIECE / 2, &tm.w3, rr * 32, 0, 0, i * 8, full);
                    LST(128 + N_TAIL0 + j);
                    due += step * ((j < NUP - 1 ? cfg::T_UP : cfg::T_UP2) * 4096 / 478) >> 12;
                }
            }
        }
    } else if (warp == 10) {
        asm volatile("bar.sync 4, 64;" ::: "memory");
        if (lane == 0) {
            uint32_t epoch0;
            asm volatile("ld.relaxed.gpu.global.u32 %0, [%1];" : "=r"(epoch0) : "l"(&p.sc->epoch) : "memory");
            constexpr int MN = cfg::MN;
            const uint32_t t0 = now_q();
            uint32_t sa = 0, sb = 0;
#pragma unroll 1
            for (int n = 0; n < cfg::MB + MN; n++) {
#pragma unroll 1
                for (int k = 0; k < 256 && !mbar_try(bar_full + 8 * (n & (NSLOT - 1)), (n >> 4) & 1); k++) { }
                const uint32_t t = now_q() - t0;
                LST(n);
                if ((uint32_t)(n - cfg::MA) < MN) sa += t;
                if (n >= cfg::MB) sb += t;
            }
            const uint32_t mb = t0 + sb / MN;
            unsigned long long* pace = p.sc->pace + ((epoch0 + 1) & 1);
            mbar_wait(bar_set, 0);
            asm volatile("red.relaxed.gpu.global.add.u64 [%0], %1;" ::"l"(pace), "l"((unsigned long long)mb << 32 | min((sb - sa) / (4 * MN), 0xffffu) << 8 | 1) : "memory");
            if (b == 0) p.sc->pace[epoch0 & 1] = 0;
            unsigned long long v;
            uint32_t n = 0, cnt;
#pragma unroll 1
            do {
                __nanosleep(n ? 200 : 1000);
                asm volatile("ld.relaxed.gpu.global.u64 %0, [%1];" : "=l"(v) : "l"(pace) : "memory");
                cnt = (uint32_t)v & 0xff;
                if (++n > SPIN_LIMIT) __trap();
            } while (cnt < NCTA);
            const uint32_t step = min(max(((uint32_t)v >> 8) / (NCTA / 4 * (cfg::MB - cfg::MA)), p.t_step), p.t_smax);
            s_pace[0] = mb + (int)((uint32_t)(v >> 32) - NCTA * mb) / NCTA + step * (2 * (cfg::ADAPT - cfg::MB) - (MN - 1)) / 2 - p.t_lat;
            s_pace[1] = step;
            mbar_arrive(bar_pace);
            LST(89);
        }
    } else if (warp == 9) {
        const uint32_t c_start = now_q();
        uint32_t epoch0;
        asm volatile("ld.relaxed.gpu.global.u32 %0, [%1];" : "=r"(epoch0) : "l"(&p.sc->epoch) : "memory");
        sleep_until(c_start + p.t_first);
        unsigned char* slot[2];
        slot[0] = p.xa + xa_off(o_off(b * 48 + (lane % 6) * 8), lane / 6 & 1);
        slot[1] = p.xa + (is_wo ? xa_off(L_GATHER + (lane >> 4) * HCOPY_BYTES + (kg * D_MODEL + ng * 64 + (lane & 7) * 8) * 2, lane >> 3 & 1)
                                : xa_off(L_ACT + rr * 64 + (lane & 3) * 16, lane >> 2 & 1));
        const int n2 = is_wo ? 16 * cfg::HCOPY : is_ffn ? 8 : 0;
#pragma unroll
        for (int i = 0; i < 2; i++) if (lane < (i ? n2 : 12)) in_st4(slot[i], SENT, SENT, SENT, SENT);
#pragma unroll
        for (int i = 1; i <= cfg::PREPART; i++) pkt_st(p.sc->part + (((NHEAD - i) * 4 + (lane & 3)) * NCTA + b) * 8 + (lane >> 2), 0, 0, 0, epoch0 & 3);
        unsigned char* probe = p.xa + xa_off(L_PROBE + b * 1024 + (lane >> 1 & 7) * 128 + (lane & 1) * 16, lane >> 4);
        in_st4(probe, SENT, SENT, SENT, SENT);
        const bool clr = is_out && !oh && lane < 2;
        if (clr) in_st4(p.out + oq * 16 + lane * 8, 0, 0, 0, 0);
        sleep_until(now_q() + 4 * cfg::RBDELAY + b * 60);
        uint32_t acc = SENT;
#pragma unroll
        for (int i = 0; i < 2; i++) if (lane < (i ? n2 : 12)) acc &= in_ld1(slot[i]);
        if (clr) acc &= ~in_ld1(p.out + oq * 16 + lane * 8);
        if (__any_sync(0xffffffffu, acc != SENT)) __trap();
        int vote = 0;
        uint32_t lat[2] = {0, 0};
#pragma unroll 1
        for (int r = 0; r <= cfg::NPROBE && abs(vote) < cfg::VOTES; r++) {
            __nanosleep(300);
            uint32_t d[2];
#pragma unroll
            for (int i = 0; i < 2; i++) {
                const uint32_t c0 = (uint32_t)clock();
                if (__any_sync(0xffffffffu, in_ld1(p.xa + xa_off(L_PROBE + b * 1024 + (lane & 7) * 128, i)) != SENT)) __trap();
                d[i] = (uint32_t)clock() - c0;
                if (r) lat[i] += min(d[i], 1500u);
            }
            if (r) vote = __shfl_sync(0xffffffffu, vote + (d[1] < d[0]) - (d[0] < d[1]), 0);
        }
        const uint32_t sel = vote ? vote > 0 : lat[1] < lat[0];
        const uint32_t tag = epoch0 + 1;
        asm volatile("bar.sync 3, 64;" ::: "memory");
        if (lane == 0) { s_pace[2] = sel; mbar_arrive(bar_set); }
        {
            mbar_wait(bar_pace, 0);
            sleep_until(s_pace[0] + (cfg::KEEP_AT - cfg::ADAPT) * s_pace[1]);
            const uint32_t t_res = tail_time(cfg::T_RESAT);
            float c[4] = {0.f, 0.f, 0.f, 0.f};
            const uint32_t z[4] = {p.zero, p.zero, p.zero, p.zero};
            uint32_t n = 0;
#pragma unroll 1
            do {
                mma_bf16(c, z, p.zero, p.zero);
                __nanosleep(cfg::KEEP);
                n += 1 + __float_as_uint(c[0]);
            } while (!__all_sync(0xffffffffu, is_ffn ? mbar_test(bar_tail, 0) : (int)(now_q() - t_res) >= 0) && n < SPIN_LIMIT);
            if (is_ffn) {
                unsigned char* adst = p.xa + xa_off(L_ACT + rr * 64 + (lane >> 3) * 16 + (lane & 3) * 4, lane >> 2 & 1);
                uint32_t src = sbase + SM_RED + lane * 8;
                asm volatile("bar.sync %0, 192;" ::"r"(after(p.zero, 11, adst, src)) : "memory");
                float mean_b, inv_den;
                {
                    uint2 hv[5];
#pragma unroll
                    for (int i = 0; i < 5; i++) { const float2 v = lds64f(sbase + SM_HN + i * 256 + lane * 8); hv[i] = make_uint2(__float_as_uint(v.x), __float_as_uint(v.y)); }
                    ln_stats(hv, mean_b, inv_den);
                }
                float2 r[8];
#define S_(c) (((r[0].c + r[1].c) + (r[2].c + r[3].c)) + ((r[4].c + r[5].c) + (r[6].c + r[7].c)))
                asm volatile("bar.sync %0, 288;" ::"r"(after(p.zero, 8, inv_den, mean_b)) : "memory");
#pragma unroll
                for (int i = 0; i < 8; i++) r[i] = lds64f(src + i * 256);
                const float gate = bfr(fmaf(-mean_b, S_(y), S_(x)) * inv_den);
                const float silu = bfr(__fdividef(gate, 1.0f + ex2(-gate * L2E)));
                asm volatile("bar.sync %0, 288;" ::"r"(after(p.zero, 5, silu)) : "memory");
#pragma unroll
                for (int i = 0; i < 8; i++) r[i] = lds64f(src + 2048 + i * 256);
                const float act = silu * bfr(fmaf(-mean_b, S_(y), S_(x)) * inv_den);
#undef S_
                const float oth = __shfl_xor_sync(0xffffffffu, act, 4);
                in_st1(adst, __uint_as_float((lane & 4) ? pack_bf(act, oth) : pack_bf(oth, act)));
                if (lane == 0) LST(110);
            }
            if (is_out) {
                const int col = oq * 16 + (lane & 15);
                float res = 0.f;
                if (!oh) {
                    uint32_t u[NG], xv;
                    asm volatile("ld.global.nc.u16 %0, [%1];" : "=r"(xv) : "l"(p.x + col));
                    n = 0;
#pragma unroll 1
                    do {
#pragma unroll
                        for (int i = 0; i < NG; i++) u[i] = in_ld1(p.xa + xa_off(L_GATHER + rr % cfg::HCOPY * HCOPY_BYTES + (i * D_MODEL + (col & ~1)) * 2, sel));
                        if (++n > SPIN_LIMIT) __trap();
                    } while (__any_sync(0xffffffffu, max(max(max(u[0], u[1]), max(u[2], u[3])), max(u[4], u[5])) == SENT));
                    if (b == 0 && lane == 0) p.sc->epoch = tag;
#define F_(i) ((lane & 1) ? bf_hi(u[i]) : bf_lo(u[i]))
                    res = bfr(bf_lo(xv) + bfr(((F_(0) + F_(1)) + (F_(2) + F_(3))) + (F_(4) + F_(5))));
#undef F_
                }
                mma_bf16(c, z, p.zero, p.zero);
                mbar_wait(after(p.zero, bar_tail + 8 * NWP, c[0]), 0);
                mma_bf16(c, z, p.zero, p.zero);
                res += c[0];
                __nv_bfloat16* dst = p.out + (col & ~1);
                uint32_t src = sbase + SM_HN + (lane & 15) * 48;
                asm volatile("bar.sync %0, 288;" ::"r"(after(p.zero, 5, src, dst, res)) : "memory");
                const float4 ra = lds128f(src), rb = lds128f(src + 16);
                const float e = ((ra.x + ra.y) + (ra.z + ra.w)) + (((rb.x + rb.y) + (rb.z + rb.w)) + res);
                if (lane < 16) asm volatile("red.relaxed.gpu.global.add.noftz.bf16x2 [%0], %1;" ::"l"(dst), "r"((lane & 1) ? pack_bf(e, 0.f) : pack_bf(0.f, e)) : "memory");
                if (lane == 0) LST(96);
            }
        }
    } else if (warp > 10) {
        if (is_ffn) {
            const int col = (tid - 352) * 4;
            uint2 xres;
            asm volatile("bar.sync 10, 192;" ::: "memory");
            mbar_wait(bar_pace, 0);
            asm volatile("ld.global.nc.v2.u32 {%0, %1}, [%2];" : "=r"(xres.x), "=r"(xres.y) : "l"(p.x + col) : "memory");
            const unsigned char* gsrc[NG];
            uint2 u[NG];
#pragma unroll
            for (int i = 0; i < NG; i++) gsrc[i] = p.xa + xa_off(L_GATHER + rr % cfg::HCOPY * HCOPY_BYTES + (i * D_MODEL + col) * 2, s_pace[2]);
            const uint32_t hdst = sbase + SM_HN + col * 2;
            const uint32_t at = after(p.zero, tail_time(cfg::T_HAT), gsrc[0], gsrc[1], gsrc[2], gsrc[3], gsrc[4], gsrc[5], hdst, xres.x);
            sleep_until(at - 4 * 300);
            wait_until(at);
#pragma unroll
            for (int i = 0; i < NG; i++) { u[i] = make_uint2(0, 0); in_ld2p(gsrc[i], u[i], true); }
            uint32_t n = 0;
#pragma unroll 1
            while (__any_sync(0xffffffffu, max(max(max(u[0].x, u[0].y), max(u[1].x, u[1].y)), max(max(max(u[2].x, u[2].y), max(u[3].x, u[3].y)),
                                                                                                max(max(u[4].x, u[4].y), max(u[5].x, u[5].y)))) == SENT)) {
#pragma unroll
                for (int i = 0; i < NG; i++) in_ld2p(gsrc[i], u[i], !in_ok(u[i]));
                if (++n > SPIN_LIMIT) __trap();
            }
#define F_(f, c) (f(xres.c) + bfr(((f(u[0].c) + f(u[1].c)) + (f(u[2].c) + f(u[3].c))) + (f(u[4].c) + f(u[5].c))))
            const uint32_t hp0 = pack_bf(F_(bf_hi, x), F_(bf_lo, x)), hp1 = pack_bf(F_(bf_hi, y), F_(bf_lo, y));
#undef F_
            sts64(hdst, hp0, hp1);
            asm volatile("bar.arrive 9, 416;" ::: "memory");
            asm volatile("bar.arrive 11, 192;" ::: "memory");
            if (lane == 0) LST(100);
        }
    } else {
        const int t = lane & 3, g = lane >> 2;
        const int arow = (lane & 7) + ((lane >> 4) << 3), ahalf = (lane >> 3) & 1;
        uint32_t epoch0;
        const char* xb = reinterpret_cast<const char*>(p.x);
        asm volatile("ld.relaxed.gpu.global.u32 %0, [%1];" : "=r"(epoch0) : "l"(&p.sc->epoch) : "memory");
        uint64_t* q1dst = p.sc->q1 + ((head * 4 + (warp & 3)) * 4 + sp) * 48 + min(t, 2) * 16 + g;
        uint4* q2dst = p.sc->q2 + (head * 8 + sp * 2 + lane / 12) * 4 + t;
        if (warp == 7) {
            uint2 xu[5];
#pragma unroll
            for (int i = 0; i < 5; i++) asm volatile("ld.global.nc.v2.u32 {%0, %1}, [%2];" : "=r"(xu[i].x), "=r"(xu[i].y) : "l"(xb + i * 256 + lane * 8));
            float mean_b, inv_den;
            ln_stats(xu, mean_b, inv_den);
#define N_(v) (bfr((v) - mean_b) * inv_den)
#pragma unroll
            for (int i = 0; i < 5; i++)
                sts64(sbase + SM_HN + i * 256 + lane * 8, pack_bf(N_(bf_hi(xu[i].x)), N_(bf_lo(xu[i].x))), pack_bf(N_(bf_hi(xu[i].y)), N_(bf_lo(xu[i].y))));
#undef N_
        } else {
            if (warp < 4 && t < 3) { ll_st1(q1dst, 0.f, 0); ll_st1(q1dst + 8, 0.f, 0); }
            if (warp == 4 && lane < 24 && lane % 12 < 4) pkt_st(q2dst, 0, 0, 0, 0);
        }
        asm volatile("cp.async.wait_all;" ::: "memory");
        if (lane == 0) LST(80 + warp);
        asm volatile("bar.sync 2, 288;" ::: "memory");
        const uint32_t tag = epoch0 + 1;
        auto block = [&](int i) { const int unit = arow * 3 + (i >> 2); return sbase + SM_RING + unit * 128 + ((((i & 3) * 2 + ahalf) ^ (unit & 7)) << 4); };

        if (warp < 4) {
            {
                float c[3][4];
                uint32_t wa[3];
#pragma unroll
                for (int k = 0; k < 3; k++) { c[k][0] = c[k][1] = c[k][2] = c[k][3] = 0.f; wa[k] = block(warp * 3 + k) + QSLOT * TILE_BYTES; }
                const uint32_t xa = sbase + SM_HN + sp * 320 + t * 4;
#pragma unroll 2
                for (int ks = 0; ks < 2 * NQT; ks++) {
                    const uint32_t b0 = lds32(xa + ks * 32), b1 = lds32(xa + ks * 32 + 16);
#pragma unroll
                    for (int k = 0; k < 3; k++) { uint32_t a[4]; ldsm_x4_t(a, wa[k] + ks * (TILE_BYTES / 2)); mma_bf16(c[k], a, b0, b1); }
                }
                if (t < 3) {
                    ll_st1(q1dst, t == 0 ? c[0][0] : t == 1 ? c[1][0] : c[2][0], tag);
                    ll_st1(q1dst + 8, t == 0 ? c[0][2] : t == 1 ? c[1][2] : c[2][2], tag);
                }
                asm volatile("bar.sync 6, 128;" ::: "memory");
                if (tid < NQT) mbar_arrive(bar_empty + 8 * (QSLOT + tid));
                if (tid == 0) LST(90);
            }
            const uint32_t ta[3] = {block(0), block(4), block(8)};
            mbar_wait(bar_q, 0);
            if (tid == 0) LST(92);
#pragma unroll 1
            for (int h = warp; h < NHEAD; h += 4) {
                const int slot = (2 * h) & (NSLOT - 1);
                const uint32_t par = (h >> 3) & 1;
                if (h >= NHEAD - cfg::PREPART) mbar_wait(bar_set, 0);
                uint32_t qf[24];
#pragma unroll
                for (int i = 0; i < 6; i++) { const uint4 v = lds128(sbase + SM_Q + h * ROW_BYTES + t * 96 + i * 16); qf[4 * i] = v.x; qf[4 * i + 1] = v.y; qf[4 * i + 2] = v.z; qf[4 * i + 3] = v.w; }
                uint32_t ad[12];
#pragma unroll
                for (int i = 0; i < 12; i++) ad[i] = (ta[i >> 2] + slot * TILE_BYTES) ^ ((i & 3) << 5);
                float sc[4][4];
#pragma unroll
                for (int j = 0; j < 4; j++) sc[j][0] = sc[j][1] = sc[j][2] = sc[j][3] = 0.f;
                mbar_wait(bar_full + 8 * slot, par);
#pragma unroll
                for (int i = 0; i < 12; i++) {
                    const uint32_t a[4] = {qf[2 * i], qf[2 * i], qf[2 * i + 1], qf[2 * i + 1]};
                    uint32_t k0[4], k1[4];
                    ldsm_x4(k0, ad[i]); ldsm_x4(k1, ad[i] + TILE_BYTES / 2);
                    mma_bf16(sc[0], a, k0[0], k0[1]); mma_bf16(sc[1], a, k0[2], k0[3]);
                    mma_bf16(sc[2], a, k1[0], k1[1]); mma_bf16(sc[3], a, k1[2], k1[3]);
                }
                const float scale = 0.07216878364870322f;
                float m = -INFINITY;
#pragma unroll
                for (int j = 0; j < 4; j++) { sc[j][0] = bfr(bfr(sc[j][0]) * scale); sc[j][1] = bfr(bfr(sc[j][1]) * scale); m = fmaxf(m, fmaxf(sc[j][0], sc[j][1])); }
                if (lane == 0) mbar_arrive(after(p.zero, bar_empty + 8 * slot, m));
                m = fmaxf(m, __shfl_xor_sync(0xffffffffu, m, 1));
                m = fmaxf(m, __shfl_xor_sync(0xffffffffu, m, 2));
                float l = 0.f;
                uint32_t pf[4];
#pragma unroll
                for (int j = 0; j < 4; j++) {
                    const float p0 = ex2((sc[j][0] - m) * L2E), p1 = ex2((sc[j][1] - m) * L2E);
                    l += p0 + p1;
                    const uint32_t hi = pack_bf(p1, p0);
                    pf[j] = (g & 1) ? pack_bf(p1 - bf_hi(hi), p0 - bf_lo(hi)) : hi;
                }
                l += __shfl_xor_sync(0xffffffffu, l, 1);
                l += __shfl_xor_sync(0xffffffffu, l, 2);
                const uint32_t meta = (__float_as_uint(m) & 0xffff0000u) | ((__float_as_uint(l) - 0x3f800000u + 0x800u) >> 10 & 0xfffcu) | (tag & 3);
                uint32_t pq[4][4];
#pragma unroll
                for (int q = 0; q < 4; q++)
#pragma unroll
                    for (int j = 0; j < 4; j++) pq[q][j] = (g >> 1) == q ? pf[j] : 0;
                float o[6][4];
#pragma unroll
                for (int k = 0; k < 6; k++) o[k][0] = o[k][1] = o[k][2] = o[k][3] = 0.f;
                uint4* dst = p.sc->part + ((h * 4 + t) * NCTA + b) * 8 + g;
                mbar_wait(after(p.zero, bar_full + 8 * slot + 8, meta, dst, pq[0][0], pq[1][1], pq[2][2], pq[3][3]), par);
#pragma unroll
                for (int i = 0; i < 12; i++) {
                    uint32_t v0[4], v1[4];
                    ldsm_x4_t(v0, ad[i] + TILE_BYTES); ldsm_x4_t(v1, ad[i] + TILE_BYTES + TILE_BYTES / 2);
                    mma_bf16(o[i % 3], v0, pq[i / 3][0], pq[i / 3][1]);
                    mma_bf16(o[3 + i % 3], v1, pq[i / 3][2], pq[i / 3][3]);
                }
                uint32_t w[3];
#pragma unroll
                for (int k = 0; k < 3; k++) w[k] = pack_bf((o[k][2] + o[k][3]) + (o[k + 3][2] + o[k + 3][3]), (o[k][0] + o[k][1]) + (o[k + 3][0] + o[k + 3][1]));
                pkt_st(dst, w[0], w[1], w[2], meta);
                if (lane == 0) {
                    mbar_arrive(after(p.zero, bar_empty + 8 * slot + 8, w[0], w[1], w[2]));
                    if (h == head) mbar_arrive(bar_part);
                }
            }
            if (tid == 96) LST(91);
        } else {
            const int u = tid - 128;
            uint32_t n = 0;
            if (warp == 4) {
                const uint4* src = reinterpret_cast<const uint4*>(p.sc->q1 + (head * 4 + sp) * 4 * 48) + min(lane, 23);
                uint4 v[4];
                sleep_until(now_q() + 4 * cfg::QDELAY);
#pragma unroll 1
                do {
                    if (n) __nanosleep(cfg::QSLEEP);
#pragma unroll
                    for (int i = 0; i < 4; i++) v[i] = ll_ld2(src + i * 24);
                    if (++n > SPIN_LIMIT) __trap();
                } while (__any_sync(0xffffffffu, ((v[0].y ^ tag) | (v[0].w ^ tag) | (v[1].y ^ tag) | (v[1].w ^ tag) | (v[2].y ^ tag) | (v[2].w ^ tag) | (v[3].y ^ tag) | (v[3].w ^ tag)) != 0));
#define F_(c) ((__uint_as_float(v[0].c) + __uint_as_float(v[1].c)) + (__uint_as_float(v[2].c) + __uint_as_float(v[3].c)))
                const uint32_t w0 = pack_bf(F_(z), F_(x));
#undef F_
                const uint32_t w1 = __shfl_down_sync(0xffffffffu, w0, 4), w2 = __shfl_down_sync(0xffffffffu, w0, 8);
                if (lane < 24 && lane % 12 < 4) pkt_st(q2dst, w0, w1, w2, tag);
            }
            asm volatile("bar.sync 7, 128;" ::: "memory");
            uint4 v[8];
            {
#pragma unroll
                for (int i = 0; i < 8; i++) v[i] = make_uint4(0, 0, 0, ~tag);
                sleep_until(now_q() + 4 * cfg::QDELAY2);
                n = 0;
                bool ok;
#pragma unroll 1
                do {
                    if (n) __nanosleep(cfg::QSLEEP);
#pragma unroll
                    for (int i = 0; i < 8; i++) pkt_ldp(p.sc->q2 + u + i * 128, v[i], v[i].w != tag);
                    ok = true;
#pragma unroll
                    for (int i = 0; i < 8; i++) ok &= v[i].w == tag;
                    if (++n > SPIN_LIMIT) __trap();
                } while (!__all_sync(0xffffffffu, ok));
                const uint32_t qd = sbase + SM_Q + (u >> 5) * ROW_BYTES + t * 96 + g * 12;
#pragma unroll
                for (int i = 0; i < 8; i++) {
                    sts32(qd + i * 4 * ROW_BYTES, __uint_as_float(v[i].x)); sts32(qd + i * 4 * ROW_BYTES + 4, __uint_as_float(v[i].y)); sts32(qd + i * 4 * ROW_BYTES + 8, __uint_as_float(v[i].z));
                }
                __syncwarp();
                if (lane == 0) mbar_arrive(bar_q);
            }
            {
                const uint4* src = p.sc->part + b * NCTA * 8 + u;
                const uint32_t rdst = sbase + SM_RED + (warp - 4) * 256 + min(lane >> 3, 2) * 64 + (lane & 7) * 4;
                const uint32_t lo = o_off(b * 48 + (min(lane, 23) >> 3) * 16) + (lane & 3) * 8 + (lane & 4);
                unsigned char *od0 = p.xa + xa_off(lo, 0), *od1 = p.xa + xa_off(lo, 1);
#pragma unroll
                for (int i = 0; i < 8; i++) v[i].w = ~tag;
                mbar_wait(bar_set, 0);
                mbar_wait(after(p.zero, bar_part, src, rdst, od0, od1), 0);
                {
                    const uint32_t at = now_q() + 4 * min(cfg::PDELAY, cfg::PDELAY_LAST + (NHEAD - 1 - head) * cfg::PDELAY_STEP);
                    sleep_until(at - 4 * 300);
                    wait_until(at);
                }
                n = 0;
                uint32_t bad;
#pragma unroll 1
                do {
                    if (n && head != NHEAD - 1) __nanosleep(cfg::QSLEEP);
#pragma unroll
                    for (int i = 0; i < 8; i++) pkt_ldp(src + i * 128, v[i], ((v[i].w ^ tag) & 3) != 0);
                    bad = 0;
#pragma unroll
                    for (int i = 0; i < 8; i++) bad |= v[i].w ^ tag;
                    if (++n > SPIN_LIMIT) __trap();
                } while (__any_sync(0xffffffffu, (bad & 3) != 0));
                if (u == 0) LST(119);
                float m = -INFINITY;
#pragma unroll
                for (int i = 0; i < 8; i++) m = fmaxf(m, bf_hi(v[i].w));
                m = fmaxf(m, __shfl_xor_sync(0xffffffffu, m, 8));
                m = fmaxf(m, __shfl_xor_sync(0xffffffffu, m, 16));
                float a[7] = {0.f, 0.f, 0.f, 0.f, 0.f, 0.f, 0.f};
#pragma unroll
                for (int i = 0; i < 8; i++) {
                    const float f = ex2((bf_hi(v[i].w) - m) * L2E);
                    a[0] = fmaf(f, bf_lo(v[i].x), a[0]); a[1] = fmaf(f, bf_hi(v[i].x), a[1]);
                    a[2] = fmaf(f, bf_lo(v[i].y), a[2]); a[3] = fmaf(f, bf_hi(v[i].y), a[3]);
                    a[4] = fmaf(f, bf_lo(v[i].z), a[4]); a[5] = fmaf(f, bf_hi(v[i].z), a[5]);
                    a[6] = fmaf(f, __uint_as_float(((v[i].w & 0xfffcu) << 10) + 0x3f800000u), a[6]);
                }
#pragma unroll
                for (int o = 8; o < 32; o <<= 1)
#pragma unroll
                    for (int i = 0; i < 7; i++) a[i] += __shfl_xor_sync(0xffffffffu, a[i], o);
                if (lane < 24) { sts32(rdst, lane < 8 ? a[0] : lane < 16 ? a[2] : a[4]); sts32(rdst + 32, lane < 8 ? a[1] : lane < 16 ? a[3] : a[5]); }
                if (lane == 24) sts64(rdst + 64, __float_as_uint(a[6]), __float_as_uint(m));
                asm volatile("bar.sync 7, 128;" ::: "memory");
                if (warp == 4) {
                    float2 st[4], r[4];
#pragma unroll
                    for (int i = 0; i < 4; i++) { st[i] = lds64f(sbase + SM_RED + i * 256 + 192); r[i] = lds64f(sbase + SM_RED + i * 256 + lane * 8); }
                    const float mm = fmaxf(fmaxf(st[0].y, st[1].y), fmaxf(st[2].y, st[3].y));
                    float den = 0.f, x0 = 0.f, x1 = 0.f;
#pragma unroll
                    for (int i = 0; i < 4; i++) { const float f = ex2((st[i].y - mm) * L2E); den = fmaf(f, st[i].x, den); x0 = fmaf(f, r[i].x, x0); x1 = fmaf(f, r[i].y, x1); }
                    const float inv = rcp_fast(den);
                    const float ow = __uint_as_float(pack_bf(x1 * inv, x0 * inv));
                    if (lane < 24) { in_st1(od0, ow); in_st1(od1, ow); }
                    if (lane == 0) LST(120);
                }
            }
        }
        mbar_wait(bar_pace, 0);
        const uint32_t msel = s_pace[2];
        cons_sync();
        if (is_wo) {
            uint32_t wa = sbase + (warp * 16 + arow) * 128 + ((ahalf ^ (lane & 7)) << 4);
            uint32_t pw = sbase + SM_RED + (warp * 64 + t * 16 + (lane >> 2)) * 4, pr = sbase + SM_RED + lane * 8;
            unsigned char* gdst = p.xa + xa_off(L_GATHER + (warp >> 1) % cfg::HCOPY * HCOPY_BYTES + (kg * D_MODEL + ng * 64 + lane * 2) * 2, warp & 1);
            const unsigned char* osrc = p.xa + xa_off(L_O + kg * 2048, msel) + warp * 32 + t * 8;
            uint2 ov[NWP];
#pragma unroll
            for (int j = 0; j < NWP; j++) ov[j] = make_uint2(SENT, SENT);
            auto gather = [&](int j0, int j1) {
                uint32_t n = 0;
#pragma unroll 1
                while (true) {
                    uint32_t mx = 0;
#pragma unroll
                    for (int j = j0; j < j1; j++) mx = max(mx, max(ov[j].x, ov[j].y));
                    if (!__any_sync(0xffffffffu, mx == SENT)) break;
#pragma unroll
                    for (int j = j0; j < j1; j++) in_ld2p(osrc + j * 256, ov[j], !in_ok(ov[j]));
                    if (++n > SPIN_LIMIT) __trap();
                }
            };
            float cw[4][4];
#pragma unroll
            for (int i = 0; i < 4; i++) cw[i][0] = cw[i][1] = cw[i][2] = cw[i][3] = 0.f;
            mbar_wait(after(p.zero, bar_tail + 8, osrc, wa, pw, pr, gdst), 0);
#pragma unroll
            for (int j = 0; j < NWP; j++) in_ld2p(osrc + j * 256, ov[j], true);
            gather(0, NWP - 1);
#pragma unroll
            for (int j = 0; j < NWP; j++) {
                if (j == NWP - 1) { gather(NWP - 1, NWP); if (tid == 224) LST(93); }
                mbar_wait(bar_tail + 8 * j, 0);
                if (j == NWP - 3) in_ld2p(osrc + (NWP - 1) * 256, ov[NWP - 1], !in_ok(ov[NWP - 1]));
                uint32_t a[4][4];
#pragma unroll
                for (int i = 0; i < 4; i++) ldsm_x4_t(a[i], (wa ^ (i << 5)) + j * WPIECE);
#pragma unroll
                for (int i = 0; i < 4; i++) mma_bf16(cw[i], a[i], ov[j].x, ov[j].y);
            }
#define SEL_(e) ((t & 2) ? ((t & 1) ? cw[3][e] : cw[2][e]) : ((t & 1) ? cw[1][e] : cw[0][e]))
            sts32(pw, SEL_(0)); sts32(pw + 32, SEL_(2));
#undef SEL_
            cons_sync();
            if (warp < 2 * cfg::HCOPY) {
                float2 r[8];
#pragma unroll
                for (int i = 0; i < 8; i++) r[i] = lds64f(pr + i * 256);
#define S_(c) (((r[0].c + r[1].c) + (r[2].c + r[3].c)) + ((r[4].c + r[5].c) + (r[6].c + r[7].c)))
                in_st1(gdst, __uint_as_float(pack_bf(S_(y), S_(x))));
#undef S_
            }
            if (tid == 0) LST(94);
        } else if (is_ffn) {
            uint32_t w13a = sbase + (warp * 16 + arow) * 64 + ((ahalf ^ (lane >> 1 & 3)) << 4);
            uint32_t red_dst = sbase + SM_RED + tid * 8;
            const uint32_t ha = sbase + SM_HN + warp * 32 + t * 8;
            uint32_t aw[NUP][4][4];
            auto load_w13 = [&](int i) {
                mbar_wait(i ? bar_tail + 8 * i : after(p.zero, bar_tail, w13a, red_dst, ha), 0);
#pragma unroll
                for (int k = 0; k < 4; k++) ldsm_x4_t(aw[i][k], (w13a ^ (k << 5 & 32)) + i * WPIECE + (k >> 1) * (WPIECE / 2));
            };
            {
                uint32_t b0[NUP], b1[NUP];
                float cf[4][4];
#pragma unroll
                for (int e = 0; e < 4; e++) cf[0][e] = cf[1][e] = cf[2][e] = cf[3][e] = 0.f;
                auto mma_w13 = [&](int i) {
#pragma unroll
                    for (int k = 0; k < 4; k++) mma_bf16(cf[k], aw[i][k], b0[i], b1[i]);
                };
#pragma unroll
                for (int i = 0; i < cfg::HPRE; i++) load_w13(i);
                LSC(0);
                asm volatile("bar.sync 9, 416;" ::: "memory");
#pragma unroll
                for (int i = 0; i < NUP; i++) {
                    b0[i] = b1[i] = 0x3f803f80u;
                    asm volatile("{\n.reg .pred q;\nsetp.eq.u32 q, %3, 0;\n@q ld.shared.v2.u32 {%0, %1}, [%2];\n}" : "+r"(b0[i]), "+r"(b1[i]) : "r"(ha + i * 256), "r"(lane & 4) : "memory");
                }
#pragma unroll
                for (int i = 0; i < cfg::HPRE; i++) mma_w13(i);
                LSC(3);
#pragma unroll
                for (int i = cfg::HPRE; i < NUP - 1; i++) { load_w13(i); mma_w13(i); }
                LSC(4);
#define SEL_(k, e) ((t & 2) ? ((t & 1) ? cf[k + 1][e + 2] : cf[k + 1][e]) : ((t & 1) ? cf[k][e + 2] : cf[k][e]))
#pragma unroll
                for (int m = 0; m < 2; m++) {
                    mbar_wait(bar_tail + 8 * (NUP - 1 + m), 0);
#pragma unroll
                    for (int k = 2 * m; k < 2 * m + 2; k++) ldsm_x4_t(aw[NUP - 1][k], (w13a ^ (k << 5 & 32)) + (NUP - 1) * WPIECE + m * (WPIECE / 2));
#pragma unroll
                    for (int k = 2 * m; k < 2 * m + 2; k++) mma_bf16(cf[k], aw[NUP - 1][k], b0[NUP - 1], b1[NUP - 1]);
                    sts64(red_dst + m * 2048, __float_as_uint(SEL_(2 * m, 0)), __float_as_uint(SEL_(2 * m, 1)));
                    if (m == 0) asm volatile("bar.arrive 8, 288;" ::: "memory");
                }
                LSC(6);
#undef SEL_
            }
            LSC(7);
            asm volatile("bar.arrive 5, 288;" ::: "memory");
        }
        if (is_out) {
            uint32_t w2a = sbase + SM_W2 + (warp * 32 + arow) * 32 + ((ahalf ^ (lane >> 2 & 1)) << 4);
            uint32_t ydst = sbase + SM_HN + ((t & 1) * 8 + (lane >> 2)) * 48 + warp * 4;
            const unsigned char* asrc = p.xa + xa_off(L_ACT, msel) + oh * (NDP * 512) + warp * 64 + t * 16;
            uint32_t a[NDP][2][4];
            auto load_w2 = [&](int i) {
                mbar_wait(i ? bar_tail + 8 * (NWP + i) : after(p.zero, bar_tail + 8 * NWP, w2a, ydst, asrc), 0);
                ldsm_x4_t(a[i][0], w2a + i * PIECE); ldsm_x4_t(a[i][1], w2a + i * PIECE + 512);
            };
#pragma unroll
            for (int i = 0; i < cfg::AGATE; i++) load_w2(i);
            uint4 u[NDP];
            LSC(0);
#pragma unroll
            for (int i = 0; i < NDP; i++) u[i] = in_ld4(asrc + i * 512);
            uint32_t n = 0;
#pragma unroll 1
            while (true) {
                uint32_t m[NDP];
#pragma unroll
                for (int i = 0; i < NDP; i++) m[i] = max(max(u[i].x, u[i].y), max(u[i].z, u[i].w));
                if (!__any_sync(0xffffffffu, max(max(m[0], m[1]), m[2]) == SENT)) break;
#pragma unroll
                for (int i = 0; i < NDP; i++) in_ld4p(asrc + i * 512, u[i], m[i] == SENT);
                if (++n > SPIN_LIMIT) __trap();
            }
            LSC(12);
            if (tid == 96) LST(118);
            float cy[2 * NDP][4];
#pragma unroll
            for (int i = 0; i < NDP; i++) {
#pragma unroll
                for (int e = 0; e < 4; e++) cy[2 * i][e] = cy[2 * i + 1][e] = 0.f;
                if (i >= cfg::AGATE) load_w2(i);
                mma_bf16(cy[2 * i], a[i][0], u[i].x, u[i].y);
                mma_bf16(cy[2 * i + 1], a[i][1], u[i].z, u[i].w);
            }
#define Y_(e) (((cy[0][e] + cy[1][e]) + (cy[2][e] + cy[3][e])) + (cy[4][e] + cy[5][e]))
            const float y = (t & 1) ? Y_(2) : Y_(0);
#undef Y_
            if (t < 2) sts32(ydst, y);
            LSC(13);
            asm volatile("bar.arrive 5, 288;" ::: "memory");
        }
    }
}

typedef CUresult (*EncodeTiledFn)(CUtensorMap*, CUtensorMapDataType, cuuint32_t, void*, const cuuint64_t*, const cuuint64_t*,
                                  const cuuint32_t*, const cuuint32_t*, CUtensorMapInterleave, CUtensorMapSwizzle,
                                  CUtensorMapL2promotion, CUtensorMapFloatOOBfill);

void make_map(EncodeTiledFn fn, CUtensorMap* tm, const void* w, const int (&d)[5], const int (&st)[4], const int (&bx)[5],
              CUtensorMapSwizzle sw, int promo) {
    cuuint64_t dims[5], strides[4];
    cuuint32_t box[5], estr[5];
    for (int i = 0; i < 5; i++) { dims[i] = (cuuint64_t)d[i]; box[i] = (cuuint32_t)bx[i]; estr[i] = 1; }
    for (int i = 0; i < 4; i++) strides[i] = (cuuint64_t)st[i];
    fn(tm, CU_TENSOR_MAP_DATA_TYPE_BFLOAT16, 5, const_cast<void*>(w), dims, strides, box, estr, CU_TENSOR_MAP_INTERLEAVE_NONE, sw,
       (CUtensorMapL2promotion)promo, CU_TENSOR_MAP_FLOAT_OOB_FILL_NONE);
}

}

extern "C" void kernel_launch(void* const* d_in, const int* in_sizes, int n_in, void* d_out, int out_size) {
    (void)in_sizes; (void)n_in; (void)out_size;
    static EncodeTiledFn encode = nullptr;
    static Scratch* scratch = nullptr;
    static unsigned char* xarea = nullptr;
    static double tscale = 1.0;
    if (!encode) {
        void* sp = nullptr;
        cudaGetSymbolAddress(&sp, g_scratch);
        scratch = reinterpret_cast<Scratch*>(sp);
        cudaGetSymbolAddress(&sp, g_xarea);
        xarea = reinterpret_cast<unsigned char*>((reinterpret_cast<uintptr_t>(sp) + XA_ALIGN - 1) / XA_ALIGN * XA_ALIGN);
        void* fn = nullptr;
        cudaDriverEntryPointQueryResult st;
        cudaGetDriverEntryPoint("cuTensorMapEncodeTiled", &fn, cudaEnableDefault, &st);
        encode = reinterpret_cast<EncodeTiledFn>(fn);
        int dev = 0, khz = 0, bits = 0;
        cudaGetDevice(&dev);
        cudaDeviceGetAttribute(&khz, cudaDevAttrMemoryClockRate, dev);
        cudaDeviceGetAttribute(&bits, cudaDevAttrGlobalMemoryBusWidth, dev);
        if (khz > 0 && bits > 0) tscale = (2619000.0 * 5120.0) / ((double)khz * bits);
        cudaFuncSetAttribute(fused_decode_kernel, cudaFuncAttributeMaxDynamicSharedMemorySize, SM_TOTAL);
    }
    KParams p;
    p.x = (const __nv_bfloat16*)d_in[0];
    p.wq = (const __nv_bfloat16*)d_in[3];
    p.out = (__nv_bfloat16*)d_out;
    p.sc = scratch;
    p.xa = xarea;
    p.zero = 0;
    p.t_first = (uint32_t)(4 * cfg::T_FIRST * tscale);
    p.t_step = (uint32_t)(cfg::T_STEP * tscale);
    p.t_smax = (uint32_t)(cfg::T_SMAX * tscale);
    p.t_lat = (uint32_t)(4 * (450 + (cfg::T_LAT - 450) * tscale));
    TMaps tm;
    constexpr int R1 = FF * 2, R2 = D_MODEL * 2;
    make_map(encode, &tm.k, d_in[1], {64, NHEAD * SK * 3, 1, 1, 1}, {128, 128, 128, 128}, {64, 96, 1, 1, 1}, CU_TENSOR_MAP_SWIZZLE_128B, cfg::PROMO_KV);
    make_map(encode, &tm.v, d_in[2], {64, NHEAD * SK * 3, 1, 1, 1}, {128, 128, 128, 128}, {64, 96, 1, 1, 1}, CU_TENSOR_MAP_SWIZZLE_128B, cfg::PROMO_KV);
    make_map(encode, &tm.wo, d_in[4], {D_MODEL, NHEAD * DH, 1, 1, 1}, {R2, R2, R2, R2}, {64, 128, 1, 1, 1}, CU_TENSOR_MAP_SWIZZLE_128B, cfg::PROMO_WO);
    make_map(encode, &tm.w1, d_in[6], {FF, 2, 4, 2, 40}, {R1, 4 * R1, 2 * R1, 16 * R1}, {32, 2, 4, 2, 8}, CU_TENSOR_MAP_SWIZZLE_64B, cfg::PROMO_W13);
    make_map(encode, &tm.w3, d_in[7], {FF, 2, 4, 2, 40}, {R1, 4 * R1, 2 * R1, 16 * R1}, {32, 2, 4, 2, 8}, CU_TENSOR_MAP_SWIZZLE_64B, cfg::PROMO_W13);
    make_map(encode, &tm.w2, d_in[8], {D_MODEL, FF, 1, 1, 1}, {R2, R2, R2, R2}, {16, 256, 1, 1, 1}, CU_TENSOR_MAP_SWIZZLE_32B, cfg::PROMO_W2);
    fused_decode_kernel<<<NCTA, NTHREADS, SM_TOTAL, cudaStreamPerThread>>>(p, tm);
}
```

```cpp
#include <cuda_runtime.h>
#include <cuda_bf16.h>
#include <cuda.h>
#include <stdint.h>
#include <math.h>

namespace {

constexpr int D_MODEL = 640;
constexpr int NHEAD = 32;
constexpr int DH = 192;
constexpr int SK = 32768;
constexpr int WIN = 4096;
constexpr int FF = 1536;

constexpr int NCTA = 128;
constexpr int NCONS = 256;
constexpr int NTHREADS = NCONS + 256;
constexpr int ROW_BYTES = DH * 2;
constexpr int TILE_BYTES = 32 * ROW_BYTES;
constexpr int NSLOT = 16;
constexpr int NQT = 5;
constexpr int QSLOT = NSLOT - NQT;
constexpr int NWO = 60;
constexpr int NG = 6;
constexpr int NFFN = 48;
constexpr int NWP = 8;
constexpr int NUP = 5;
constexpr int WPIECE = 16384;
constexpr int NDP = 3;
constexpr int PIECE = 8192;
constexpr int NTAIL = NWP + NDP;
constexpr int N_TAIL0 = 2 * NHEAD;

#define CFG(name, value) constexpr int name = value
#define CFG_OVERRIDE
namespace cfg_default {
CFG(T_FIRST, 1850);
CFG(T_STEP, 1906);
CFG(T_SMAX, 1940);
CFG(CAP, 5);
CFG(MN, 12);
CFG(MA, 4);
CFG(MB, 40);
CFG(ADAPT, 60);
CFG(T_LAT, 1240);
CFG(T_WO, 296);
CFG(T_GAP, 115);
CFG(T_UP, 234);
CFG(T_UP2, 140);
CFG(T_W2AT, 1330);
CFG(T_W2, 200);
CFG(T_HAT, 1130);
CFG(T_RESAT, 1750);
CFG(T_AAT, 2440);
CFG(KEEP_AT, 65);
CFG(KEEP, 150);
CFG(HCOPY, 1);
CFG(QDELAY, 1200);
CFG(QDELAY2, 900);
CFG(QSLEEP, 400);
CFG(PDELAY, 2500);
CFG(PDELAY_LAST, 250);
CFG(PDELAY_STEP, 650);
CFG(PREPART, 3);
CFG(RBDELAY, 5000);
CFG(NPROBE, 10);
CFG(VOTES, 3);
CFG(PROMO_KV, 2);
CFG(PROMO_WO, 2);
CFG(PROMO_W13, 2);
CFG(PROMO_W2, 2);
CFG(BOUNDED_MBAR, 0);
}
namespace cfg { using namespace cfg_default; CFG_OVERRIDE }

constexpr int SM_RING = 0;
constexpr int SM_W2 = NWP * WPIECE;
constexpr int SM_Q = SM_RING + NSLOT * TILE_BYTES;
constexpr int SM_RED = SM_Q + NHEAD * ROW_BYTES;
constexpr int SM_HN = SM_RED + 4096;
constexpr int SM_STAT = SM_HN + D_MODEL * 2;
constexpr int SM_MISC = SM_STAT + 256;
constexpr int SM_BAR = SM_MISC + 128;
constexpr int SM_TOTAL = SM_BAR + 512;
static_assert(SM_TOTAL <= 232448, "shared memory");

struct __align__(128) Scratch {
    uint4 part[NHEAD * 4 * NCTA * 8];
    uint64_t q1[NHEAD * 4 * DH];
    uint4 q2[NHEAD * 32];
    uint32_t epoch;
    uint32_t pad;
    unsigned long long pace[2];
};
__device__ Scratch g_scratch;
constexpr int XA_ALIGN = 1 << 20;
constexpr uint32_t SENT = 0xffffffffu;
constexpr int L_GATHER = 0;
constexpr int HCOPY_BYTES = NG * D_MODEL * 2;
constexpr int L_O = 9 * 4096;
constexpr int L_ACT = 30 * 4096;
constexpr int L_PROBE = 32 * 4096;
static_assert(2 * (L_PROBE + NCTA * 1024) <= XA_ALIGN, "");
__device__ unsigned char g_xarea[2 * XA_ALIGN];
__device__ __forceinline__ uint32_t xa_off(uint32_t l, uint32_t side) {
    const uint32_t k = l >> 12;
    return (2 * k + ((side ^ k ^ (k >> 3) ^ (k >> 4) ^ (k >> 6)) & 1)) * 4096 + (l & 4095);
}

__device__ __forceinline__ uint32_t o_off(uint32_t r) { return L_O + (r >> 7) % NG * 2048 + (r >> 7) / NG * 256 + (r & 127) * 2; }

#define LST(i) do { } while (0)
#define LSC(i) do { } while (0)
#define LSCD(i, v) do { } while (0)
constexpr uint32_t SPIN_LIMIT = cfg::BOUNDED_MBAR ? 1u << 14 : 1u << 22;

__device__ __forceinline__ uint32_t now_q() { uint32_t t; asm volatile("mov.u32 %0, %globaltimer_lo;" : "=r"(t)); return t * 4; }
__device__ __forceinline__ void wait_until(uint32_t due) {
#pragma unroll 1
    for (int n = 0; n < 4096 && (int)(now_q() - due) < 0; n++) { }
}
__device__ __forceinline__ void sleep_until(uint32_t due) {
#pragma unroll 1
    for (int n = 0; n < 4096 && (int)(now_q() - due) < 0; n++) __nanosleep(200);
}
__device__ __forceinline__ uint32_t smem_u32(const void* p) { return (uint32_t)__cvta_generic_to_shared(p); }
__device__ __forceinline__ void mbar_init(uint32_t bar, uint32_t cnt) {
    asm volatile("mbarrier.init.shared::cta.b64 [%0], %1;" ::"r"(bar), "r"(cnt) : "memory");
}
__device__ __forceinline__ void mbar_expect_tx(uint32_t bar, uint32_t bytes) {
    asm volatile("mbarrier.arrive.expect_tx.shared::cta.b64 _, [%0], %1;" ::"r"(bar), "r"(bytes) : "memory");
}
__device__ __forceinline__ void mbar_arrive(uint32_t bar) {
    asm volatile("mbarrier.arrive.shared::cta.b64 _, [%0];" ::"r"(bar) : "memory");
}
__device__ __forceinline__ bool mbar_test(uint32_t bar, uint32_t parity) {
    uint32_t ok;
    asm volatile("{\n.reg .pred p;\nmbarrier.test_wait.parity.shared::cta.b64 p, [%1], %2;\nselp.u32 %0, 1, 0, p;\n}"
                 : "=r"(ok) : "r"(bar), "r"(parity) : "memory");
    return ok;
}
__device__ __forceinline__ bool mbar_try(uint32_t bar, uint32_t parity) {
    uint32_t ok;
    asm volatile("{\n.reg .pred p;\nmbarrier.try_wait.parity.shared::cta.b64 p, [%1], %2;\nselp.u32 %0, 1, 0, p;\n}"
                 : "=r"(ok) : "r"(bar), "r"(parity) : "memory");
    return ok;
}
__device__ __forceinline__ void mbar_wait(uint32_t bar, uint32_t parity) {
    if (cfg::BOUNDED_MBAR) {
        uint32_t n = 0;
        while (!mbar_try(bar, parity)) if (++n > SPIN_LIMIT) __trap();
    } else {
        asm volatile("{\n.reg .pred p;\nW_%=:\nmbarrier.try_wait.parity.shared::cta.b64 p, [%0], %1;\n@!p bra W_%=;\n}" ::"r"(bar), "r"(parity) : "memory");
    }
}
__device__ __forceinline__ void tma_tile(uint32_t dst, const CUtensorMap* tm, int c1, uint32_t bar, uint64_t pol) {
    asm volatile("cp.async.bulk.tensor.5d.shared::cluster.global.mbarrier::complete_tx::bytes.L2::cache_hint [%0], [%1, {%4, %3, %4, %4, %4}], [%2], %5;"
                 ::"r"(dst), "l"(reinterpret_cast<uint64_t>(tm)), "r"(bar), "r"(c1), "r"(0), "l"(pol) : "memory");
}
__device__ __forceinline__ void tma_5d(uint32_t dst, const CUtensorMap* tm, int c0, int c1, int c2, int c4, uint32_t bar) {
    asm volatile("cp.async.bulk.tensor.5d.shared::cluster.global.mbarrier::complete_tx::bytes [%0], [%1, {%3, %4, %5, %7, %6}], [%2];"
                 ::"r"(dst), "l"(reinterpret_cast<uint64_t>(tm)), "r"(bar), "r"(c0), "r"(c1), "r"(c2), "r"(c4), "r"(0) : "memory");
}
__device__ __forceinline__ uint32_t bits(uint32_t v) { return v; }
__device__ __forceinline__ uint32_t bits(float v) { return __float_as_uint(v); }
__device__ __forceinline__ uint32_t bits(const void* v) { return (uint32_t)(uintptr_t)v ^ (uint32_t)((uintptr_t)v >> 32); }
template <class... T> __device__ __forceinline__ uint32_t after(uint32_t zero, uint32_t bar, T... v) { return bar | ((bits(v) ^ ...) & zero); }
__device__ __forceinline__ void sts32(uint32_t a, float v) { asm volatile("st.shared.f32 [%0], %1;" ::"r"(a), "f"(v) : "memory"); }
__device__ __forceinline__ void sts64(uint32_t a, uint32_t x, uint32_t y) { asm volatile("st.shared.v2.u32 [%0], {%1, %2};" ::"r"(a), "r"(x), "r"(y) : "memory"); }
__device__ __forceinline__ void cons_sync() { asm volatile("bar.sync 1, 256;" ::: "memory"); }

__device__ __forceinline__ uint4 lds128(uint32_t a) {
    uint4 v;
    asm volatile("ld.shared.v4.u32 {%0,%1,%2,%3}, [%4];" : "=r"(v.x), "=r"(v.y), "=r"(v.z), "=r"(v.w) : "r"(a));
    return v;
}
__device__ __forceinline__ float4 lds128f(uint32_t a) {
    float4 v;
    asm volatile("ld.shared.v4.f32 {%0,%1,%2,%3}, [%4];" : "=f"(v.x), "=f"(v.y), "=f"(v.z), "=f"(v.w) : "r"(a) : "memory");
    return v;
}
__device__ __forceinline__ float2 lds64f(uint32_t a) {
    float2 v;
    asm volatile("ld.shared.v2.f32 {%0,%1}, [%2];" : "=f"(v.x), "=f"(v.y) : "r"(a) : "memory");
    return v;
}
__device__ __forceinline__ uint32_t lds32(uint32_t a) {
    uint32_t v;
    asm volatile("ld.shared.u32 %0, [%1];" : "=r"(v) : "r"(a));
    return v;
}
__device__ __forceinline__ void ldsm_x4(uint32_t* r, uint32_t a) {
    asm volatile("ldmatrix.sync.aligned.m8n8.x4.shared.b16 {%0,%1,%2,%3}, [%4];"
                 : "=r"(r[0]), "=r"(r[1]), "=r"(r[2]), "=r"(r[3]) : "r"(a));
}
__device__ __forceinline__ void ldsm_x4_t(uint32_t* r, uint32_t a) {
    asm volatile("ldmatrix.sync.aligned.m8n8.x4.trans.shared.b16 {%0,%1,%2,%3}, [%4];"
                 : "=r"(r[0]), "=r"(r[1]), "=r"(r[2]), "=r"(r[3]) : "r"(a));
}
__device__ __forceinline__ void mma_bf16(float* c, const uint32_t* a, uint32_t b0, uint32_t b1) {
    asm volatile("mma.sync.aligned.m16n8k16.row.col.f32.bf16.bf16.f32 {%0,%1,%2,%3}, {%4,%5,%6,%7}, {%8,%9}, {%0,%1,%2,%3};"
                 : "+f"(c[0]), "+f"(c[1]), "+f"(c[2]), "+f"(c[3]) : "r"(a[0]), "r"(a[1]), "r"(a[2]), "r"(a[3]), "r"(b0), "r"(b1));
}
__device__ __forceinline__ float bf_lo(uint32_t u) { return __uint_as_float(u << 16); }
__device__ __forceinline__ float bf_hi(uint32_t u) { return __uint_as_float(u & 0xffff0000u); }
__device__ __forceinline__ uint32_t pack_bf(float hi, float lo) { uint32_t r; asm("cvt.rn.bf16x2.f32 %0, %1, %2;" : "=r"(r) : "f"(hi), "f"(lo)); return r; }
__device__ __forceinline__ float bfr(float x) { return __uint_as_float(pack_bf(x, 0.f)); }

__device__ __forceinline__ uint64_t pk(float v, uint32_t tag) { return ((uint64_t)tag << 32) | (uint64_t)__float_as_uint(v); }
__device__ __forceinline__ void ll_st1(uint64_t* p, float a, uint32_t tag) {
    asm volatile("st.relaxed.gpu.global.b64 [%0], %1;" ::"l"(p), "l"(pk(a, tag)) : "memory");
}
__device__ __forceinline__ uint4 ll_ld2(const uint4* p) {
    uint4 v;
    asm volatile("{\n.reg .b64 a, b;\nld.relaxed.gpu.global.v2.b64 {a, b}, [%4];\nmov.b64 {%0, %1}, a;\nmov.b64 {%2, %3}, b;\n}"
                 : "=r"(v.x), "=r"(v.y), "=r"(v.z), "=r"(v.w) : "l"(p) : "memory");
    return v;
}
__device__ __forceinline__ uint32_t in_word(float v) {
    uint32_t r;
    asm("min.u32 %0, %1, 0xfffffffe;" : "=r"(r) : "r"(__float_as_uint(v)));
    return r;
}
__device__ __forceinline__ void in_st1(void* p, float v) {
    asm volatile("st.relaxed.gpu.global.u32 [%0], %1;" ::"l"(p), "r"(in_word(v)) : "memory");
}
__device__ __forceinline__ void in_st4(void* p, uint32_t a, uint32_t b, uint32_t c, uint32_t d) {
    asm volatile("st.relaxed.gpu.global.v4.u32 [%0], {%1, %2, %3, %4};" ::"l"(p), "r"(a), "r"(b), "r"(c), "r"(d) : "memory");
}
__device__ __forceinline__ uint32_t in_ld1(const void* p) {
    uint32_t v;
    asm volatile("ld.relaxed.gpu.global.u32 %0, [%1];" : "=r"(v) : "l"(p) : "memory");
    return v;
}
__device__ __forceinline__ uint4 in_ld4(const void* p) {
    uint4 v;
    asm volatile("ld.relaxed.gpu.global.v4.u32 {%0, %1, %2, %3}, [%4];" : "=r"(v.x), "=r"(v.y), "=r"(v.z), "=r"(v.w) : "l"(p) : "memory");
    return v;
}
__device__ __forceinline__ void in_ld2p(const void* p, uint2& v, bool on) {
    asm volatile("{\n.reg .pred q;\nsetp.ne.u32 q, %3, 0;\n@q ld.relaxed.gpu.global.v2.u32 {%0, %1}, [%2];\n}"
                 : "+r"(v.x), "+r"(v.y) : "l"(p), "r"((uint32_t)on) : "memory");
}
__device__ __forceinline__ bool in_ok(const uint2& v) { return max(v.x, v.y) != SENT; }
__device__ __forceinline__ void in_ld4p(const void* p, uint4& v, bool on) {
    asm volatile("{\n.reg .pred q;\nsetp.ne.u32 q, %5, 0;\n@q ld.relaxed.gpu.global.v4.u32 {%0, %1, %2, %3}, [%4];\n}"
                 : "+r"(v.x), "+r"(v.y), "+r"(v.z), "+r"(v.w) : "l"(p), "r"((uint32_t)on) : "memory");
}
__device__ __forceinline__ void pkt_st(uint4* p, uint32_t x, uint32_t y, uint32_t z, uint32_t w) {
    asm volatile("{\n.reg .b128 t;\n.reg .b64 a, b;\nmov.b64 a, {%1, %2};\nmov.b64 b, {%3, %4};\nmov.b128 t, {a, b};\nst.relaxed.gpu.global.b128 [%0], t;\n}"
                 ::"l"(p), "r"(x), "r"(y), "r"(z), "r"(w) : "memory");
}
__device__ __forceinline__ void pkt_ldp(const uint4* p, uint4& v, bool on) {
    asm volatile("{\n.reg .pred q;\n.reg .b128 t;\n.reg .b64 a, b;\nsetp.ne.u32 q, %5, 0;\nmov.b64 a, {%0, %1};\nmov.b64 b, {%2, %3};\nmov.b128 t, {a, b};\n"
                 "@q ld.relaxed.gpu.global.b128 t, [%4];\nmov.b128 {a, b}, t;\nmov.b64 {%0, %1}, a;\nmov.b64 {%2, %3}, b;\n}"
                 : "+r"(v.x), "+r"(v.y), "+r"(v.z), "+r"(v.w) : "l"(p), "r"((uint32_t)on) : "memory");
}

__device__ __forceinline__ float sqrt_fast(float x) { float r; asm("sqrt.approx.ftz.f32 %0, %1;" : "=f"(r) : "f"(x)); return r; }
__device__ __forceinline__ float rcp_fast(float x) { float r; asm("rcp.approx.ftz.f32 %0, %1;" : "=f"(r) : "f"(x)); return r; }
__device__ __forceinline__ float ex2(float x) { float r; asm("ex2.approx.ftz.f32 %0, %1;" : "=f"(r) : "f"(x)); return r; }
constexpr float L2E = 1.4426950408889634f;
__device__ __forceinline__ void ln_sums(const uint2* v, float& t1, float& t2) {
    float s1[5], s2[5];
#pragma unroll
    for (int i = 0; i < 5; i++) {
        const float a0 = bf_lo(v[i].x), a1 = bf_hi(v[i].x), a2 = bf_lo(v[i].y), a3 = bf_hi(v[i].y);
        s1[i] = (a0 + a1) + (a2 + a3);
        s2[i] = fmaf(a0, a0, a1 * a1) + fmaf(a2, a2, a3 * a3);
    }
    t1 = ((s1[0] + s1[1]) + (s1[2] + s1[3])) + s1[4]; t2 = ((s2[0] + s2[1]) + (s2[2] + s2[3])) + s2[4];
#pragma unroll
    for (int o = 16; o > 0; o >>= 1) { t1 += __shfl_xor_sync(0xffffffffu, t1, o); t2 += __shfl_xor_sync(0xffffffffu, t2, o); }
}
__device__ __forceinline__ void ln_finish(float t1, float t2, float& mean_b, float& inv_den) {
    const float mean = t1 * (1.0f / D_MODEL);
    const float var = fmaxf(fmaf(-mean, mean, t2 * (1.0f / D_MODEL)), 0.f);
    mean_b = bfr(mean);
    inv_den = rcp_fast(bfr(sqrt_fast(bfr(bfr(var) + 1e-5f))));
}

struct KParams {
    const __nv_bfloat16* wq;
    uint32_t t_first;
    uint32_t t_step;
    const __nv_bfloat16* x;
    Scratch* sc;
    unsigned char* xa;
    __nv_bfloat16* out;
    uint32_t t_smax;
    uint32_t t_lat;
    uint32_t zero;
};
struct TMaps { CUtensorMap k, v, wo, w1, w3, w2; };

__global__ void __launch_bounds__(NTHREADS, 1)
fused_decode_kernel(const KParams p, const __grid_constant__ TMaps tm) {
    extern __shared__ __align__(1024) unsigned char smem[];
    const uint32_t sbase = smem_u32(smem);
    const int tid = threadIdx.x;
    const int b = blockIdx.x;
    const int head = b >> 2, sp = b & 3;
    {
        if (tid < 192) {
            const uint32_t rg = tid / 24, ch = tid - rg * 24;
            const char* src = reinterpret_cast<const char*>(p.wq) + (uint32_t)(sp * 160 * (NHEAD * DH * 2) + head * ROW_BYTES + rg * (NHEAD * DH * 2) + ch * 16);
            uint32_t dst = sbase + SM_RING + QSLOT * TILE_BYTES + ((tid ^ (tid >> 3 & 7)) << 4);
#pragma unroll 4
            for (int i = 0; i < 20; i++) {
                asm volatile("cp.async.cg.shared.global [%0], [%1], 16;" ::"r"(dst), "l"(src) : "memory");
                dst += 8 * ROW_BYTES;
                src += (size_t)8 * (NHEAD * DH * 2);
            }
        }
    }
    const int warp = __shfl_sync(0xffffffffu, tid >> 5, 0), lane = tid & 31;
    const int rr = !(b & 1) ? b >> 1 : (b & 15) < 12 ? (b >> 4) * 6 + (b >> 1 & 7) : NFFN + (b >> 4) * 2 + (b >> 1 & 1);
    const bool is_wo = !(b & 1) && rr < NWO, is_ffn = (b & 1) && rr < NFFN, is_out = !is_ffn;
    const int og = (rr >> 2) + (b & 1) * 4, oh = og >= 10, oq = (og - 10 * oh) * 4 + (rr & 3);
    const int kg = min(rr / 10, NG - 1), ng = rr % 10;
    const uint32_t bar_full = sbase + SM_BAR;
    const uint32_t bar_empty = sbase + SM_BAR + 128;
    const uint32_t bar_tail = sbase + SM_BAR + 256;
    const uint32_t bar_set = bar_tail + 8 * NTAIL;
    const uint32_t bar_pace = bar_set + 8;
    const uint32_t bar_q = bar_set + 16;
    const uint32_t bar_part = bar_set + 24;
    volatile uint32_t* s_pace = reinterpret_cast<volatile uint32_t*>(smem + SM_MISC + 64);
    auto tail_time = [&](int t) { return s_pace[0] + (s_pace[1] * (((N_TAIL0 - cfg::ADAPT) * 478 + NWP * cfg::T_WO + t) * 256 / 478) >> 8); };

    if (warp == 8) {
        const uint32_t c_start = now_q();
        if (lane >= 1 && lane <= 6) asm volatile("prefetch.tensormap [%0];" ::"l"(reinterpret_cast<uint64_t>(&tm.k + (lane - 1))) : "memory");
        uint64_t pol_stream;
        asm volatile("createpolicy.fractional.L2::evict_first.b64 %0, 1.0;" : "=l"(pol_stream));
        if (lane == 0) {
#pragma unroll 1
            for (int i = 0; i < NSLOT; i++) { mbar_init(bar_full + 8 * i, 1); mbar_init(bar_empty + 8 * i, 1); }
#pragma unroll 1
            for (int i = 0; i < NTAIL + 4; i++) mbar_init(bar_tail + 8 * i, i == NTAIL + 2 ? 4 : 1);
            asm volatile("fence.mbarrier_init.release.cluster;" ::: "memory");
        }
        __syncwarp();
        asm volatile("bar.arrive 2, 288;" ::: "memory");
        asm volatile("bar.arrive 3, 64;" ::: "memory");
        asm volatile("bar.arrive 4, 64;" ::: "memory");
        if (is_ffn) asm volatile("bar.arrive 10, 192;" ::: "memory");
        if (lane == 0) {
            uint32_t due = c_start + p.t_first, step = p.t_step;
#pragma unroll 1
            for (int n = 0; n < N_TAIL0; n++) {
                const int slot = n & (NSLOT - 1);
                const int use = (n >> 4) + (slot >= QSLOT);
                if (n >= cfg::CAP) mbar_wait(bar_full + 8 * ((n - cfg::CAP) & (NSLOT - 1)), ((n - cfg::CAP) >> 4) & 1);
                if (use >= 1) mbar_wait(bar_empty + 8 * slot, (use - 1) & 1);
                if (n == cfg::ADAPT) { mbar_wait(bar_pace, 0); due = s_pace[0]; step = s_pace[1]; }
                const uint32_t full = bar_full + 8 * slot;
                mbar_expect_tx(full, TILE_BYTES);
                wait_until(due);
                LST(128 + n);
                tma_tile(sbase + SM_RING + slot * TILE_BYTES, &tm.k + (n & 1), ((n >> 1) * SK + (SK - WIN) + b * 32) * 3, full, pol_stream);
                due += step;
            }
            int rel = 0;
            auto released = [&](int end) {
#pragma unroll 1
                for (; rel * TILE_BYTES < end; rel++) mbar_wait(bar_empty + 8 * rel, rel < QSLOT);
            };
            const uint32_t t_wo = step * (cfg::T_WO * 4096 / 478) >> 12;
            if (is_wo) {
#pragma unroll 1
                for (int j = 0; j < NWP; j++) {
                    released((j + 1) * WPIECE);
                    mbar_expect_tx(bar_tail + 8 * j, WPIECE);
                    wait_until(due);
                    LST(128 + N_TAIL0 + j);
                    tma_5d(sbase + j * WPIECE, &tm.wo, ng * 64, j * (NG * 128) + kg * 128, 0, 0, bar_tail + 8 * j);
                    due += t_wo;
                }
            } else {
                due += NWP * t_wo;
            }
            due += 4 * cfg::T_GAP;
            if (is_out) {
                due += step * (cfg::T_W2AT * 4096 / 478) >> 12;
                released(SM_W2 + NDP * PIECE);
#pragma unroll
                for (int j = 0; j < NDP; j++) mbar_expect_tx(bar_tail + 8 * (NWP + j), PIECE);
                sleep_until(due - 4 * 400);
#pragma unroll
                for (int j = 0; j < NDP; j++) {
                    wait_until(due);
                    tma_5d(sbase + SM_W2 + j * PIECE, &tm.w2, oq * 16, (oh * NDP + j) * 256, 0, 0, bar_tail + 8 * (NWP + j));
                    LST(128 + N_TAIL0 + NWP + j);
                    due += step * (cfg::T_W2 * 4096 / 478) >> 12;
                }
            } else if (is_ffn) {
                released(NUP * WPIECE);
#pragma unroll
                for (int j = 0; j <= NUP; j++) mbar_expect_tx(bar_tail + 8 * j, j < NUP - 1 ? WPIECE : WPIECE / 2);
                sleep_until(due - 4 * 400);
#pragma unroll
                for (int j = 0; j <= NUP; j++) {
                    const uint32_t full = bar_tail + 8 * j;
                    wait_until(due);
                    if (j == 0) tma_5d(sbase, &tm.w1, rr * 32, 0, 0, 0, full);
                    else tma_5d(sbase + (j - 1) * WPIECE + WPIECE / 2, &tm.w3, rr * 32, 0, 0, (j - 1) * 8, full);
                    if (j < NUP - 1) tma_5d(sbase + (j + 1) * WPIECE, &tm.w1, rr * 32, 0, 0, (j + 1) * 8, full);
                    LST(128 + N_TAIL0 + j);
                    due += step * ((j < NUP - 1 ? cfg::T_UP : cfg::T_UP2) * 4096 / 478) >> 12;
                }
            }
        }
    } else if (warp == 10) {
        asm volatile("bar.sync 4, 64;" ::: "memory");
        if (lane == 0) {
            uint32_t epoch0;
            asm volatile("ld.relaxed.gpu.global.u32 %0, [%1];" : "=r"(epoch0) : "l"(&p.sc->epoch) : "memory");
            constexpr int MN = cfg::MN;
            const uint32_t t0 = now_q();
            uint32_t sa = 0, sb = 0;
#pragma unroll 1
            for (int n = 0; n < cfg::MB + MN; n++) {
#pragma unroll 1
                for (int k = 0; k < 256 && !mbar_try(bar_full + 8 * (n & (NSLOT - 1)), (n >> 4) & 1); k++) { }
                const uint32_t t = now_q() - t0;
                LST(n);
                if ((uint32_t)(n - cfg::MA) < MN) sa += t;
                if (n >= cfg::MB) sb += t;
            }
            const uint32_t mb = t0 + sb / MN;
            unsigned long long* pace = p.sc->pace + ((epoch0 + 1) & 1);
            mbar_wait(bar_set, 0);
            asm volatile("red.relaxed.gpu.global.add.u64 [%0], %1;" ::"l"(pace), "l"((unsigned long long)mb << 32 | min((sb - sa) / (4 * MN), 0xffffu) << 8 | 1) : "memory");
            if (b == 0) p.sc->pace[epoch0 & 1] = 0;
            unsigned long long v;
            uint32_t n = 0, cnt;
#pragma unroll 1
            do {
                __nanosleep(n ? 200 : 1000);
                asm volatile("ld.relaxed.gpu.global.u64 %0, [%1];" : "=l"(v) : "l"(pace) : "memory");
                cnt = (uint32_t)v & 0xff;
                if (++n > SPIN_LIMIT) __trap();
            } while (cnt < NCTA);
            const uint32_t step = min(max(((uint32_t)v >> 8) / (NCTA / 4 * (cfg::MB - cfg::MA)), p.t_step), p.t_smax);
            s_pace[0] = mb + (int)((uint32_t)(v >> 32) - NCTA * mb) / NCTA + step * (2 * (cfg::ADAPT - cfg::MB) - (MN - 1)) / 2 - p.t_lat;
            s_pace[1] = step;
            mbar_arrive(bar_pace);
            LST(89);
        }
    } else if (warp == 9) {
        const uint32_t c_start = now_q();
        uint32_t epoch0;
        asm volatile("ld.relaxed.gpu.global.u32 %0, [%1];" : "=r"(epoch0) : "l"(&p.sc->epoch) : "memory");
        sleep_until(c_start + p.t_first);
        unsigned char* slot[2];
        slot[0] = p.xa + xa_off(o_off(b * 48 + (lane % 6) * 8), lane / 6 & 1);
        slot[1] = p.xa + (is_wo ? xa_off(L_GATHER + (lane >> 4) * HCOPY_BYTES + (kg * D_MODEL + ng * 64 + (lane & 7) * 8) * 2, lane >> 3 & 1)
                                : xa_off(L_ACT + rr * 64 + (lane & 3) * 16, lane >> 2 & 1));
        const int n2 = is_wo ? 16 * cfg::HCOPY : is_ffn ? 8 : 0;
#pragma unroll
        for (int i = 0; i < 2; i++) if (lane < (i ? n2 : 12)) in_st4(slot[i], SENT, SENT, SENT, SENT);
#pragma unroll
        for (int i = 1; i <= cfg::PREPART; i++) pkt_st(p.sc->part + (((NHEAD - i) * 4 + (lane & 3)) * NCTA + b) * 8 + (lane >> 2), 0, 0, 0, epoch0 & 3);
        unsigned char* probe = p.xa + xa_off(L_PROBE + b * 1024 + (lane >> 1 & 7) * 128 + (lane & 1) * 16, lane >> 4);
        in_st4(probe, SENT, SENT, SENT, SENT);
        const bool clr = is_out && !oh && lane < 2;
        if (clr) in_st4(p.out + oq * 16 + lane * 8, 0, 0, 0, 0);
        sleep_until(now_q() + 4 * cfg::RBDELAY + b * 60);
        uint32_t acc = SENT;
#pragma unroll
        for (int i = 0; i < 2; i++) if (lane < (i ? n2 : 12)) acc &= in_ld1(slot[i]);
        if (clr) acc &= ~in_ld1(p.out + oq * 16 + lane * 8);
        if (__any_sync(0xffffffffu, acc != SENT)) __trap();
        int vote = 0;
        uint32_t lat[2] = {0, 0};
#pragma unroll 1
        for (int r = 0; r <= cfg::NPROBE && abs(vote) < cfg::VOTES; r++) {
            __nanosleep(300);
            uint32_t d[2];
#pragma unroll
            for (int i = 0; i < 2; i++) {
                const uint32_t c0 = (uint32_t)clock();
                if (__any_sync(0xffffffffu, in_ld1(p.xa + xa_off(L_PROBE + b * 1024 + (lane & 7) * 128, i)) != SENT)) __trap();
                d[i] = (uint32_t)clock() - c0;
                if (r) lat[i] += min(d[i], 1500u);
            }
            if (r) vote = __shfl_sync(0xffffffffu, vote + (d[1] < d[0]) - (d[0] < d[1]), 0);
        }
        const uint32_t sel = vote ? vote > 0 : lat[1] < lat[0];
        const uint32_t tag = epoch0 + 1;
        asm volatile("bar.sync 3, 64;" ::: "memory");
        if (lane == 0) { s_pace[2] = sel; mbar_arrive(bar_set); }
        {
            mbar_wait(bar_pace, 0);
            sleep_until(s_pace[0] + (cfg::KEEP_AT - cfg::ADAPT) * s_pace[1]);
            const uint32_t t_res = tail_time(cfg::T_RESAT);
            float c[4] = {0.f, 0.f, 0.f, 0.f};
            const uint32_t z[4] = {p.zero, p.zero, p.zero, p.zero};
            uint32_t n = 0;
#pragma unroll 1
            do {
                mma_bf16(c, z, p.zero, p.zero);
                __nanosleep(cfg::KEEP);
                n += 1 + __float_as_uint(c[0]);
            } while (!__all_sync(0xffffffffu, is_ffn ? mbar_test(bar_tail, 0) : (int)(now_q() - t_res) >= 0) && n < SPIN_LIMIT);
            if (is_ffn) {
                unsigned char* adst = p.xa + xa_off(L_ACT + rr * 64 + (lane >> 3) * 16 + (lane & 3) * 4, lane >> 2 & 1);
                uint32_t src = sbase + SM_RED + lane * 8;
                asm volatile("bar.sync %0, 192;" ::"r"(after(p.zero, 11, adst, src)) : "memory");
                float t1, t2, mean_b, inv_den;
                {
                    float q1[5], q2[5];
#pragma unroll
                    for (int i = 0; i < 5; i++) {
                        const float4 a = lds128f(sbase + SM_STAT + i * 48), c = lds128f(sbase + SM_STAT + i * 48 + 16), d = lds128f(sbase + SM_STAT + i * 48 + 32);
                        q2[i] = ((a.x + a.y) + (a.z + a.w)) + ((c.x + c.y) + (c.z + c.w));
                        q1[i] = (d.x + d.y) + (d.z + d.w);
                    }
                    t1 = ((q1[0] + q1[1]) + (q1[2] + q1[3])) + q1[4]; t2 = ((q2[0] + q2[1]) + (q2[2] + q2[3])) + q2[4];
                }
                ln_finish(t1, t2, mean_b, inv_den);
                float2 r[8];
#define S_(c) (((r[0].c + r[1].c) + (r[2].c + r[3].c)) + ((r[4].c + r[5].c) + (r[6].c + r[7].c)))
                asm volatile("bar.sync %0, 288;" ::"r"(after(p.zero, 8, mean_b, inv_den)) : "memory");
#pragma unroll
                for (int i = 0; i < 8; i++) r[i] = lds64f(src + i * 256);
                const float gate = bfr(fmaf(-mean_b, S_(y), S_(x)) * inv_den);
                const float silu = bfr(__fdividef(gate, 1.0f + ex2(-gate * L2E)));
                asm volatile("bar.sync %0, 288;" ::"r"(after(p.zero, 5, silu)) : "memory");
#pragma unroll
                for (int i = 0; i < 8; i++) r[i] = lds64f(src + 2048 + i * 256);
                const float act = silu * bfr(fmaf(-mean_b, S_(y), S_(x)) * inv_den);
#undef S_
                const float oth = __shfl_xor_sync(0xffffffffu, act, 4);
                in_st1(adst, __uint_as_float((lane & 4) ? pack_bf(act, oth) : pack_bf(oth, act)));
                if (lane == 0) LST(110);
            }
            if (is_out) {
                const int col = oq * 16 + (lane & 15);
                float res = 0.f;
                if (!oh) {
                    uint32_t u[NG], xv;
                    asm volatile("ld.global.nc.u16 %0, [%1];" : "=r"(xv) : "l"(p.x + col));
                    n = 0;
#pragma unroll 1
                    do {
#pragma unroll
                        for (int i = 0; i < NG; i++) u[i] = in_ld1(p.xa + xa_off(L_GATHER + rr % cfg::HCOPY * HCOPY_BYTES + (i * D_MODEL + (col & ~1)) * 2, sel));
                        if (++n > SPIN_LIMIT) __trap();
                    } while (__any_sync(0xffffffffu, max(max(max(u[0], u[1]), max(u[2], u[3])), max(u[4], u[5])) == SENT));
                    if (b == 0 && lane == 0) p.sc->epoch = tag;
#define F_(i) ((lane & 1) ? bf_hi(u[i]) : bf_lo(u[i]))
                    res = bfr(bf_lo(xv) + bfr(((F_(0) + F_(1)) + (F_(2) + F_(3))) + (F_(4) + F_(5))));
#undef F_
                }
                mma_bf16(c, z, p.zero, p.zero);
                mbar_wait(after(p.zero, bar_tail + 8 * NWP, c[0]), 0);
                mma_bf16(c, z, p.zero, p.zero);
                res += c[0];
                __nv_bfloat16* dst = p.out + (col & ~1);
                uint32_t src = sbase + SM_HN + (lane & 15) * 48;
                asm volatile("bar.sync %0, 288;" ::"r"(after(p.zero, 5, src, dst, res)) : "memory");
                const float4 ra = lds128f(src), rb = lds128f(src + 16);
                const float e = ((ra.x + ra.y) + (ra.z + ra.w)) + (((rb.x + rb.y) + (rb.z + rb.w)) + res);
                if (lane < 16) asm volatile("red.relaxed.gpu.global.add.noftz.bf16x2 [%0], %1;" ::"l"(dst), "r"((lane & 1) ? pack_bf(e, 0.f) : pack_bf(0.f, e)) : "memory");
                if (lane == 0) LST(96);
            }
        }
    } else if (warp > 10) {
        if (is_ffn) {
            const int col = (tid - 352) * 4;
            uint2 xres;
            asm volatile("bar.sync 10, 192;" ::: "memory");
            mbar_wait(bar_pace, 0);
            asm volatile("ld.global.nc.v2.u32 {%0, %1}, [%2];" : "=r"(xres.x), "=r"(xres.y) : "l"(p.x + col) : "memory");
            const unsigned char* gsrc[NG];
            uint2 u[NG];
#pragma unroll
            for (int i = 0; i < NG; i++) gsrc[i] = p.xa + xa_off(L_GATHER + rr % cfg::HCOPY * HCOPY_BYTES + (i * D_MODEL + col) * 2, s_pace[2]);
            const uint32_t hdst = sbase + SM_HN + col * 2;
            const bool diag = (lane & 3) == (lane >> 3);
            const uint32_t sdst = sbase + SM_STAT + (warp - 11) * 48 + (diag ? (lane >> 2) : 8 + (lane & 3)) * 4;
            const uint32_t at = after(p.zero, tail_time(cfg::T_HAT), gsrc[0], gsrc[1], gsrc[2], gsrc[3], gsrc[4], gsrc[5], hdst, sdst, xres.x);
            sleep_until(at - 4 * 300);
            wait_until(at);
#pragma unroll
            for (int i = 0; i < NG; i++) { u[i] = make_uint2(0, 0); in_ld2p(gsrc[i], u[i], true); }
            uint32_t n = 0;
#pragma unroll 1
            while (__any_sync(0xffffffffu, max(max(max(u[0].x, u[0].y), max(u[1].x, u[1].y)), max(max(max(u[2].x, u[2].y), max(u[3].x, u[3].y)),
                                                                                                max(max(u[4].x, u[4].y), max(u[5].x, u[5].y)))) == SENT)) {
#pragma unroll
                for (int i = 0; i < NG; i++) in_ld2p(gsrc[i], u[i], !in_ok(u[i]));
                if (++n > SPIN_LIMIT) __trap();
            }
#define F_(f, c) (f(xres.c) + bfr(((f(u[0].c) + f(u[1].c)) + (f(u[2].c) + f(u[3].c))) + (f(u[4].c) + f(u[5].c))))
            const uint32_t hp0 = pack_bf(F_(bf_hi, x), F_(bf_lo, x)), hp1 = pack_bf(F_(bf_hi, y), F_(bf_lo, y));
#undef F_
            sts64(hdst, hp0, hp1);
            asm volatile("bar.arrive 9, 416;" ::: "memory");
            float cs[4] = {0.f, 0.f, 0.f, 0.f};
            const uint32_t sa[4] = {hp0, 0x3f803f80u, hp1, 0x3f803f80u};
            mma_bf16(cs, sa, hp0, hp1);
            if (diag || (!(lane & 4) && (lane & 3) == (lane >> 3 ^ 1))) sts32(sdst, !diag ? cs[2] + cs[3] : (lane & 4) ? cs[1] : cs[0]);
            asm volatile("bar.arrive 11, 192;" ::: "memory");
            if (lane == 0) LST(100);
        }
    } else {
        const int t = lane & 3, g = lane >> 2;
        const int arow = (lane & 7) + ((lane >> 4) << 3), ahalf = (lane >> 3) & 1;
        uint32_t epoch0;
        const char* xb = reinterpret_cast<const char*>(p.x);
        asm volatile("ld.relaxed.gpu.global.u32 %0, [%1];" : "=r"(epoch0) : "l"(&p.sc->epoch) : "memory");
        uint64_t* q1dst = p.sc->q1 + ((head * 4 + (warp & 3)) * 4 + sp) * 48 + min(t, 2) * 16 + g;
        uint4* q2dst = p.sc->q2 + (head * 8 + sp * 2 + lane / 12) * 4 + t;
        if (warp == 7) {
            uint2 xu[5];
#pragma unroll
            for (int i = 0; i < 5; i++) asm volatile("ld.global.nc.v2.u32 {%0, %1}, [%2];" : "=r"(xu[i].x), "=r"(xu[i].y) : "l"(xb + i * 256 + lane * 8));
            float t1, t2, mean_b, inv_den;
            ln_sums(xu, t1, t2);
            ln_finish(t1, t2, mean_b, inv_den);
#define N_(v) (bfr((v) - mean_b) * inv_den)
#pragma unroll
            for (int i = 0; i < 5; i++)
                sts64(sbase + SM_HN + i * 256 + lane * 8, pack_bf(N_(bf_hi(xu[i].x)), N_(bf_lo(xu[i].x))), pack_bf(N_(bf_hi(xu[i].y)), N_(bf_lo(xu[i].y))));
#undef N_
        } else {
            if (warp < 4 && t < 3) { ll_st1(q1dst, 0.f, 0); ll_st1(q1dst + 8, 0.f, 0); }
            if (warp == 4 && lane < 24 && lane % 12 < 4) pkt_st(q2dst, 0, 0, 0, 0);
        }
        asm volatile("cp.async.wait_all;" ::: "memory");
        if (lane == 0) LST(80 + warp);
        asm volatile("bar.sync 2, 288;" ::: "memory");
        const uint32_t tag = epoch0 + 1;
        auto block = [&](int i) { const int unit = arow * 3 + (i >> 2); return sbase + SM_RING + unit * 128 + ((((i & 3) * 2 + ahalf) ^ (unit & 7)) << 4); };

        if (warp < 4) {
            {
                float c[3][4];
                uint32_t wa[3];
#pragma unroll
                for (int k = 0; k < 3; k++) { c[k][0] = c[k][1] = c[k][2] = c[k][3] = 0.f; wa[k] = block(warp * 3 + k) + QSLOT * TILE_BYTES; }
                const uint32_t xa = sbase + SM_HN + sp * 320 + t * 4;
#pragma unroll 2
                for (int ks = 0; ks < 2 * NQT; ks++) {
                    const uint32_t b0 = lds32(xa + ks * 32), b1 = lds32(xa + ks * 32 + 16);
#pragma unroll
                    for (int k = 0; k < 3; k++) { uint32_t a[4]; ldsm_x4_t(a, wa[k] + ks * (TILE_BYTES / 2)); mma_bf16(c[k], a, b0, b1); }
                }
                if (t < 3) {
                    ll_st1(q1dst, t == 0 ? c[0][0] : t == 1 ? c[1][0] : c[2][0], tag);
                    ll_st1(q1dst + 8, t == 0 ? c[0][2] : t == 1 ? c[1][2] : c[2][2], tag);
                }
                asm volatile("bar.sync 6, 128;" ::: "memory");
                if (tid < NQT) mbar_arrive(bar_empty + 8 * (QSLOT + tid));
                if (tid == 0) LST(90);
            }
            const uint32_t ta[3] = {block(0), block(4), block(8)};
            mbar_wait(bar_q, 0);
            if (tid == 0) LST(92);
#pragma unroll 1
            for (int h = warp; h < NHEAD; h += 4) {
                const int slot = (2 * h) & (NSLOT - 1);
                const uint32_t par = (h >> 3) & 1;
                if (h >= NHEAD - cfg::PREPART) mbar_wait(bar_set, 0);
                uint32_t qf[24];
#pragma unroll
                for (int i = 0; i < 6; i++) { const uint4 v = lds128(sbase + SM_Q + h * ROW_BYTES + t * 96 + i * 16); qf[4 * i] = v.x; qf[4 * i + 1] = v.y; qf[4 * i + 2] = v.z; qf[4 * i + 3] = v.w; }
                uint32_t ad[12];
#pragma unroll
                for (int i = 0; i < 12; i++) ad[i] = (ta[i >> 2] + slot * TILE_BYTES) ^ ((i & 3) << 5);
                float sc[4][4];
#pragma unroll
                for (int j = 0; j < 4; j++) sc[j][0] = sc[j][1] = sc[j][2] = sc[j][3] = 0.f;
                mbar_wait(bar_full + 8 * slot, par);
#pragma unroll
                for (int i = 0; i < 12; i++) {
                    const uint32_t a[4] = {qf[2 * i], qf[2 * i], qf[2 * i + 1], qf[2 * i + 1]};
                    uint32_t k0[4], k1[4];
                    ldsm_x4(k0, ad[i]); ldsm_x4(k1, ad[i] + TILE_BYTES / 2);
                    mma_bf16(sc[0], a, k0[0], k0[1]); mma_bf16(sc[1], a, k0[2], k0[3]);
                    mma_bf16(sc[2], a, k1[0], k1[1]); mma_bf16(sc[3], a, k1[2], k1[3]);
                }
                const float scale = 0.07216878364870322f;
                float m = -INFINITY;
#pragma unroll
                for (int j = 0; j < 4; j++) { sc[j][0] = bfr(bfr(sc[j][0]) * scale); sc[j][1] = bfr(bfr(sc[j][1]) * scale); m = fmaxf(m, fmaxf(sc[j][0], sc[j][1])); }
                if (lane == 0) mbar_arrive(after(p.zero, bar_empty + 8 * slot, m));
                m = fmaxf(m, __shfl_xor_sync(0xffffffffu, m, 1));
                m = fmaxf(m, __shfl_xor_sync(0xffffffffu, m, 2));
                float l = 0.f;
                uint32_t pf[4];
#pragma unroll
                for (int j = 0; j < 4; j++) {
                    const float p0 = ex2((sc[j][0] - m) * L2E), p1 = ex2((sc[j][1] - m) * L2E);
                    l += p0 + p1;
                    const uint32_t hi = pack_bf(p1, p0);
                    pf[j] = (g & 1) ? pack_bf(p1 - bf_hi(hi), p0 - bf_lo(hi)) : hi;
                }
                l += __shfl_xor_sync(0xffffffffu, l, 1);
                l += __shfl_xor_sync(0xffffffffu, l, 2);
                const uint32_t meta = (__float_as_uint(m) & 0xffff0000u) | ((__float_as_uint(l) - 0x3f800000u + 0x800u) >> 10 & 0xfffcu) | (tag & 3);
                uint32_t pq[4][4];
#pragma unroll
                for (int q = 0; q < 4; q++)
#pragma unroll
                    for (int j = 0; j < 4; j++) pq[q][j] = (g >> 1) == q ? pf[j] : 0;
                float o[6][4];
#pragma unroll
                for (int k = 0; k < 6; k++) o[k][0] = o[k][1] = o[k][2] = o[k][3] = 0.f;
                uint4* dst = p.sc->part + ((h * 4 + t) * NCTA + b) * 8 + g;
                mbar_wait(after(p.zero, bar_full + 8 * slot + 8, meta, dst, pq[0][0], pq[1][1], pq[2][2], pq[3][3]), par);
#pragma unroll
                for (int i = 0; i < 12; i++) {
                    uint32_t v0[4], v1[4];
                    ldsm_x4_t(v0, ad[i] + TILE_BYTES); ldsm_x4_t(v1, ad[i] + TILE_BYTES + TILE_BYTES / 2);
                    mma_bf16(o[i % 3], v0, pq[i / 3][0], pq[i / 3][1]);
                    mma_bf16(o[3 + i % 3], v1, pq[i / 3][2], pq[i / 3][3]);
                }
                uint32_t w[3];
#pragma unroll
                for (int k = 0; k < 3; k++) w[k] = pack_bf((o[k][2] + o[k][3]) + (o[k + 3][2] + o[k + 3][3]), (o[k][0] + o[k][1]) + (o[k + 3][0] + o[k + 3][1]));
                pkt_st(dst, w[0], w[1], w[2], meta);
                if (lane == 0) {
                    mbar_arrive(after(p.zero, bar_empty + 8 * slot + 8, w[0], w[1], w[2]));
                    if (h == head) mbar_arrive(bar_part);
                }
            }
            if (tid == 96) LST(91);
        } else {
            const int u = tid - 128;
            uint32_t n = 0;
            if (warp == 4) {
                const uint4* src = reinterpret_cast<const uint4*>(p.sc->q1 + (head * 4 + sp) * 4 * 48) + min(lane, 23);
                uint4 v[4];
                sleep_until(now_q() + 4 * cfg::QDELAY);
#pragma unroll 1
                do {
                    if (n) __nanosleep(cfg::QSLEEP);
#pragma unroll
                    for (int i = 0; i < 4; i++) v[i] = ll_ld2(src + i * 24);
                    if (++n > SPIN_LIMIT) __trap();
                } while (__any_sync(0xffffffffu, ((v[0].y ^ tag) | (v[0].w ^ tag) | (v[1].y ^ tag) | (v[1].w ^ tag) | (v[2].y ^ tag) | (v[2].w ^ tag) | (v[3].y ^ tag) | (v[3].w ^ tag)) != 0));
#define F_(c) ((__uint_as_float(v[0].c) + __uint_as_float(v[1].c)) + (__uint_as_float(v[2].c) + __uint_as_float(v[3].c)))
                const uint32_t w0 = pack_bf(F_(z), F_(x));
#undef F_
                const uint32_t w1 = __shfl_down_sync(0xffffffffu, w0, 4), w2 = __shfl_down_sync(0xffffffffu, w0, 8);
                if (lane < 24 && lane % 12 < 4) pkt_st(q2dst, w0, w1, w2, tag);
            }
            asm volatile("bar.sync 7, 128;" ::: "memory");
            uint4 v[8];
            {
#pragma unroll
                for (int i = 0; i < 8; i++) v[i] = make_uint4(0, 0, 0, ~tag);
                sleep_until(now_q() + 4 * cfg::QDELAY2);
                n = 0;
                bool ok;
#pragma unroll 1
                do {
                    if (n) __nanosleep(cfg::QSLEEP);
#pragma unroll
                    for (int i = 0; i < 8; i++) pkt_ldp(p.sc->q2 + u + i * 128, v[i], v[i].w != tag);
                    ok = true;
#pragma unroll
                    for (int i = 0; i < 8; i++) ok &= v[i].w == tag;
                    if (++n > SPIN_LIMIT) __trap();
                } while (!__all_sync(0xffffffffu, ok));
                const uint32_t qd = sbase + SM_Q + (u >> 5) * ROW_BYTES + t * 96 + g * 12;
#pragma unroll
                for (int i = 0; i < 8; i++) {
                    sts32(qd + i * 4 * ROW_BYTES, __uint_as_float(v[i].x)); sts32(qd + i * 4 * ROW_BYTES + 4, __uint_as_float(v[i].y)); sts32(qd + i * 4 * ROW_BYTES + 8, __uint_as_float(v[i].z));
                }
                __syncwarp();
                if (lane == 0) mbar_arrive(bar_q);
            }
            {
                const uint4* src = p.sc->part + b * NCTA * 8 + u;
                const uint32_t rdst = sbase + SM_RED + (warp - 4) * 256 + min(lane >> 3, 2) * 64 + (lane & 7) * 4;
                const uint32_t lo = o_off(b * 48 + (min(lane, 23) >> 3) * 16) + (lane & 3) * 8 + (lane & 4);
                unsigned char *od0 = p.xa + xa_off(lo, 0), *od1 = p.xa + xa_off(lo, 1);
#pragma unroll
                for (int i = 0; i < 8; i++) v[i].w = ~tag;
                mbar_wait(bar_set, 0);
                mbar_wait(after(p.zero, bar_part, src, rdst, od0, od1), 0);
                {
                    const uint32_t at = now_q() + 4 * min(cfg::PDELAY, cfg::PDELAY_LAST + (NHEAD - 1 - head) * cfg::PDELAY_STEP);
                    sleep_until(at - 4 * 300);
                    wait_until(at);
                }
                n = 0;
                uint32_t bad;
#pragma unroll 1
                do {
                    if (n && head != NHEAD - 1) __nanosleep(cfg::QSLEEP);
#pragma unroll
                    for (int i = 0; i < 8; i++) pkt_ldp(src + i * 128, v[i], ((v[i].w ^ tag) & 3) != 0);
                    bad = 0;
#pragma unroll
                    for (int i = 0; i < 8; i++) bad |= v[i].w ^ tag;
                    if (++n > SPIN_LIMIT) __trap();
                } while (__any_sync(0xffffffffu, (bad & 3) != 0));
                if (u == 0) LST(119);
                float m = -INFINITY;
#pragma unroll
                for (int i = 0; i < 8; i++) m = fmaxf(m, bf_hi(v[i].w));
                m = fmaxf(m, __shfl_xor_sync(0xffffffffu, m, 8));
                m = fmaxf(m, __shfl_xor_sync(0xffffffffu, m, 16));
                float a[7] = {0.f, 0.f, 0.f, 0.f, 0.f, 0.f, 0.f};
#pragma unroll
                for (int i = 0; i < 8; i++) {
                    const float f = ex2((bf_hi(v[i].w) - m) * L2E);
                    a[0] = fmaf(f, bf_lo(v[i].x), a[0]); a[1] = fmaf(f, bf_hi(v[i].x), a[1]);
                    a[2] = fmaf(f, bf_lo(v[i].y), a[2]); a[3] = fmaf(f, bf_hi(v[i].y), a[3]);
                    a[4] = fmaf(f, bf_lo(v[i].z), a[4]); a[5] = fmaf(f, bf_hi(v[i].z), a[5]);
                    a[6] = fmaf(f, __uint_as_float(((v[i].w & 0xfffcu) << 10) + 0x3f800000u), a[6]);
                }
#pragma unroll
                for (int o = 8; o < 32; o <<= 1)
#pragma unroll
                    for (int i = 0; i < 7; i++) a[i] += __shfl_xor_sync(0xffffffffu, a[i], o);
                if (lane < 24) { sts32(rdst, lane < 8 ? a[0] : lane < 16 ? a[2] : a[4]); sts32(rdst + 32, lane < 8 ? a[1] : lane < 16 ? a[3] : a[5]); }
                if (lane == 24) sts64(rdst + 64, __float_as_uint(a[6]), __float_as_uint(m));
                asm volatile("bar.sync 7, 128;" ::: "memory");
                if (warp == 4) {
                    float2 st[4], r[4];
#pragma unroll
                    for (int i = 0; i < 4; i++) { st[i] = lds64f(sbase + SM_RED + i * 256 + 192); r[i] = lds64f(sbase + SM_RED + i * 256 + lane * 8); }
                    const float mm = fmaxf(fmaxf(st[0].y, st[1].y), fmaxf(st[2].y, st[3].y));
                    float den = 0.f, x0 = 0.f, x1 = 0.f;
#pragma unroll
                    for (int i = 0; i < 4; i++) { const float f = ex2((st[i].y - mm) * L2E); den = fmaf(f, st[i].x, den); x0 = fmaf(f, r[i].x, x0); x1 = fmaf(f, r[i].y, x1); }
                    const float inv = rcp_fast(den);
                    const float ow = __uint_as_float(pack_bf(x1 * inv, x0 * inv));
                    if (lane < 24) { in_st1(od0, ow); in_st1(od1, ow); }
                    if (lane == 0) LST(120);
                }
            }
        }
        mbar_wait(bar_pace, 0);
        const uint32_t msel = s_pace[2];
        cons_sync();
        if (is_wo) {
            uint32_t wa = sbase + (warp * 16 + arow) * 128 + ((ahalf ^ (lane & 7)) << 4);
            uint32_t pw = sbase + SM_RED + (warp * 64 + t * 16 + (lane >> 2)) * 4, pr = sbase + SM_RED + lane * 8;
            unsigned char* gdst = p.xa + xa_off(L_GATHER + (warp >> 1) % cfg::HCOPY * HCOPY_BYTES + (kg * D_MODEL + ng * 64 + lane * 2) * 2, warp & 1);
            const unsigned char* osrc = p.xa + xa_off(L_O + kg * 2048, msel) + warp * 32 + t * 8;
            uint2 ov[NWP];
#pragma unroll
            for (int j = 0; j < NWP; j++) ov[j] = make_uint2(SENT, SENT);
            auto gather = [&](int j0, int j1) {
                uint32_t n = 0;
#pragma unroll 1
                while (true) {
                    uint32_t mx = 0;
#pragma unroll
                    for (int j = j0; j < j1; j++) mx = max(mx, max(ov[j].x, ov[j].y));
                    if (!__any_sync(0xffffffffu, mx == SENT)) break;
#pragma unroll
                    for (int j = j0; j < j1; j++) in_ld2p(osrc + j * 256, ov[j], !in_ok(ov[j]));
                    if (++n > SPIN_LIMIT) __trap();
                }
            };
            float cw[4][4];
#pragma unroll
            for (int i = 0; i < 4; i++) cw[i][0] = cw[i][1] = cw[i][2] = cw[i][3] = 0.f;
            mbar_wait(after(p.zero, bar_tail + 8, osrc, wa, pw, pr, gdst), 0);
#pragma unroll
            for (int j = 0; j < NWP; j++) in_ld2p(osrc + j * 256, ov[j], true);
            gather(0, NWP - 1);
#pragma unroll
            for (int j = 0; j < NWP; j++) {
                if (j == NWP - 1) { gather(NWP - 1, NWP); if (tid == 224) LST(93); }
                mbar_wait(bar_tail + 8 * j, 0);
                if (j == NWP - 3) in_ld2p(osrc + (NWP - 1) * 256, ov[NWP - 1], !in_ok(ov[NWP - 1]));
                uint32_t a[4][4];
#pragma unroll
                for (int i = 0; i < 4; i++) ldsm_x4_t(a[i], (wa ^ (i << 5)) + j * WPIECE);
#pragma unroll
                for (int i = 0; i < 4; i++) mma_bf16(cw[i], a[i], ov[j].x, ov[j].y);
            }
#define SEL_(e) ((t & 2) ? ((t & 1) ? cw[3][e] : cw[2][e]) : ((t & 1) ? cw[1][e] : cw[0][e]))
            sts32(pw, SEL_(0)); sts32(pw + 32, SEL_(2));
#undef SEL_
            cons_sync();
            if (warp < 2 * cfg::HCOPY) {
                float2 r[8];
#pragma unroll
                for (int i = 0; i < 8; i++) r[i] = lds64f(pr + i * 256);
#define S_(c) (((r[0].c + r[1].c) + (r[2].c + r[3].c)) + ((r[4].c + r[5].c) + (r[6].c + r[7].c)))
                in_st1(gdst, __uint_as_float(pack_bf(S_(y), S_(x))));
#undef S_
            }
            if (tid == 0) LST(94);
        } else if (is_ffn) {
            uint32_t w13a = sbase + (warp * 16 + arow) * 64 + ((ahalf ^ (lane >> 1 & 3)) << 4);
            uint32_t red_dst = sbase + SM_RED + tid * 8;
            const uint32_t ha = sbase + SM_HN + warp * 32 + t * 8;
            uint32_t aw[2][NUP][2][4];
            auto load = [&](int m, int i) {
#pragma unroll
                for (int k = 0; k < 2; k++) ldsm_x4_t(aw[m][i][k], (w13a ^ (k << 5)) + i * WPIECE + m * (WPIECE / 2));
            };
#pragma unroll
            for (int j = 0; j < NUP - 1; j++) {
                mbar_wait(j ? bar_tail + 8 * j : after(p.zero, bar_tail, w13a, red_dst, ha), 0);
                if (j) load(1, j - 1); else load(0, 0);
                load(0, j + 1);
            }
            LSC(0);
            asm volatile("bar.sync 9, 416;" ::: "memory");
            uint32_t b0[NUP], b1[NUP];
#pragma unroll
            for (int i = 0; i < NUP; i++) {
                b0[i] = b1[i] = 0x3f803f80u;
                asm volatile("{\n.reg .pred q;\nsetp.eq.u32 q, %3, 0;\n@q ld.shared.v2.u32 {%0, %1}, [%2];\n}" : "+r"(b0[i]), "+r"(b1[i]) : "r"(ha + i * 256), "r"(lane & 4) : "memory");
            }
#pragma unroll
            for (int m = 0; m < 2; m++) {
                float cf[2][2][4];
#pragma unroll
                for (int e = 0; e < 4; e++) cf[0][0][e] = cf[0][1][e] = cf[1][0][e] = cf[1][1][e] = 0.f;
#pragma unroll
                for (int i = 0; i < NUP; i++) {
                    if (m && i >= NUP - 2) { mbar_wait(bar_tail + 8 * (i + 1), 0); load(1, i); }
#pragma unroll
                    for (int k = 0; k < 2; k++) mma_bf16(cf[m ? 0 : i & 1][k], aw[m][i][k], b0[i], b1[i]);
                }
#define SEL_(c, e) ((t & 2) ? ((t & 1) ? cf[c][1][e + 2] : cf[c][1][e]) : ((t & 1) ? cf[c][0][e + 2] : cf[c][0][e]))
                if (m == 0) {
                    sts64(red_dst, __float_as_uint(SEL_(0, 0) + SEL_(1, 0)), __float_as_uint(SEL_(0, 1) + SEL_(1, 1)));
                    asm volatile("bar.arrive 8, 288;" ::: "memory");
                } else {
                    sts64(red_dst + 2048, __float_as_uint(SEL_(0, 0)), __float_as_uint(SEL_(0, 1)));
                }
#undef SEL_
            }
            LSC(7);
            asm volatile("bar.arrive 5, 288;" ::: "memory");
        }
        if (is_out) {
            uint32_t w2a = sbase + SM_W2 + (warp * 32 + arow) * 32 + ((ahalf ^ (lane >> 2 & 1)) << 4);
            uint32_t ydst = sbase + SM_HN + ((t & 1) * 8 + (lane >> 2)) * 48 + warp * 4;
            const unsigned char* asrc = p.xa + xa_off(L_ACT, msel) + oh * (NDP * 512) + warp * 64 + t * 16;
            const uint32_t at = tail_time(cfg::T_AAT);
            uint32_t a[NDP][2][4];
            auto load_w2 = [&](int i) {
                mbar_wait(i ? bar_tail + 8 * (NWP + i) : after(p.zero, bar_tail + 8 * NWP, w2a, ydst, asrc, at), 0);
                ldsm_x4_t(a[i][0], w2a + i * PIECE); ldsm_x4_t(a[i][1], w2a + i * PIECE + 512);
            };
            load_w2(0);
            uint4 u[NDP];
            wait_until(at);
            LSC(0);
#pragma unroll
            for (int i = 0; i < NDP; i++) u[i] = in_ld4(asrc + i * 512);
            load_w2(1);
            uint32_t n = 0;
#pragma unroll 1
            while (true) {
                uint32_t m[NDP];
#pragma unroll
                for (int i = 0; i < NDP; i++) m[i] = max(max(u[i].x, u[i].y), max(u[i].z, u[i].w));
                if (!__any_sync(0xffffffffu, max(max(m[0], m[1]), m[2]) == SENT)) break;
#pragma unroll
                for (int i = 0; i < NDP; i++) in_ld4p(asrc + i * 512, u[i], m[i] == SENT);
                if (++n > SPIN_LIMIT) __trap();
            }
            LSC(12);
            if (tid == 96) LST(118);
            float cy[2 * NDP][4];
#pragma unroll
            for (int i = 0; i < NDP; i++) {
#pragma unroll
                for (int e = 0; e < 4; e++) cy[2 * i][e] = cy[2 * i + 1][e] = 0.f;
                if (i == NDP - 1) load_w2(i);
                mma_bf16(cy[2 * i], a[i][0], u[i].x, u[i].y);
                mma_bf16(cy[2 * i + 1], a[i][1], u[i].z, u[i].w);
            }
#define Y_(e) (((cy[0][e] + cy[1][e]) + (cy[2][e] + cy[3][e])) + (cy[4][e] + cy[5][e]))
            const float y = (t & 1) ? Y_(2) : Y_(0);
#undef Y_
            if (t < 2) sts32(ydst, y);
            LSC(13);
            asm volatile("bar.arrive 5, 288;" ::: "memory");
        }
    }
}

typedef CUresult (*EncodeTiledFn)(CUtensorMap*, CUtensorMapDataType, cuuint32_t, void*, const cuuint64_t*, const cuuint64_t*,
                                  const cuuint32_t*, const cuuint32_t*, CUtensorMapInterleave, CUtensorMapSwizzle,
                                  CUtensorMapL2promotion, CUtensorMapFloatOOBfill);

void make_map(EncodeTiledFn fn, CUtensorMap* tm, const void* w, const int (&d)[5], const int (&st)[4], const int (&bx)[5],
              CUtensorMapSwizzle sw, int promo) {
    cuuint64_t dims[5], strides[4];
    cuuint32_t box[5], estr[5];
    for (int i = 0; i < 5; i++) { dims[i] = (cuuint64_t)d[i]; box[i] = (cuuint32_t)bx[i]; estr[i] = 1; }
    for (int i = 0; i < 4; i++) strides[i] = (cuuint64_t)st[i];
    fn(tm, CU_TENSOR_MAP_DATA_TYPE_BFLOAT16, 5, const_cast<void*>(w), dims, strides, box, estr, CU_TENSOR_MAP_INTERLEAVE_NONE, sw,
       (CUtensorMapL2promotion)promo, CU_TENSOR_MAP_FLOAT_OOB_FILL_NONE);
}

}

extern "C" void kernel_launch(void* const* d_in, const int* in_sizes, int n_in, void* d_out, int out_size) {
    (void)in_sizes; (void)n_in; (void)out_size;
    static EncodeTiledFn encode = nullptr;
    static Scratch* scratch = nullptr;
    static unsigned char* xarea = nullptr;
    static double tscale = 1.0;
    if (!encode) {
        void* sp = nullptr;
        cudaGetSymbolAddress(&sp, g_scratch);
        scratch = reinterpret_cast<Scratch*>(sp);
        cudaGetSymbolAddress(&sp, g_xarea);
        xarea = reinterpret_cast<unsigned char*>((reinterpret_cast<uintptr_t>(sp) + XA_ALIGN - 1) / XA_ALIGN * XA_ALIGN);
        void* fn = nullptr;
        cudaDriverEntryPointQueryResult st;
        cudaGetDriverEntryPoint("cuTensorMapEncodeTiled", &fn, cudaEnableDefault, &st);
        encode = reinterpret_cast<EncodeTiledFn>(fn);
        int dev = 0, khz = 0, bits = 0;
        cudaGetDevice(&dev);
        cudaDeviceGetAttribute(&khz, cudaDevAttrMemoryClockRate, dev);
        cudaDeviceGetAttribute(&bits, cudaDevAttrGlobalMemoryBusWidth, dev);
        if (khz > 0 && bits > 0) tscale = (2619000.0 * 5120.0) / ((double)khz * bits);
        cudaFuncSetAttribute(fused_decode_kernel, cudaFuncAttributeMaxDynamicSharedMemorySize, SM_TOTAL);
    }
    KParams p;
    p.x = (const __nv_bfloat16*)d_in[0];
    p.wq = (const __nv_bfloat16*)d_in[3];
    p.out = (__nv_bfloat16*)d_out;
    p.sc = scratch;
    p.xa = xarea;
    p.zero = 0;
    p.t_first = (uint32_t)(4 * cfg::T_FIRST * tscale);
    p.t_step = (uint32_t)(cfg::T_STEP * tscale);
    p.t_smax = (uint32_t)(cfg::T_SMAX * tscale);
    p.t_lat = (uint32_t)(4 * (450 + (cfg::T_LAT - 450) * tscale));
    TMaps tm;
    constexpr int R1 = FF * 2, R2 = D_MODEL * 2;
    make_map(encode, &tm.k, d_in[1], {64, NHEAD * SK * 3, 1, 1, 1}, {128, 128, 128, 128}, {64, 96, 1, 1, 1}, CU_TENSOR_MAP_SWIZZLE_128B, cfg::PROMO_KV);
    make_map(encode, &tm.v, d_in[2], {64, NHEAD * SK * 3, 1, 1, 1}, {128, 128, 128, 128}, {64, 96, 1, 1, 1}, CU_TENSOR_MAP_SWIZZLE_128B, cfg::PROMO_KV);
    make_map(encode, &tm.wo, d_in[4], {D_MODEL, NHEAD * DH, 1, 1, 1}, {R2, R2, R2, R2}, {64, 128, 1, 1, 1}, CU_TENSOR_MAP_SWIZZLE_128B, cfg::PROMO_WO);
    make_map(encode, &tm.w1, d_in[6], {FF, 2, 4, 2, 40}, {R1, 4 * R1, 2 * R1, 16 * R1}, {32, 2, 4, 2, 8}, CU_TENSOR_MAP_SWIZZLE_64B, cfg::PROMO_W13);
    make_map(encode, &tm.w3, d_in[7], {FF, 2, 4, 2, 40}, {R1, 4 * R1, 2 * R1, 16 * R1}, {32, 2, 4, 2, 8}, CU_TENSOR_MAP_SWIZZLE_64B, cfg::PROMO_W13);
    make_map(encode, &tm.w2, d_in[8], {D_MODEL, FF, 1, 1, 1}, {R2, R2, R2, R2}, {16, 256, 1, 1, 1}, CU_TENSOR_MAP_SWIZZLE_32B, cfg::PROMO_W2);
    fused_decode_kernel<<<NCTA, NTHREADS, SM_TOTAL, cudaStreamPerThread>>>(p, tm);
}
```

```cpp
#include <cuda_runtime.h>
#include <cuda_bf16.h>
#include <cuda.h>
#include <stdint.h>
#include <math.h>

namespace {

constexpr int D_MODEL = 640;
constexpr int NHEAD = 32;
constexpr int DH = 192;
constexpr int SK = 32768;
constexpr int WIN = 4096;
constexpr int FF = 1536;

constexpr int NCTA = 128;
constexpr int NCONS = 256;
constexpr int NTHREADS = NCONS + 256;
constexpr int ROW_BYTES = DH * 2;
constexpr int TILE_BYTES = 32 * ROW_BYTES;
constexpr int NSLOT = 16;
constexpr int NQT = 5;
constexpr int QSLOT = NSLOT - NQT;
constexpr int NWO = 60;
constexpr int NG = 6;
constexpr int NFFN = 48;
constexpr int NWP = 8;
constexpr int NUP = 5;
constexpr int WPIECE = 16384;
constexpr int NDP = 3;
constexpr int PIECE = 8192;
constexpr int NTAIL = NWP + NDP;
constexpr int N_TAIL0 = 2 * NHEAD;

#define CFG(name, value) constexpr int name = value
#define CFG_OVERRIDE
namespace cfg_default {
CFG(T_FIRST, 1850);
CFG(T_STEP, 1906);
CFG(T_SMAX, 1940);
CFG(CAP, 5);
CFG(MN, 12);
CFG(MA, 4);
CFG(MB, 40);
CFG(ADAPT, 60);
CFG(T_LAT, 1230);
CFG(T_WO, 296);
CFG(T_GAP, 95);
CFG(T_UP, 240);
CFG(T_UP2, 120);
CFG(T_W2AT, 1320);
CFG(T_W2, 200);
CFG(T_HAT, 1130);
CFG(T_RESAT, 1750);
CFG(T_AAT, 2420);
CFG(KEEP_AT, 65);
CFG(KEEP, 150);
CFG(HCOPY, 1);
CFG(QDELAY, 1200);
CFG(QDELAY2, 900);
CFG(QSLEEP, 400);
CFG(PDELAY, 2500);
CFG(PDELAY_LAST, 250);
CFG(PDELAY_STEP, 650);
CFG(PREPART, 3);
CFG(RBDELAY, 5000);
CFG(NPROBE, 10);
CFG(VOTES, 3);
CFG(PROMO_KV, 2);
CFG(PROMO_WO, 2);
CFG(PROMO_W13, 2);
CFG(PROMO_W2, 2);
CFG(BOUNDED_MBAR, 0);
}
namespace cfg { using namespace cfg_default; CFG_OVERRIDE }

constexpr int SM_RING = 0;
constexpr int SM_W2 = NWP * WPIECE;
constexpr int SM_Q = SM_RING + NSLOT * TILE_BYTES;
constexpr int SM_RED = SM_Q + NHEAD * ROW_BYTES;
constexpr int SM_HN = SM_RED + 4096;
constexpr int SM_STAT = SM_HN + D_MODEL * 2;
constexpr int SM_MISC = SM_STAT + 256;
constexpr int SM_BAR = SM_MISC + 128;
constexpr int SM_TOTAL = SM_BAR + 512;
static_assert(SM_TOTAL <= 232448, "shared memory");

struct __align__(128) Scratch {
    uint4 part[NHEAD * 4 * NCTA * 8];
    uint64_t q1[NHEAD * 4 * DH];
    uint4 q2[NHEAD * 32];
    uint32_t epoch;
    uint32_t pad;
    unsigned long long pace[2];
};
__device__ Scratch g_scratch;
constexpr int XA_ALIGN = 1 << 20;
constexpr uint32_t SENT = 0xffffffffu;
constexpr int L_GATHER = 0;
constexpr int HCOPY_BYTES = NG * D_MODEL * 2;
constexpr int L_O = 9 * 4096;
constexpr int L_ACT = 30 * 4096;
constexpr int L_PROBE = 32 * 4096;
constexpr int L_PART = 64 * 4096;
static_assert(2 * (L_PART + 65536) <= XA_ALIGN, "");
__device__ unsigned char g_xarea[2 * XA_ALIGN];
__device__ __forceinline__ uint32_t xa_off(uint32_t l, uint32_t side) {
    const uint32_t k = l >> 12;
    return (2 * k + ((side ^ k ^ (k >> 3) ^ (k >> 4) ^ (k >> 6)) & 1)) * 4096 + (l & 4095);
}

__device__ __forceinline__ uint32_t o_off(uint32_t r) { return L_O + (r >> 7) % NG * 2048 + (r >> 7) / NG * 256 + (r & 127) * 2; }

#define LST(i) do { } while (0)
#define LSC(i) do { } while (0)
#define LSCD(i, v) do { } while (0)
constexpr uint32_t SPIN_LIMIT = cfg::BOUNDED_MBAR ? 1u << 14 : 1u << 22;

__device__ __forceinline__ uint32_t now_q() { uint32_t t; asm volatile("mov.u32 %0, %globaltimer_lo;" : "=r"(t)); return t * 4; }
__device__ __forceinline__ void wait_until(uint32_t due) {
#pragma unroll 1
    for (int n = 0; n < 4096 && (int)(now_q() - due) < 0; n++) { }
}
__device__ __forceinline__ void sleep_until(uint32_t due) {
#pragma unroll 1
    for (int n = 0; n < 4096 && (int)(now_q() - due) < 0; n++) __nanosleep(200);
}
__device__ __forceinline__ uint32_t smem_u32(const void* p) { return (uint32_t)__cvta_generic_to_shared(p); }
__device__ __forceinline__ void mbar_init(uint32_t bar, uint32_t cnt) {
    asm volatile("mbarrier.init.shared::cta.b64 [%0], %1;" ::"r"(bar), "r"(cnt) : "memory");
}
__device__ __forceinline__ void mbar_expect_tx(uint32_t bar, uint32_t bytes) {
    asm volatile("mbarrier.arrive.expect_tx.shared::cta.b64 _, [%0], %1;" ::"r"(bar), "r"(bytes) : "memory");
}
__device__ __forceinline__ void mbar_arrive(uint32_t bar) {
    asm volatile("mbarrier.arrive.shared::cta.b64 _, [%0];" ::"r"(bar) : "memory");
}
__device__ __forceinline__ bool mbar_test(uint32_t bar, uint32_t parity) {
    uint32_t ok;
    asm volatile("{\n.reg .pred p;\nmbarrier.test_wait.parity.shared::cta.b64 p, [%1], %2;\nselp.u32 %0, 1, 0, p;\n}"
                 : "=r"(ok) : "r"(bar), "r"(parity) : "memory");
    return ok;
}
__device__ __forceinline__ bool mbar_try(uint32_t bar, uint32_t parity) {
    uint32_t ok;
    asm volatile("{\n.reg .pred p;\nmbarrier.try_wait.parity.shared::cta.b64 p, [%1], %2;\nselp.u32 %0, 1, 0, p;\n}"
                 : "=r"(ok) : "r"(bar), "r"(parity) : "memory");
    return ok;
}
__device__ __forceinline__ void mbar_wait(uint32_t bar, uint32_t parity) {
    if (cfg::BOUNDED_MBAR) {
        uint32_t n = 0;
        while (!mbar_try(bar, parity)) if (++n > SPIN_LIMIT) __trap();
    } else {
        asm volatile("{\n.reg .pred p;\nW_%=:\nmbarrier.try_wait.parity.shared::cta.b64 p, [%0], %1;\n@!p bra W_%=;\n}" ::"r"(bar), "r"(parity) : "memory");
    }
}
__device__ __forceinline__ void tma_tile(uint32_t dst, const CUtensorMap* tm, int c1, uint32_t bar, uint64_t pol) {
    asm volatile("cp.async.bulk.tensor.5d.shared::cluster.global.mbarrier::complete_tx::bytes.L2::cache_hint [%0], [%1, {%4, %3, %4, %4, %4}], [%2], %5;"
                 ::"r"(dst), "l"(reinterpret_cast<uint64_t>(tm)), "r"(bar), "r"(c1), "r"(0), "l"(pol) : "memory");
}
__device__ __forceinline__ void tma_5d(uint32_t dst, const CUtensorMap* tm, int c0, int c1, int c2, int c4, uint32_t bar) {
    asm volatile("cp.async.bulk.tensor.5d.shared::cluster.global.mbarrier::complete_tx::bytes [%0], [%1, {%3, %4, %5, %7, %6}], [%2];"
                 ::"r"(dst), "l"(reinterpret_cast<uint64_t>(tm)), "r"(bar), "r"(c0), "r"(c1), "r"(c2), "r"(c4), "r"(0) : "memory");
}
__device__ __forceinline__ uint32_t bits(uint32_t v) { return v; }
__device__ __forceinline__ uint32_t bits(float v) { return __float_as_uint(v); }
__device__ __forceinline__ uint32_t bits(const void* v) { return (uint32_t)(uintptr_t)v ^ (uint32_t)((uintptr_t)v >> 32); }
template <class... T> __device__ __forceinline__ uint32_t after(uint32_t zero, uint32_t bar, T... v) { return bar | ((bits(v) ^ ...) & zero); }
__device__ __forceinline__ void sts32(uint32_t a, float v) { asm volatile("st.shared.f32 [%0], %1;" ::"r"(a), "f"(v) : "memory"); }
__device__ __forceinline__ void sts64(uint32_t a, uint32_t x, uint32_t y) { asm volatile("st.shared.v2.u32 [%0], {%1, %2};" ::"r"(a), "r"(x), "r"(y) : "memory"); }
__device__ __forceinline__ void cons_sync() { asm volatile("bar.sync 1, 256;" ::: "memory"); }

__device__ __forceinline__ uint4 lds128(uint32_t a) {
    uint4 v;
    asm volatile("ld.shared.v4.u32 {%0,%1,%2,%3}, [%4];" : "=r"(v.x), "=r"(v.y), "=r"(v.z), "=r"(v.w) : "r"(a));
    return v;
}
__device__ __forceinline__ float4 lds128f(uint32_t a) {
    float4 v;
    asm volatile("ld.shared.v4.f32 {%0,%1,%2,%3}, [%4];" : "=f"(v.x), "=f"(v.y), "=f"(v.z), "=f"(v.w) : "r"(a) : "memory");
    return v;
}
__device__ __forceinline__ float2 lds64f(uint32_t a) {
    float2 v;
    asm volatile("ld.shared.v2.f32 {%0,%1}, [%2];" : "=f"(v.x), "=f"(v.y) : "r"(a) : "memory");
    return v;
}
__device__ __forceinline__ uint32_t lds32(uint32_t a) {
    uint32_t v;
    asm volatile("ld.shared.u32 %0, [%1];" : "=r"(v) : "r"(a));
    return v;
}
__device__ __forceinline__ void ldsm_x4(uint32_t* r, uint32_t a) {
    asm volatile("ldmatrix.sync.aligned.m8n8.x4.shared.b16 {%0,%1,%2,%3}, [%4];"
                 : "=r"(r[0]), "=r"(r[1]), "=r"(r[2]), "=r"(r[3]) : "r"(a));
}
__device__ __forceinline__ void ldsm_x4_t(uint32_t* r, uint32_t a) {
    asm volatile("ldmatrix.sync.aligned.m8n8.x4.trans.shared.b16 {%0,%1,%2,%3}, [%4];"
                 : "=r"(r[0]), "=r"(r[1]), "=r"(r[2]), "=r"(r[3]) : "r"(a));
}
__device__ __forceinline__ void mma_bf16(float* c, const uint32_t* a, uint32_t b0, uint32_t b1) {
    asm volatile("mma.sync.aligned.m16n8k16.row.col.f32.bf16.bf16.f32 {%0,%1,%2,%3}, {%4,%5,%6,%7}, {%8,%9}, {%0,%1,%2,%3};"
                 : "+f"(c[0]), "+f"(c[1]), "+f"(c[2]), "+f"(c[3]) : "r"(a[0]), "r"(a[1]), "r"(a[2]), "r"(a[3]), "r"(b0), "r"(b1));
}
__device__ __forceinline__ float bf_lo(uint32_t u) { return __uint_as_float(u << 16); }
__device__ __forceinline__ float bf_hi(uint32_t u) { return __uint_as_float(u & 0xffff0000u); }
__device__ __forceinline__ uint32_t pack_bf(float hi, float lo) { uint32_t r; asm("cvt.rn.bf16x2.f32 %0, %1, %2;" : "=r"(r) : "f"(hi), "f"(lo)); return r; }
__device__ __forceinline__ float bfr(float x) { return __uint_as_float(pack_bf(x, 0.f)); }

__device__ __forceinline__ uint64_t pk(float v, uint32_t tag) { return ((uint64_t)tag << 32) | (uint64_t)__float_as_uint(v); }
__device__ __forceinline__ void ll_st1(uint64_t* p, float a, uint32_t tag) {
    asm volatile("st.relaxed.gpu.global.b64 [%0], %1;" ::"l"(p), "l"(pk(a, tag)) : "memory");
}
__device__ __forceinline__ uint4 ll_ld2(const uint4* p) {
    uint4 v;
    asm volatile("{\n.reg .b64 a, b;\nld.relaxed.gpu.global.v2.b64 {a, b}, [%4];\nmov.b64 {%0, %1}, a;\nmov.b64 {%2, %3}, b;\n}"
                 : "=r"(v.x), "=r"(v.y), "=r"(v.z), "=r"(v.w) : "l"(p) : "memory");
    return v;
}
__device__ __forceinline__ uint32_t in_word(float v) {
    uint32_t r;
    asm("min.u32 %0, %1, 0xfffffffe;" : "=r"(r) : "r"(__float_as_uint(v)));
    return r;
}
__device__ __forceinline__ void in_st1(void* p, float v) {
    asm volatile("st.relaxed.gpu.global.u32 [%0], %1;" ::"l"(p), "r"(in_word(v)) : "memory");
}
__device__ __forceinline__ void in_st4(void* p, uint32_t a, uint32_t b, uint32_t c, uint32_t d) {
    asm volatile("st.relaxed.gpu.global.v4.u32 [%0], {%1, %2, %3, %4};" ::"l"(p), "r"(a), "r"(b), "r"(c), "r"(d) : "memory");
}
__device__ __forceinline__ uint32_t in_ld1(const void* p) {
    uint32_t v;
    asm volatile("ld.relaxed.gpu.global.u32 %0, [%1];" : "=r"(v) : "l"(p) : "memory");
    return v;
}
__device__ __forceinline__ uint4 in_ld4(const void* p) {
    uint4 v;
    asm volatile("ld.relaxed.gpu.global.v4.u32 {%0, %1, %2, %3}, [%4];" : "=r"(v.x), "=r"(v.y), "=r"(v.z), "=r"(v.w) : "l"(p) : "memory");
    return v;
}
__device__ __forceinline__ void in_ld2p(const void* p, uint2& v, bool on) {
    asm volatile("{\n.reg .pred q;\nsetp.ne.u32 q, %3, 0;\n@q ld.relaxed.gpu.global.v2.u32 {%0, %1}, [%2];\n}"
                 : "+r"(v.x), "+r"(v.y) : "l"(p), "r"((uint32_t)on) : "memory");
}
__device__ __forceinline__ bool in_ok(const uint2& v) { return max(v.x, v.y) != SENT; }
__device__ __forceinline__ void in_ld4p(const void* p, uint4& v, bool on) {
    asm volatile("{\n.reg .pred q;\nsetp.ne.u32 q, %5, 0;\n@q ld.relaxed.gpu.global.v4.u32 {%0, %1, %2, %3}, [%4];\n}"
                 : "+r"(v.x), "+r"(v.y), "+r"(v.z), "+r"(v.w) : "l"(p), "r"((uint32_t)on) : "memory");
}
__device__ __forceinline__ void pkt_st(uint4* p, uint32_t x, uint32_t y, uint32_t z, uint32_t w) {
    asm volatile("{\n.reg .b128 t;\n.reg .b64 a, b;\nmov.b64 a, {%1, %2};\nmov.b64 b, {%3, %4};\nmov.b128 t, {a, b};\nst.relaxed.gpu.global.b128 [%0], t;\n}"
                 ::"l"(p), "r"(x), "r"(y), "r"(z), "r"(w) : "memory");
}
__device__ __forceinline__ void pkt_ldp(const uint4* p, uint4& v, bool on) {
    asm volatile("{\n.reg .pred q;\n.reg .b128 t;\n.reg .b64 a, b;\nsetp.ne.u32 q, %5, 0;\nmov.b64 a, {%0, %1};\nmov.b64 b, {%2, %3};\nmov.b128 t, {a, b};\n"
                 "@q ld.relaxed.gpu.global.b128 t, [%4];\nmov.b128 {a, b}, t;\nmov.b64 {%0, %1}, a;\nmov.b64 {%2, %3}, b;\n}"
                 : "+r"(v.x), "+r"(v.y), "+r"(v.z), "+r"(v.w) : "l"(p), "r"((uint32_t)on) : "memory");
}

__device__ __forceinline__ float sqrt_fast(float x) { float r; asm("sqrt.approx.ftz.f32 %0, %1;" : "=f"(r) : "f"(x)); return r; }
__device__ __forceinline__ float rcp_fast(float x) { float r; asm("rcp.approx.ftz.f32 %0, %1;" : "=f"(r) : "f"(x)); return r; }
__device__ __forceinline__ float ex2(float x) { float r; asm("ex2.approx.ftz.f32 %0, %1;" : "=f"(r) : "f"(x)); return r; }
constexpr float L2E = 1.4426950408889634f;
__device__ __forceinline__ void ln_sums(const uint2* v, float& t1, float& t2) {
    float s1[5], s2[5];
#pragma unroll
    for (int i = 0; i < 5; i++) {
        const float a0 = bf_lo(v[i].x), a1 = bf_hi(v[i].x), a2 = bf_lo(v[i].y), a3 = bf_hi(v[i].y);
        s1[i] = (a0 + a1) + (a2 + a3);
        s2[i] = fmaf(a0, a0, a1 * a1) + fmaf(a2, a2, a3 * a3);
    }
    t1 = ((s1[0] + s1[1]) + (s1[2] + s1[3])) + s1[4]; t2 = ((s2[0] + s2[1]) + (s2[2] + s2[3])) + s2[4];
#pragma unroll
    for (int o = 16; o > 0; o >>= 1) { t1 += __shfl_xor_sync(0xffffffffu, t1, o); t2 += __shfl_xor_sync(0xffffffffu, t2, o); }
}
__device__ __forceinline__ void ln_finish(float t1, float t2, float& mean_b, float& inv_den) {
    const float mean = t1 * (1.0f / D_MODEL);
    const float var = fmaxf(fmaf(-mean, mean, t2 * (1.0f / D_MODEL)), 0.f);
    mean_b = bfr(mean);
    inv_den = rcp_fast(bfr(sqrt_fast(bfr(bfr(var) + 1e-5f))));
}

struct KParams {
    const __nv_bfloat16* wq;
    uint32_t t_first;
    uint32_t t_step;
    const __nv_bfloat16* x;
    Scratch* sc;
    unsigned char* xa;
    __nv_bfloat16* out;
    uint32_t t_smax;
    uint32_t t_lat;
    uint32_t zero;
};
struct TMaps { CUtensorMap k, v, wo, w1, w3, w2; };

__global__ void __launch_bounds__(NTHREADS, 1)
fused_decode_kernel(const KParams p, const __grid_constant__ TMaps tm) {
    extern __shared__ __align__(1024) unsigned char smem[];
    const uint32_t sbase = smem_u32(smem);
    const int tid = threadIdx.x;
    const int b = blockIdx.x;
    const int head = b >> 2, sp = b & 3;
    {
        if (tid < 192) {
            const uint32_t rg = tid / 24, ch = tid - rg * 24;
            const char* src = reinterpret_cast<const char*>(p.wq) + (uint32_t)(sp * 160 * (NHEAD * DH * 2) + head * ROW_BYTES + rg * (NHEAD * DH * 2) + ch * 16);
            uint32_t dst = sbase + SM_RING + QSLOT * TILE_BYTES + ((tid ^ (tid >> 3 & 7)) << 4);
#pragma unroll 4
            for (int i = 0; i < 20; i++) {
                asm volatile("cp.async.cg.shared.global [%0], [%1], 16;" ::"r"(dst), "l"(src) : "memory");
                dst += 8 * ROW_BYTES;
                src += (size_t)8 * (NHEAD * DH * 2);
            }
        }
    }
    const int warp = __shfl_sync(0xffffffffu, tid >> 5, 0), lane = tid & 31;
    const int rr = !(b & 1) ? b >> 1 : (b & 15) < 12 ? (b >> 4) * 6 + (b >> 1 & 7) : NFFN + (b >> 4) * 2 + (b >> 1 & 1);
    const bool is_wo = !(b & 1) && rr < NWO, is_ffn = (b & 1) && rr < NFFN, is_out = !is_ffn;
    const int og = (rr >> 2) + (b & 1) * 4, oh = og >= 10, oq = (og - 10 * oh) * 4 + (rr & 3);
    const int kg = min(rr / 10, NG - 1), ng = rr % 10;
    const uint32_t bar_full = sbase + SM_BAR;
    const uint32_t bar_empty = sbase + SM_BAR + 128;
    const uint32_t bar_tail = sbase + SM_BAR + 256;
    const uint32_t bar_set = bar_tail + 8 * NTAIL;
    const uint32_t bar_pace = bar_set + 8;
    const uint32_t bar_q = bar_set + 16;
    const uint32_t bar_part = bar_set + 24;
    volatile uint32_t* s_pace = reinterpret_cast<volatile uint32_t*>(smem + SM_MISC + 64);
    auto tail_time = [&](int t) { return s_pace[0] + (s_pace[1] * (((N_TAIL0 - cfg::ADAPT) * 478 + NWP * cfg::T_WO + t) * 256 / 478) >> 8); };

    if (warp == 8) {
        const uint32_t c_start = now_q();
        if (lane >= 1 && lane <= 6) asm volatile("prefetch.tensormap [%0];" ::"l"(reinterpret_cast<uint64_t>(&tm.k + (lane - 1))) : "memory");
        uint64_t pol_stream;
        asm volatile("createpolicy.fractional.L2::evict_first.b64 %0, 1.0;" : "=l"(pol_stream));
        if (lane == 0) {
#pragma unroll 1
            for (int i = 0; i < NSLOT; i++) { mbar_init(bar_full + 8 * i, 1); mbar_init(bar_empty + 8 * i, 1); }
#pragma unroll 1
            for (int i = 0; i < NTAIL + 4; i++) mbar_init(bar_tail + 8 * i, i == NTAIL + 2 ? 4 : 1);
            asm volatile("fence.mbarrier_init.release.cluster;" ::: "memory");
        }
        __syncwarp();
        asm volatile("bar.arrive 2, 288;" ::: "memory");
        asm volatile("bar.arrive 3, 64;" ::: "memory");
        asm volatile("bar.arrive 4, 64;" ::: "memory");
        if (is_ffn) asm volatile("bar.arrive 10, 192;" ::: "memory");
        if (lane == 0) {
            uint32_t due = c_start + p.t_first, step = p.t_step;
#pragma unroll 1
            for (int n = 0; n < N_TAIL0; n++) {
                const int slot = n & (NSLOT - 1);
                const int use = (n >> 4) + (slot >= QSLOT);
                if (n >= cfg::CAP) mbar_wait(bar_full + 8 * ((n - cfg::CAP) & (NSLOT - 1)), ((n - cfg::CAP) >> 4) & 1);
                if (use >= 1) mbar_wait(bar_empty + 8 * slot, (use - 1) & 1);
                if (n == cfg::ADAPT) { mbar_wait(bar_pace, 0); due = s_pace[0]; step = s_pace[1]; }
                const uint32_t full = bar_full + 8 * slot;
                mbar_expect_tx(full, TILE_BYTES);
                wait_until(due);
                LST(128 + n);
                tma_tile(sbase + SM_RING + slot * TILE_BYTES, &tm.k + (n & 1), ((n >> 1) * SK + (SK - WIN) + b * 32) * 3, full, pol_stream);
                due += step;
            }
            int rel = 0;
            auto released = [&](int end) {
#pragma unroll 1
                for (; rel * TILE_BYTES < end; rel++) mbar_wait(bar_empty + 8 * rel, rel < QSLOT);
            };
            const uint32_t t_wo = step * (cfg::T_WO * 4096 / 478) >> 12;
            if (is_wo) {
#pragma unroll 1
                for (int j = 0; j < NWP; j++) {
                    released((j + 1) * WPIECE);
                    mbar_expect_tx(bar_tail + 8 * j, WPIECE);
                    wait_until(due);
                    LST(128 + N_TAIL0 + j);
                    tma_5d(sbase + j * WPIECE, &tm.wo, ng * 64, j * (NG * 128) + kg * 128, 0, 0, bar_tail + 8 * j);
                    due += t_wo;
                }
            } else {
                due += NWP * t_wo;
            }
            due += 4 * cfg::T_GAP;
            if (is_out) {
                due += step * (cfg::T_W2AT * 4096 / 478) >> 12;
                released(SM_W2 + NDP * PIECE);
#pragma unroll
                for (int j = 0; j < NDP; j++) mbar_expect_tx(bar_tail + 8 * (NWP + j), PIECE);
                sleep_until(due - 4 * 400);
#pragma unroll
                for (int j = 0; j < NDP; j++) {
                    wait_until(due);
                    tma_5d(sbase + SM_W2 + j * PIECE, &tm.w2, oq * 16, (oh * NDP + j) * 256, 0, 0, bar_tail + 8 * (NWP + j));
                    LST(128 + N_TAIL0 + NWP + j);
                    due += step * (cfg::T_W2 * 4096 / 478) >> 12;
                }
            } else if (is_ffn) {
                released(NUP * WPIECE);
#pragma unroll
                for (int j = 0; j <= NUP; j++) mbar_expect_tx(bar_tail + 8 * j, j < NUP - 1 ? WPIECE : WPIECE / 2);
                sleep_until(due - 4 * 400);
#pragma unroll
                for (int j = 0; j <= NUP; j++) {
                    const uint32_t full = bar_tail + 8 * j;
                    wait_until(due);
#pragma unroll
                    for (int e = min(2 * j, j + NUP - 1); e < min(2 * j + 2, j + NUP); e++)
                        tma_5d(sbase + e * (WPIECE / 2), e < NUP ? &tm.w1 : &tm.w3, rr * 32, 0, 0, e % NUP * 8, full);
                    LST(128 + N_TAIL0 + j);
                    due += step * ((j < NUP - 1 ? cfg::T_UP : cfg::T_UP2) * 4096 / 478) >> 12;
                }
            }
        }
    } else if (warp == 10) {
        asm volatile("bar.sync 4, 64;" ::: "memory");
        if (lane == 0) {
            uint32_t epoch0;
            asm volatile("ld.relaxed.gpu.global.u32 %0, [%1];" : "=r"(epoch0) : "l"(&p.sc->epoch) : "memory");
            constexpr int MN = cfg::MN;
            const uint32_t t0 = now_q();
            uint32_t sa = 0, sb = 0;
#pragma unroll 1
            for (int n = 0; n < cfg::MB + MN; n++) {
#pragma unroll 1
                for (int k = 0; k < 256 && !mbar_try(bar_full + 8 * (n & (NSLOT - 1)), (n >> 4) & 1); k++) { }
                const uint32_t t = now_q() - t0;
                LST(n);
                if ((uint32_t)(n - cfg::MA) < MN) sa += t;
                if (n >= cfg::MB) sb += t;
            }
            const uint32_t mb = t0 + sb / MN;
            unsigned long long* pace = p.sc->pace + ((epoch0 + 1) & 1);
            mbar_wait(bar_set, 0);
            asm volatile("red.relaxed.gpu.global.add.u64 [%0], %1;" ::"l"(pace), "l"((unsigned long long)mb << 32 | min((sb - sa) / (4 * MN), 0xffffu) << 8 | 1) : "memory");
            if (b == 0) p.sc->pace[epoch0 & 1] = 0;
            unsigned long long v;
            uint32_t n = 0, cnt;
#pragma unroll 1
            do {
                __nanosleep(n ? 200 : 1000);
                asm volatile("ld.relaxed.gpu.global.u64 %0, [%1];" : "=l"(v) : "l"(pace) : "memory");
                cnt = (uint32_t)v & 0xff;
                if (++n > SPIN_LIMIT) __trap();
            } while (cnt < NCTA);
            const uint32_t step = min(max(((uint32_t)v >> 8) / (NCTA / 4 * (cfg::MB - cfg::MA)), p.t_step), p.t_smax);
            s_pace[0] = mb + (int)((uint32_t)(v >> 32) - NCTA * mb) / NCTA + step * (2 * (cfg::ADAPT - cfg::MB) - (MN - 1)) / 2 - p.t_lat;
            s_pace[1] = step;
            mbar_arrive(bar_pace);
            LST(89);
        }
    } else if (warp == 9) {
        const uint32_t c_start = now_q();
        uint32_t epoch0;
        asm volatile("ld.relaxed.gpu.global.u32 %0, [%1];" : "=r"(epoch0) : "l"(&p.sc->epoch) : "memory");
        sleep_until(c_start + p.t_first);
        unsigned char* slot[2];
        slot[0] = p.xa + xa_off(o_off(b * 48 + (lane % 6) * 8), lane / 6 & 1);
        slot[1] = p.xa + (is_wo ? xa_off(L_GATHER + (lane >> 4) * HCOPY_BYTES + (kg * D_MODEL + ng * 64 + (lane & 7) * 8) * 2, lane >> 3 & 1)
                                : xa_off(L_ACT + rr * 64 + (lane & 3) * 16, lane >> 2 & 1));
        const int n2 = is_wo ? 16 * cfg::HCOPY : is_ffn ? 8 : 0;
#pragma unroll
        for (int i = 0; i < 2; i++) if (lane < (i ? n2 : 12)) in_st4(slot[i], SENT, SENT, SENT, SENT);
#pragma unroll
        for (int i = 2; i <= cfg::PREPART; i++) pkt_st(p.sc->part + (((NHEAD - i) * 4 + (lane & 3)) * NCTA + b) * 8 + (lane >> 2), 0, 0, 0, epoch0 & 3);
#pragma unroll
        for (int i = 0; i < 2; i++) pkt_st(reinterpret_cast<uint4*>(p.xa + xa_off(L_PART + (((lane & 3) * NCTA + b) * 8 + (lane >> 2)) * 16, i)), 0, 0, 0, epoch0 & 3);
        unsigned char* probe = p.xa + xa_off(L_PROBE + b * 1024 + (lane >> 1 & 7) * 128 + (lane & 1) * 16, lane >> 4);
        in_st4(probe, SENT, SENT, SENT, SENT);
        const bool clr = is_out && !oh && lane < 2;
        if (clr) in_st4(p.out + oq * 16 + lane * 8, 0, 0, 0, 0);
        sleep_until(now_q() + 4 * cfg::RBDELAY + b * 60);
        uint32_t acc = SENT;
#pragma unroll
        for (int i = 0; i < 2; i++) if (lane < (i ? n2 : 12)) acc &= in_ld1(slot[i]);
        if (clr) acc &= ~in_ld1(p.out + oq * 16 + lane * 8);
        if (__any_sync(0xffffffffu, acc != SENT)) __trap();
        int vote = 0;
        uint32_t lat[2] = {0, 0};
#pragma unroll 1
        for (int r = 0; r <= cfg::NPROBE && abs(vote) < cfg::VOTES; r++) {
            __nanosleep(300);
            uint32_t d[2];
#pragma unroll
            for (int i = 0; i < 2; i++) {
                const uint32_t c0 = (uint32_t)clock();
                if (__any_sync(0xffffffffu, in_ld1(p.xa + xa_off(L_PROBE + b * 1024 + (lane & 7) * 128, i)) != SENT)) __trap();
                d[i] = (uint32_t)clock() - c0;
                if (r) lat[i] += min(d[i], 1500u);
            }
            if (r) vote = __shfl_sync(0xffffffffu, vote + (d[1] < d[0]) - (d[0] < d[1]), 0);
        }
        const uint32_t sel = vote ? vote > 0 : lat[1] < lat[0];
        const uint32_t tag = epoch0 + 1;
        asm volatile("bar.sync 3, 64;" ::: "memory");
        if (lane == 0) { s_pace[2] = sel; mbar_arrive(bar_set); }
        {
            mbar_wait(bar_pace, 0);
            sleep_until(s_pace[0] + (cfg::KEEP_AT - cfg::ADAPT) * s_pace[1]);
            const uint32_t t_res = tail_time(cfg::T_RESAT);
            float c[4] = {0.f, 0.f, 0.f, 0.f};
            const uint32_t z[4] = {p.zero, p.zero, p.zero, p.zero};
            uint32_t n = 0;
#pragma unroll 1
            do {
                mma_bf16(c, z, p.zero, p.zero);
                __nanosleep(cfg::KEEP);
                n += 1 + __float_as_uint(c[0]);
            } while (!__all_sync(0xffffffffu, is_ffn ? mbar_test(bar_tail, 0) : (int)(now_q() - t_res) >= 0) && n < SPIN_LIMIT);
            if (is_ffn) {
                unsigned char* adst = p.xa + xa_off(L_ACT + rr * 64 + (lane >> 3) * 16 + (lane & 3) * 4, lane >> 2 & 1);
                uint32_t src = sbase + SM_RED + lane * 8;
                asm volatile("bar.sync %0, 192;" ::"r"(after(p.zero, 11, adst, src)) : "memory");
                float t1, t2, mean_b, inv_den;
                {
                    float q1[5], q2[5];
#pragma unroll
                    for (int i = 0; i < 5; i++) {
                        const float4 a = lds128f(sbase + SM_STAT + i * 48), c = lds128f(sbase + SM_STAT + i * 48 + 16), d = lds128f(sbase + SM_STAT + i * 48 + 32);
                        q2[i] = ((a.x + a.y) + (a.z + a.w)) + ((c.x + c.y) + (c.z + c.w));
                        q1[i] = (d.x + d.y) + (d.z + d.w);
                    }
                    t1 = ((q1[0] + q1[1]) + (q1[2] + q1[3])) + q1[4]; t2 = ((q2[0] + q2[1]) + (q2[2] + q2[3])) + q2[4];
                }
                ln_finish(t1, t2, mean_b, inv_den);
                float2 r[8];
#define S_(c) (((r[0].c + r[1].c) + (r[2].c + r[3].c)) + ((r[4].c + r[5].c) + (r[6].c + r[7].c)))
                asm volatile("bar.sync %0, 288;" ::"r"(after(p.zero, 8, mean_b, inv_den)) : "memory");
#pragma unroll
                for (int i = 0; i < 8; i++) r[i] = lds64f(src + i * 256);
                const float gate = bfr(fmaf(-mean_b, S_(y), S_(x)) * inv_den);
                const float silu = bfr(__fdividef(gate, 1.0f + ex2(-gate * L2E)));
                asm volatile("bar.sync %0, 288;" ::"r"(after(p.zero, 5, silu)) : "memory");
#pragma unroll
                for (int i = 0; i < 8; i++) r[i] = lds64f(src + 2048 + i * 256);
                const float act = silu * bfr(fmaf(-mean_b, S_(y), S_(x)) * inv_den);
#undef S_
                const float oth = __shfl_xor_sync(0xffffffffu, act, 4);
                in_st1(adst, __uint_as_float((lane & 4) ? pack_bf(act, oth) : pack_bf(oth, act)));
                if (lane == 0) LST(110);
            }
            if (is_out) {
                const int col = oq * 16 + (lane & 15);
                float res = 0.f;
                if (!oh) {
                    uint32_t u[NG], xv;
                    asm volatile("ld.global.nc.u16 %0, [%1];" : "=r"(xv) : "l"(p.x + col));
                    n = 0;
#pragma unroll 1
                    do {
#pragma unroll
                        for (int i = 0; i < NG; i++) u[i] = in_ld1(p.xa + xa_off(L_GATHER + rr % cfg::HCOPY * HCOPY_BYTES + (i * D_MODEL + (col & ~1)) * 2, sel));
                        if (++n > SPIN_LIMIT) __trap();
                    } while (__any_sync(0xffffffffu, max(max(max(u[0], u[1]), max(u[2], u[3])), max(u[4], u[5])) == SENT));
                    if (b == 0 && lane == 0) p.sc->epoch = tag;
#define F_(i) ((lane & 1) ? bf_hi(u[i]) : bf_lo(u[i]))
                    res = bfr(bf_lo(xv) + bfr(((F_(0) + F_(1)) + (F_(2) + F_(3))) + (F_(4) + F_(5))));
#undef F_
                }
                mma_bf16(c, z, p.zero, p.zero);
                mbar_wait(after(p.zero, bar_tail + 8 * NWP, c[0]), 0);
                mma_bf16(c, z, p.zero, p.zero);
                res += c[0];
                __nv_bfloat16* dst = p.out + (col & ~1);
                uint32_t src = sbase + SM_HN + (lane & 15) * 48;
                asm volatile("bar.sync %0, 288;" ::"r"(after(p.zero, 5, src, dst, res)) : "memory");
                const float4 ra = lds128f(src), rb = lds128f(src + 16);
                const float e = ((ra.x + ra.y) + (ra.z + ra.w)) + (((rb.x + rb.y) + (rb.z + rb.w)) + res);
                if (lane < 16) asm volatile("red.relaxed.gpu.global.add.noftz.bf16x2 [%0], %1;" ::"l"(dst), "r"((lane & 1) ? pack_bf(e, 0.f) : pack_bf(0.f, e)) : "memory");
                if (lane == 0) LST(96);
            }
        }
    } else if (warp > 10) {
        if (is_ffn) {
            const int col = (tid - 352) * 4;
            uint2 xres;
            asm volatile("bar.sync 10, 192;" ::: "memory");
            mbar_wait(bar_pace, 0);
            asm volatile("ld.global.nc.v2.u32 {%0, %1}, [%2];" : "=r"(xres.x), "=r"(xres.y) : "l"(p.x + col) : "memory");
            const unsigned char* gsrc[NG];
            uint2 u[NG];
#pragma unroll
            for (int i = 0; i < NG; i++) gsrc[i] = p.xa + xa_off(L_GATHER + rr % cfg::HCOPY * HCOPY_BYTES + (i * D_MODEL + col) * 2, s_pace[2]);
            const uint32_t hdst = sbase + SM_HN + col * 2;
            const bool diag = (lane & 3) == (lane >> 3);
            const uint32_t sdst = sbase + SM_STAT + (warp - 11) * 48 + (diag ? (lane >> 2) : 8 + (lane & 3)) * 4;
            const uint32_t at = after(p.zero, tail_time(cfg::T_HAT), gsrc[0], gsrc[1], gsrc[2], gsrc[3], gsrc[4], gsrc[5], hdst, sdst, xres.x);
            sleep_until(at - 4 * 300);
            wait_until(at);
#pragma unroll
            for (int i = 0; i < NG; i++) { u[i] = make_uint2(0, 0); in_ld2p(gsrc[i], u[i], true); }
            uint32_t n = 0;
#pragma unroll 1
            while (__any_sync(0xffffffffu, max(max(max(u[0].x, u[0].y), max(u[1].x, u[1].y)), max(max(max(u[2].x, u[2].y), max(u[3].x, u[3].y)),
                                                                                                max(max(u[4].x, u[4].y), max(u[5].x, u[5].y)))) == SENT)) {
#pragma unroll
                for (int i = 0; i < NG; i++) in_ld2p(gsrc[i], u[i], !in_ok(u[i]));
                if (++n > SPIN_LIMIT) __trap();
            }
#define F_(f, c) (f(xres.c) + bfr(((f(u[0].c) + f(u[1].c)) + (f(u[2].c) + f(u[3].c))) + (f(u[4].c) + f(u[5].c))))
            const uint32_t hp0 = pack_bf(F_(bf_hi, x), F_(bf_lo, x)), hp1 = pack_bf(F_(bf_hi, y), F_(bf_lo, y));
#undef F_
            sts64(hdst, hp0, hp1);
            asm volatile("bar.arrive 9, 416;" ::: "memory");
            float cs[4] = {0.f, 0.f, 0.f, 0.f};
            const uint32_t sa[4] = {hp0, 0x3f803f80u, hp1, 0x3f803f80u};
            mma_bf16(cs, sa, hp0, hp1);
            if (diag || (!(lane & 4) && (lane & 3) == (lane >> 3 ^ 1))) sts32(sdst, !diag ? cs[2] + cs[3] : (lane & 4) ? cs[1] : cs[0]);
            asm volatile("bar.arrive 11, 192;" ::: "memory");
            if (lane == 0) LST(100);
        }
    } else {
        const int t = lane & 3, g = lane >> 2;
        const int arow = (lane & 7) + ((lane >> 4) << 3), ahalf = (lane >> 3) & 1;
        uint32_t epoch0;
        const char* xb = reinterpret_cast<const char*>(p.x);
        asm volatile("ld.relaxed.gpu.global.u32 %0, [%1];" : "=r"(epoch0) : "l"(&p.sc->epoch) : "memory");
        uint64_t* q1dst = p.sc->q1 + ((head * 4 + (warp & 3)) * 4 + sp) * 48 + min(t, 2) * 16 + g;
        uint4* q2dst = p.sc->q2 + (head * 8 + sp * 2 + lane / 12) * 4 + t;
        if (warp == 7) {
            uint2 xu[5];
#pragma unroll
            for (int i = 0; i < 5; i++) asm volatile("ld.global.nc.v2.u32 {%0, %1}, [%2];" : "=r"(xu[i].x), "=r"(xu[i].y) : "l"(xb + i * 256 + lane * 8));
            float t1, t2, mean_b, inv_den;
            ln_sums(xu, t1, t2);
            ln_finish(t1, t2, mean_b, inv_den);
#define N_(v) (bfr((v) - mean_b) * inv_den)
#pragma unroll
            for (int i = 0; i < 5; i++)
                sts64(sbase + SM_HN + i * 256 + lane * 8, pack_bf(N_(bf_hi(xu[i].x)), N_(bf_lo(xu[i].x))), pack_bf(N_(bf_hi(xu[i].y)), N_(bf_lo(xu[i].y))));
#undef N_
        } else {
            if (warp < 4 && t < 3) { ll_st1(q1dst, 0.f, 0); ll_st1(q1dst + 8, 0.f, 0); }
            if (warp == 4 && lane < 24 && lane % 12 < 4) pkt_st(q2dst, 0, 0, 0, 0);
        }
        asm volatile("cp.async.wait_all;" ::: "memory");
        if (lane == 0) LST(80 + warp);
        asm volatile("bar.sync 2, 288;" ::: "memory");
        const uint32_t tag = epoch0 + 1;
        auto block = [&](int i) { const int unit = arow * 3 + (i >> 2); return sbase + SM_RING + unit * 128 + ((((i & 3) * 2 + ahalf) ^ (unit & 7)) << 4); };

        if (warp < 4) {
            {
                float c[3][4];
                uint32_t wa[3];
#pragma unroll
                for (int k = 0; k < 3; k++) { c[k][0] = c[k][1] = c[k][2] = c[k][3] = 0.f; wa[k] = block(warp * 3 + k) + QSLOT * TILE_BYTES; }
                const uint32_t xa = sbase + SM_HN + sp * 320 + t * 4;
#pragma unroll 2
                for (int ks = 0; ks < 2 * NQT; ks++) {
                    const uint32_t b0 = lds32(xa + ks * 32), b1 = lds32(xa + ks * 32 + 16);
#pragma unroll
                    for (int k = 0; k < 3; k++) { uint32_t a[4]; ldsm_x4_t(a, wa[k] + ks * (TILE_BYTES / 2)); mma_bf16(c[k], a, b0, b1); }
                }
                if (t < 3) {
                    ll_st1(q1dst, t == 0 ? c[0][0] : t == 1 ? c[1][0] : c[2][0], tag);
                    ll_st1(q1dst + 8, t == 0 ? c[0][2] : t == 1 ? c[1][2] : c[2][2], tag);
                }
                asm volatile("bar.sync 6, 128;" ::: "memory");
                if (tid < NQT) mbar_arrive(bar_empty + 8 * (QSLOT + tid));
                if (tid == 0) LST(90);
            }
            const uint32_t ta[3] = {block(0), block(4), block(8)};
            mbar_wait(bar_q, 0);
            if (tid == 0) LST(92);
#pragma unroll 1
            for (int h = warp; h < NHEAD; h += 4) {
                const int slot = (2 * h) & (NSLOT - 1);
                const uint32_t par = (h >> 3) & 1;
                if (h >= NHEAD - cfg::PREPART) mbar_wait(bar_set, 0);
                uint32_t qf[24];
#pragma unroll
                for (int i = 0; i < 6; i++) { const uint4 v = lds128(sbase + SM_Q + h * ROW_BYTES + t * 96 + i * 16); qf[4 * i] = v.x; qf[4 * i + 1] = v.y; qf[4 * i + 2] = v.z; qf[4 * i + 3] = v.w; }
                uint32_t ad[12];
#pragma unroll
                for (int i = 0; i < 12; i++) ad[i] = (ta[i >> 2] + slot * TILE_BYTES) ^ ((i & 3) << 5);
                float sc[4][4];
#pragma unroll
                for (int j = 0; j < 4; j++) sc[j][0] = sc[j][1] = sc[j][2] = sc[j][3] = 0.f;
                mbar_wait(bar_full + 8 * slot, par);
#pragma unroll
                for (int i = 0; i < 12; i++) {
                    const uint32_t a[4] = {qf[2 * i], qf[2 * i], qf[2 * i + 1], qf[2 * i + 1]};
                    uint32_t k0[4], k1[4];
                    ldsm_x4(k0, ad[i]); ldsm_x4(k1, ad[i] + TILE_BYTES / 2);
                    mma_bf16(sc[0], a, k0[0], k0[1]); mma_bf16(sc[1], a, k0[2], k0[3]);
                    mma_bf16(sc[2], a, k1[0], k1[1]); mma_bf16(sc[3], a, k1[2], k1[3]);
                }
                const float scale = 0.07216878364870322f;
                float m = -INFINITY;
#pragma unroll
                for (int j = 0; j < 4; j++) { sc[j][0] = bfr(bfr(sc[j][0]) * scale); sc[j][1] = bfr(bfr(sc[j][1]) * scale); m = fmaxf(m, fmaxf(sc[j][0], sc[j][1])); }
                if (lane == 0) mbar_arrive(after(p.zero, bar_empty + 8 * slot, m));
                m = fmaxf(m, __shfl_xor_sync(0xffffffffu, m, 1));
                m = fmaxf(m, __shfl_xor_sync(0xffffffffu, m, 2));
                float l = 0.f;
                uint32_t pf[4];
#pragma unroll
                for (int j = 0; j < 4; j++) {
                    const float p0 = ex2((sc[j][0] - m) * L2E), p1 = ex2((sc[j][1] - m) * L2E);
                    l += p0 + p1;
                    const uint32_t hi = pack_bf(p1, p0);
                    pf[j] = (g & 1) ? pack_bf(p1 - bf_hi(hi), p0 - bf_lo(hi)) : hi;
                }
                l += __shfl_xor_sync(0xffffffffu, l, 1);
                l += __shfl_xor_sync(0xffffffffu, l, 2);
                const uint32_t meta = (__float_as_uint(m) & 0xffff0000u) | ((__float_as_uint(l) - 0x3f800000u + 0x800u) >> 10 & 0xfffcu) | (tag & 3);
                uint32_t pq[4][4];
#pragma unroll
                for (int q = 0; q < 4; q++)
#pragma unroll
                    for (int j = 0; j < 4; j++) pq[q][j] = (g >> 1) == q ? pf[j] : 0;
                float o[6][4];
#pragma unroll
                for (int k = 0; k < 6; k++) o[k][0] = o[k][1] = o[k][2] = o[k][3] = 0.f;
                uint4* dst = p.sc->part + ((h * 4 + t) * NCTA + b) * 8 + g;
                uint4* dst2 = reinterpret_cast<uint4*>(p.xa + xa_off(L_PART + ((t * NCTA + b) * 8 + g) * 16, 1));
                if (h == NHEAD - 1) dst = reinterpret_cast<uint4*>(p.xa + xa_off(L_PART + ((t * NCTA + b) * 8 + g) * 16, 0));
                mbar_wait(after(p.zero, bar_full + 8 * slot + 8, meta, dst, dst2, pq[0][0], pq[1][1], pq[2][2], pq[3][3]), par);
#pragma unroll
                for (int i = 0; i < 12; i++) {
                    uint32_t v0[4], v1[4];
                    ldsm_x4_t(v0, ad[i] + TILE_BYTES); ldsm_x4_t(v1, ad[i] + TILE_BYTES + TILE_BYTES / 2);
                    mma_bf16(o[i % 3], v0, pq[i / 3][0], pq[i / 3][1]);
                    mma_bf16(o[3 + i % 3], v1, pq[i / 3][2], pq[i / 3][3]);
                }
                uint32_t w[3];
#pragma unroll
                for (int k = 0; k < 3; k++) w[k] = pack_bf((o[k][2] + o[k][3]) + (o[k + 3][2] + o[k + 3][3]), (o[k][0] + o[k][1]) + (o[k + 3][0] + o[k + 3][1]));
                pkt_st(dst, w[0], w[1], w[2], meta);
                if (h == NHEAD - 1) pkt_st(dst2, w[0], w[1], w[2], meta);
                if (lane == 0) {
                    mbar_arrive(after(p.zero, bar_empty + 8 * slot + 8, w[0], w[1], w[2]));
                    if (h == head) mbar_arrive(bar_part);
                }
            }
            if (tid == 96) LST(91);
        } else {
            const int u = tid - 128;
            uint32_t n = 0;
            if (warp == 4) {
                const uint4* src = reinterpret_cast<const uint4*>(p.sc->q1 + (head * 4 + sp) * 4 * 48) + min(lane, 23);
                uint4 v[4];
                sleep_until(now_q() + 4 * cfg::QDELAY);
#pragma unroll 1
                do {
                    if (n) __nanosleep(cfg::QSLEEP);
#pragma unroll
                    for (int i = 0; i < 4; i++) v[i] = ll_ld2(src + i * 24);
                    if (++n > SPIN_LIMIT) __trap();
                } while (__any_sync(0xffffffffu, ((v[0].y ^ tag) | (v[0].w ^ tag) | (v[1].y ^ tag) | (v[1].w ^ tag) | (v[2].y ^ tag) | (v[2].w ^ tag) | (v[3].y ^ tag) | (v[3].w ^ tag)) != 0));
#define F_(c) ((__uint_as_float(v[0].c) + __uint_as_float(v[1].c)) + (__uint_as_float(v[2].c) + __uint_as_float(v[3].c)))
                const uint32_t w0 = pack_bf(F_(z), F_(x));
#undef F_
                const uint32_t w1 = __shfl_down_sync(0xffffffffu, w0, 4), w2 = __shfl_down_sync(0xffffffffu, w0, 8);
                if (lane < 24 && lane % 12 < 4) pkt_st(q2dst, w0, w1, w2, tag);
            }
            asm volatile("bar.sync 7, 128;" ::: "memory");
            uint4 v[8];
            {
#pragma unroll
                for (int i = 0; i < 8; i++) v[i] = make_uint4(0, 0, 0, ~tag);
                sleep_until(now_q() + 4 * cfg::QDELAY2);
                n = 0;
                bool ok;
#pragma unroll 1
                do {
                    if (n) __nanosleep(cfg::QSLEEP);
#pragma unroll
                    for (int i = 0; i < 8; i++) pkt_ldp(p.sc->q2 + u + i * 128, v[i], v[i].w != tag);
                    ok = true;
#pragma unroll
                    for (int i = 0; i < 8; i++) ok &= v[i].w == tag;
                    if (++n > SPIN_LIMIT) __trap();
                } while (!__all_sync(0xffffffffu, ok));
                const uint32_t qd = sbase + SM_Q + (u >> 5) * ROW_BYTES + t * 96 + g * 12;
#pragma unroll
                for (int i = 0; i < 8; i++) {
                    sts32(qd + i * 4 * ROW_BYTES, __uint_as_float(v[i].x)); sts32(qd + i * 4 * ROW_BYTES + 4, __uint_as_float(v[i].y)); sts32(qd + i * 4 * ROW_BYTES + 8, __uint_as_float(v[i].z));
                }
                __syncwarp();
                if (lane == 0) mbar_arrive(bar_q);
            }
            {
                const uint4* src = p.sc->part + b * NCTA * 8 + u;
                const uint32_t rdst = sbase + SM_RED + (warp - 4) * 256 + min(lane >> 3, 2) * 64 + (lane & 7) * 4;
                const uint32_t lo = o_off(b * 48 + (min(lane, 23) >> 3) * 16) + (lane & 3) * 8 + (lane & 4);
                unsigned char *od0 = p.xa + xa_off(lo, 0), *od1 = p.xa + xa_off(lo, 1);
#pragma unroll
                for (int i = 0; i < 8; i++) v[i].w = ~tag;
                mbar_wait(bar_set, 0);
                const uint4* sr[4];
#pragma unroll
                for (int i = 0; i < 4; i++) sr[i] = head == NHEAD - 1 ? reinterpret_cast<const uint4*>(p.xa + xa_off(L_PART + (sp * 4 + i) * 4096, s_pace[2])) + u : src + i * 256;
                mbar_wait(after(p.zero, bar_part, sr[0], sr[1], sr[2], sr[3], rdst, od0, od1), 0);
                {
                    const uint32_t at = now_q() + 4 * min(cfg::PDELAY, cfg::PDELAY_LAST + (NHEAD - 1 - head) * cfg::PDELAY_STEP);
                    sleep_until(at - 4 * 300);
                    wait_until(at);
                }
                n = 0;
                uint32_t bad;
#pragma unroll 1
                do {
                    if (n && head != NHEAD - 1) __nanosleep(cfg::QSLEEP);
#pragma unroll
                    for (int i = 0; i < 8; i++) pkt_ldp(sr[i >> 1] + (i & 1) * 128, v[i], ((v[i].w ^ tag) & 3) != 0);
                    bad = 0;
#pragma unroll
                    for (int i = 0; i < 8; i++) bad |= v[i].w ^ tag;
                    if (++n > SPIN_LIMIT) __trap();
                } while (__any_sync(0xffffffffu, (bad & 3) != 0));
                if (u == 0) LST(119);
                float m = -INFINITY;
#pragma unroll
                for (int i = 0; i < 8; i++) m = fmaxf(m, bf_hi(v[i].w));
                m = fmaxf(m, __shfl_xor_sync(0xffffffffu, m, 8));
                m = fmaxf(m, __shfl_xor_sync(0xffffffffu, m, 16));
                float a[7] = {0.f, 0.f, 0.f, 0.f, 0.f, 0.f, 0.f};
#pragma unroll
                for (int i = 0; i < 8; i++) {
                    const float f = ex2((bf_hi(v[i].w) - m) * L2E);
                    a[0] = fmaf(f, bf_lo(v[i].x), a[0]); a[1] = fmaf(f, bf_hi(v[i].x), a[1]);
                    a[2] = fmaf(f, bf_lo(v[i].y), a[2]); a[3] = fmaf(f, bf_hi(v[i].y), a[3]);
                    a[4] = fmaf(f, bf_lo(v[i].z), a[4]); a[5] = fmaf(f, bf_hi(v[i].z), a[5]);
                    a[6] = fmaf(f, __uint_as_float(((v[i].w & 0xfffcu) << 10) + 0x3f800000u), a[6]);
                }
#pragma unroll
                for (int o = 8; o < 32; o <<= 1)
#pragma unroll
                    for (int i = 0; i < 7; i++) a[i] += __shfl_xor_sync(0xffffffffu, a[i], o);
                if (lane < 24) { sts32(rdst, lane < 8 ? a[0] : lane < 16 ? a[2] : a[4]); sts32(rdst + 32, lane < 8 ? a[1] : lane < 16 ? a[3] : a[5]); }
                if (lane == 24) sts64(rdst + 64, __float_as_uint(a[6]), __float_as_uint(m));
                asm volatile("bar.sync 7, 128;" ::: "memory");
                if (warp == 4) {
                    float2 st[4], r[4];
#pragma unroll
                    for (int i = 0; i < 4; i++) { st[i] = lds64f(sbase + SM_RED + i * 256 + 192); r[i] = lds64f(sbase + SM_RED + i * 256 + lane * 8); }
                    const float mm = fmaxf(fmaxf(st[0].y, st[1].y), fmaxf(st[2].y, st[3].y));
                    float den = 0.f, x0 = 0.f, x1 = 0.f;
#pragma unroll
                    for (int i = 0; i < 4; i++) { const float f = ex2((st[i].y - mm) * L2E); den = fmaf(f, st[i].x, den); x0 = fmaf(f, r[i].x, x0); x1 = fmaf(f, r[i].y, x1); }
                    const float inv = rcp_fast(den);
                    const float ow = __uint_as_float(pack_bf(x1 * inv, x0 * inv));
                    if (lane < 24) { in_st1(od0, ow); in_st1(od1, ow); }
                    if (lane == 0) LST(120);
                }
            }
        }
        mbar_wait(bar_pace, 0);
        const uint32_t msel = s_pace[2];
        cons_sync();
        if (is_wo) {
            uint32_t wa = sbase + (warp * 16 + arow) * 128 + ((ahalf ^ (lane & 7)) << 4);
            uint32_t pw = sbase + SM_RED + (warp * 64 + t * 16 + (lane >> 2)) * 4, pr = sbase + SM_RED + lane * 8;
            unsigned char* gdst = p.xa + xa_off(L_GATHER + (warp >> 1) % cfg::HCOPY * HCOPY_BYTES + (kg * D_MODEL + ng * 64 + lane * 2) * 2, warp & 1);
            const unsigned char* osrc = p.xa + xa_off(L_O + kg * 2048, msel) + warp * 32 + t * 8;
            uint2 ov[NWP];
#pragma unroll
            for (int j = 0; j < NWP; j++) ov[j] = make_uint2(SENT, SENT);
            auto gather = [&](int j0, int j1) {
                uint32_t n = 0;
#pragma unroll 1
                while (true) {
                    uint32_t mx = 0;
#pragma unroll
                    for (int j = j0; j < j1; j++) mx = max(mx, max(ov[j].x, ov[j].y));
                    if (!__any_sync(0xffffffffu, mx == SENT)) break;
#pragma unroll
                    for (int j = j0; j < j1; j++) in_ld2p(osrc + j * 256, ov[j], !in_ok(ov[j]));
                    if (++n > SPIN_LIMIT) __trap();
                }
            };
            float cw[4][4];
#pragma unroll
            for (int i = 0; i < 4; i++) cw[i][0] = cw[i][1] = cw[i][2] = cw[i][3] = 0.f;
            mbar_wait(after(p.zero, bar_tail + 8, osrc, wa, pw, pr, gdst), 0);
#pragma unroll
            for (int j = 0; j < NWP; j++) in_ld2p(osrc + j * 256, ov[j], true);
            gather(0, NWP - 1);
#pragma unroll
            for (int j = 0; j < NWP; j++) {
                if (j == NWP - 2) { gather(NWP - 1, NWP); if (tid == 224) LST(93); }
                mbar_wait(bar_tail + 8 * j, 0);
                if (j == NWP - 4) in_ld2p(osrc + (NWP - 1) * 256, ov[NWP - 1], !in_ok(ov[NWP - 1]));
                uint32_t a[4][4];
#pragma unroll
                for (int i = 0; i < 4; i++) ldsm_x4_t(a[i], (wa ^ (i << 5)) + j * WPIECE);
#pragma unroll
                for (int i = 0; i < 4; i++) mma_bf16(cw[i], a[i], ov[j].x, ov[j].y);
            }
#define SEL_(e) ((t & 2) ? ((t & 1) ? cw[3][e] : cw[2][e]) : ((t & 1) ? cw[1][e] : cw[0][e]))
            sts32(pw, SEL_(0)); sts32(pw + 32, SEL_(2));
#undef SEL_
            cons_sync();
            if (warp < 2 * cfg::HCOPY) {
                float2 r[8];
#pragma unroll
                for (int i = 0; i < 8; i++) r[i] = lds64f(pr + i * 256);
#define S_(c) (((r[0].c + r[1].c) + (r[2].c + r[3].c)) + ((r[4].c + r[5].c) + (r[6].c + r[7].c)))
                in_st1(gdst, __uint_as_float(pack_bf(S_(y), S_(x))));
#undef S_
            }
            if (tid == 0) LST(94);
        } else if (is_ffn) {
            uint32_t w13a = sbase + (warp * 16 + arow) * 64 + ((ahalf ^ (lane >> 1 & 3)) << 4);
            uint32_t red_dst = sbase + SM_RED + tid * 8;
            const uint32_t ha = sbase + SM_HN + warp * 32 + t * 8;
            uint32_t aw[2][NUP][2][4];
            auto load = [&](int m, int i) {
#pragma unroll
                for (int k = 0; k < 2; k++) ldsm_x4_t(aw[m][i][k], (w13a ^ (k << 5)) + (m * NUP + i) * (WPIECE / 2));
            };
#pragma unroll
            for (int j = 0; j < 3; j++) {
                mbar_wait(j ? bar_tail + 8 * j : after(p.zero, bar_tail, w13a, red_dst, ha), 0);
                load(2 * j / NUP, 2 * j % NUP); load((2 * j + 1) / NUP, (2 * j + 1) % NUP);
            }
            LSC(0);
            asm volatile("bar.sync 9, 416;" ::: "memory");
            uint32_t b0[NUP], b1[NUP];
#pragma unroll
            for (int i = 0; i < NUP; i++) {
                b0[i] = b1[i] = 0x3f803f80u;
                asm volatile("{\n.reg .pred q;\nsetp.eq.u32 q, %3, 0;\n@q ld.shared.v2.u32 {%0, %1}, [%2];\n}" : "+r"(b0[i]), "+r"(b1[i]) : "r"(ha + i * 256), "r"(lane & 4) : "memory");
            }
#pragma unroll
            for (int m = 0; m < 2; m++) {
                if (m) { mbar_wait(bar_tail + 8 * 3, 0); load(1, 1); load(1, 2); }
                float cf[2][2][4];
#pragma unroll
                for (int e = 0; e < 4; e++) cf[0][0][e] = cf[0][1][e] = cf[1][0][e] = cf[1][1][e] = 0.f;
#pragma unroll
                for (int i = 0; i < NUP; i++) {
                    if (m && i >= NUP - 2) { mbar_wait(bar_tail + 8 * (i + 1), 0); load(1, i); }
#pragma unroll
                    for (int k = 0; k < 2; k++) mma_bf16(cf[m ? 0 : i & 1][k], aw[m][i][k], b0[i], b1[i]);
                }
#define SEL_(c, e) ((t & 2) ? ((t & 1) ? cf[c][1][e + 2] : cf[c][1][e]) : ((t & 1) ? cf[c][0][e + 2] : cf[c][0][e]))
                if (m == 0) {
                    sts64(red_dst, __float_as_uint(SEL_(0, 0) + SEL_(1, 0)), __float_as_uint(SEL_(0, 1) + SEL_(1, 1)));
                    asm volatile("bar.arrive 8, 288;" ::: "memory");
                } else {
                    sts64(red_dst + 2048, __float_as_uint(SEL_(0, 0)), __float_as_uint(SEL_(0, 1)));
                }
#undef SEL_
            }
            LSC(7);
            asm volatile("bar.arrive 5, 288;" ::: "memory");
        }
        if (is_out) {
            uint32_t w2a = sbase + SM_W2 + (warp * 32 + arow) * 32 + ((ahalf ^ (lane >> 2 & 1)) << 4);
            uint32_t ydst = sbase + SM_HN + ((t & 1) * 8 + (lane >> 2)) * 48 + warp * 4;
            const unsigned char* asrc = p.xa + xa_off(L_ACT, msel) + oh * (NDP * 512) + warp * 64 + t * 16;
            const uint32_t at = tail_time(cfg::T_AAT);
            uint32_t a[NDP][2][4];
            auto load_w2 = [&](int i) {
                mbar_wait(i ? bar_tail + 8 * (NWP + i) : after(p.zero, bar_tail + 8 * NWP, w2a, ydst, asrc, at), 0);
                ldsm_x4_t(a[i][0], w2a + i * PIECE); ldsm_x4_t(a[i][1], w2a + i * PIECE + 512);
            };
            load_w2(0);
            uint4 u[NDP];
            wait_until(at);
            LSC(0);
#pragma unroll
            for (int i = 0; i < NDP; i++) u[i] = in_ld4(asrc + i * 512);
            load_w2(1);
            uint32_t n = 0;
#pragma unroll 1
            while (true) {
                uint32_t m[NDP];
#pragma unroll
                for (int i = 0; i < NDP; i++) m[i] = max(max(u[i].x, u[i].y), max(u[i].z, u[i].w));
                if (!__any_sync(0xffffffffu, max(max(m[0], m[1]), m[2]) == SENT)) break;
#pragma unroll
                for (int i = 0; i < NDP; i++) in_ld4p(asrc + i * 512, u[i], m[i] == SENT);
                if (++n > SPIN_LIMIT) __trap();
            }
            LSC(12);
            if (tid == 96) LST(118);
            float cy[2 * NDP][4];
#pragma unroll
            for (int i = 0; i < NDP; i++) {
#pragma unroll
                for (int e = 0; e < 4; e++) cy[2 * i][e] = cy[2 * i + 1][e] = 0.f;
                if (i == NDP - 1) load_w2(i);
                mma_bf16(cy[2 * i], a[i][0], u[i].x, u[i].y);
                mma_bf16(cy[2 * i + 1], a[i][1], u[i].z, u[i].w);
            }
#define Y_(e) (((cy[0][e] + cy[1][e]) + (cy[2][e] + cy[3][e])) + (cy[4][e] + cy[5][e]))
            const float y = (t & 1) ? Y_(2) : Y_(0);
#undef Y_
            if (t < 2) sts32(ydst, y);
            LSC(13);
            asm volatile("bar.arrive 5, 288;" ::: "memory");
        }
    }
}

typedef CUresult (*EncodeTiledFn)(CUtensorMap*, CUtensorMapDataType, cuuint32_t, void*, const cuuint64_t*, const cuuint64_t*,
                                  const cuuint32_t*, const cuuint32_t*, CUtensorMapInterleave, CUtensorMapSwizzle,
                                  CUtensorMapL2promotion, CUtensorMapFloatOOBfill);

void make_map(EncodeTiledFn fn, CUtensorMap* tm, const void* w, const int (&d)[5], const int (&st)[4], const int (&bx)[5],
              CUtensorMapSwizzle sw, int promo) {
    cuuint64_t dims[5], strides[4];
    cuuint32_t box[5], estr[5];
    for (int i = 0; i < 5; i++) { dims[i] = (cuuint64_t)d[i]; box[i] = (cuuint32_t)bx[i]; estr[i] = 1; }
    for (int i = 0; i < 4; i++) strides[i] = (cuuint64_t)st[i];
    fn(tm, CU_TENSOR_MAP_DATA_TYPE_BFLOAT16, 5, const_cast<void*>(w), dims, strides, box, estr, CU_TENSOR_MAP_INTERLEAVE_NONE, sw,
       (CUtensorMapL2promotion)promo, CU_TENSOR_MAP_FLOAT_OOB_FILL_NONE);
}

}

extern "C" void kernel_launch(void* const* d_in, const int* in_sizes, int n_in, void* d_out, int out_size) {
    (void)in_sizes; (void)n_in; (void)out_size;
    static EncodeTiledFn encode = nullptr;
    static Scratch* scratch = nullptr;
    static unsigned char* xarea = nullptr;
    static double tscale = 1.0;
    if (!encode) {
        void* sp = nullptr;
        cudaGetSymbolAddress(&sp, g_scratch);
        scratch = reinterpret_cast<Scratch*>(sp);
        cudaGetSymbolAddress(&sp, g_xarea);
        xarea = reinterpret_cast<unsigned char*>((reinterpret_cast<uintptr_t>(sp) + XA_ALIGN - 1) / XA_ALIGN * XA_ALIGN);
        void* fn = nullptr;
        cudaDriverEntryPointQueryResult st;
        cudaGetDriverEntryPoint("cuTensorMapEncodeTiled", &fn, cudaEnableDefault, &st);
        encode = reinterpret_cast<EncodeTiledFn>(fn);
        int dev = 0, khz = 0, bits = 0;
        cudaGetDevice(&dev);
        cudaDeviceGetAttribute(&khz, cudaDevAttrMemoryClockRate, dev);
        cudaDeviceGetAttribute(&bits, cudaDevAttrGlobalMemoryBusWidth, dev);
        if (khz > 0 && bits > 0) tscale = (2619000.0 * 5120.0) / ((double)khz * bits);
        cudaFuncSetAttribute(fused_decode_kernel, cudaFuncAttributeMaxDynamicSharedMemorySize, SM_TOTAL);
    }
    KParams p;
    p.x = (const __nv_bfloat16*)d_in[0];
    p.wq = (const __nv_bfloat16*)d_in[3];
    p.out = (__nv_bfloat16*)d_out;
    p.sc = scratch;
    p.xa = xarea;
    p.zero = 0;
    p.t_first = (uint32_t)(4 * cfg::T_FIRST * tscale);
    p.t_step = (uint32_t)(cfg::T_STEP * tscale);
    p.t_smax = (uint32_t)(cfg::T_SMAX * tscale);
    p.t_lat = (uint32_t)(4 * (450 + (cfg::T_LAT - 450) * tscale));
    TMaps tm;
    constexpr int R1 = FF * 2, R2 = D_MODEL * 2;
    make_map(encode, &tm.k, d_in[1], {64, NHEAD * SK * 3, 1, 1, 1}, {128, 128, 128, 128}, {64, 96, 1, 1, 1}, CU_TENSOR_MAP_SWIZZLE_128B, cfg::PROMO_KV);
    make_map(encode, &tm.v, d_in[2], {64, NHEAD * SK * 3, 1, 1, 1}, {128, 128, 128, 128}, {64, 96, 1, 1, 1}, CU_TENSOR_MAP_SWIZZLE_128B, cfg::PROMO_KV);
    make_map(encode, &tm.wo, d_in[4], {D_MODEL, NHEAD * DH, 1, 1, 1}, {R2, R2, R2, R2}, {64, 128, 1, 1, 1}, CU_TENSOR_MAP_SWIZZLE_128B, cfg::PROMO_WO);
    make_map(encode, &tm.w1, d_in[6], {FF, 2, 4, 2, 40}, {R1, 4 * R1, 2 * R1, 16 * R1}, {32, 2, 4, 2, 8}, CU_TENSOR_MAP_SWIZZLE_64B, cfg::PROMO_W13);
    make_map(encode, &tm.w3, d_in[7], {FF, 2, 4, 2, 40}, {R1, 4 * R1, 2 * R1, 16 * R1}, {32, 2, 4, 2, 8}, CU_TENSOR_MAP_SWIZZLE_64B, cfg::PROMO_W13);
    make_map(encode, &tm.w2, d_in[8], {D_MODEL, FF, 1, 1, 1}, {R2, R2, R2, R2}, {16, 256, 1, 1, 1}, CU_TENSOR_MAP_SWIZZLE_32B, cfg::PROMO_W2);
    fused_decode_kernel<<<NCTA, NTHREADS, SM_TOTAL, cudaStreamPerThread>>>(p, tm);
}
```

```cpp
#include <cuda_runtime.h>
#include <cuda_bf16.h>
#include <cuda.h>
#include <stdint.h>
#include <math.h>

namespace {

constexpr int D_MODEL = 640;
constexpr int NHEAD = 32;
constexpr int DH = 192;
constexpr int SK = 32768;
constexpr int WIN = 4096;
constexpr int FF = 1536;

constexpr int NCTA = 128;
constexpr int NCONS = 256;
constexpr int NTHREADS = NCONS + 256;
constexpr int ROW_BYTES = DH * 2;
constexpr int TILE_BYTES = 32 * ROW_BYTES;
constexpr int NSLOT = 16;
constexpr int NQT = 5;
constexpr int QSLOT = NSLOT - NQT;
constexpr int NWO = 60;
constexpr int NG = 6;
constexpr int NFFN = 48;
constexpr int NWP = 8;
constexpr int NUP = 5;
constexpr int WPIECE = 16384;
constexpr int NDP = 3;
constexpr int PIECE = 8192;
constexpr int NTAIL = NWP + NDP;
constexpr int N_TAIL0 = 2 * NHEAD;

#define CFG(name, value) constexpr int name = value
#define CFG_OVERRIDE
namespace cfg_default {
CFG(T_FIRST, 1850);
CFG(T_STEP, 1906);
CFG(T_SMAX, 1940);
CFG(CAP, 5);
CFG(MN, 12);
CFG(MA, 4);
CFG(MB, 40);
CFG(ADAPT, 60);
CFG(T_LAT, 1230);
CFG(T_WO, 296);
CFG(T_GAP, 95);
CFG(T_UP, 240);
CFG(T_UP2, 120);
CFG(T_W2AT, 1320);
CFG(T_W2, 200);
CFG(T_HAT, 1130);
CFG(T_RESAT, 1750);
CFG(T_AAT, 2420);
CFG(KEEP_AT, 65);
CFG(KEEP, 150);
CFG(HCOPY, 1);
CFG(QDELAY, 1200);
CFG(QDELAY2, 900);
CFG(QSLEEP, 400);
CFG(PDELAY, 2500);
CFG(PDELAY_LAST, 250);
CFG(PDELAY_STEP, 650);
CFG(PREPART, 3);
CFG(RBDELAY, 5000);
CFG(NPROBE, 10);
CFG(VOTES, 3);
CFG(PROMO_KV, 2);
CFG(PROMO_WO, 2);
CFG(PROMO_W13, 2);
CFG(PROMO_W2, 2);
CFG(BOUNDED_MBAR, 0);
}
namespace cfg { using namespace cfg_default; CFG_OVERRIDE }

constexpr uint32_t SBASE = 1024;
constexpr int SM_RING = 0;
constexpr int SM_W2 = NWP * WPIECE;
constexpr int SM_Q = SM_RING + NSLOT * TILE_BYTES;
constexpr int SM_RED = SM_Q + NHEAD * ROW_BYTES;
constexpr int SM_HN = SM_RED + 4096;
constexpr int SM_STAT = SM_HN + D_MODEL * 2;
constexpr int SM_MISC = SM_STAT + 256;
constexpr int SM_BAR = SM_MISC + 128;
constexpr int SM_TOTAL = SM_BAR + 512;
static_assert(SM_TOTAL <= 232448, "shared memory");

struct __align__(128) Scratch {
    uint4 part[NHEAD * 4 * NCTA * 8];
    uint64_t q1[NHEAD * 4 * DH];
    uint4 q2[NHEAD * 32];
    uint32_t epoch;
    uint32_t pad;
    unsigned long long pace[2];
};
__device__ Scratch g_scratch;
constexpr int XA_ALIGN = 1 << 20;
constexpr uint32_t SENT = 0xffffffffu;
constexpr int L_GATHER = 0;
constexpr int HCOPY_BYTES = NG * D_MODEL * 2;
constexpr int L_O = 9 * 4096;
constexpr int L_ACT = 30 * 4096;
constexpr int L_PROBE = 32 * 4096;
constexpr int L_PART = 64 * 4096;
static_assert(2 * (L_PART + 65536) <= XA_ALIGN, "");
__device__ unsigned char g_xarea[2 * XA_ALIGN];
__device__ __forceinline__ uint32_t xa_off(uint32_t l, uint32_t side) {
    const uint32_t k = l >> 12;
    return (2 * k + ((side ^ k ^ (k >> 3) ^ (k >> 4) ^ (k >> 6)) & 1)) * 4096 + (l & 4095);
}

__device__ __forceinline__ uint32_t o_off(uint32_t r) { return L_O + (r >> 7) % NG * 2048 + (r >> 7) / NG * 256 + (r & 127) * 2; }

#define LST(i) do { } while (0)
#define LSC(i) do { } while (0)
#define LSCD(i, v) do { } while (0)
constexpr uint32_t SPIN_LIMIT = cfg::BOUNDED_MBAR ? 1u << 14 : 1u << 22;

__device__ __forceinline__ uint32_t now_q() { uint32_t t; asm volatile("mov.u32 %0, %globaltimer_lo;" : "=r"(t)); return t * 4; }
__device__ __forceinline__ void wait_until(uint32_t due) {
#pragma unroll 1
    for (int n = 0; n < 4096 && (int)(now_q() - due) < 0; n++) { }
}
__device__ __forceinline__ void sleep_until(uint32_t due) {
#pragma unroll 1
    for (int n = 0; n < 4096 && (int)(now_q() - due) < 0; n++) __nanosleep(200);
}
__device__ __forceinline__ uint32_t smem_u32(const void* p) { return (uint32_t)__cvta_generic_to_shared(p); }
__device__ __forceinline__ void mbar_init(uint32_t bar, uint32_t cnt) {
    asm volatile("mbarrier.init.shared::cta.b64 [%0], %1;" ::"r"(bar), "r"(cnt) : "memory");
}
__device__ __forceinline__ void mbar_expect_tx(uint32_t bar, uint32_t bytes) {
    asm volatile("mbarrier.arrive.expect_tx.shared::cta.b64 _, [%0], %1;" ::"r"(bar), "r"(bytes) : "memory");
}
__device__ __forceinline__ void mbar_arrive(uint32_t bar) {
    asm volatile("mbarrier.arrive.shared::cta.b64 _, [%0];" ::"r"(bar) : "memory");
}
__device__ __forceinline__ bool mbar_test(uint32_t bar, uint32_t parity) {
    uint32_t ok;
    asm volatile("{\n.reg .pred p;\nmbarrier.test_wait.parity.shared::cta.b64 p, [%1], %2;\nselp.u32 %0, 1, 0, p;\n}"
                 : "=r"(ok) : "r"(bar), "r"(parity) : "memory");
    return ok;
}
__device__ __forceinline__ bool mbar_try(uint32_t bar, uint32_t parity) {
    uint32_t ok;
    asm volatile("{\n.reg .pred p;\nmbarrier.try_wait.parity.shared::cta.b64 p, [%1], %2;\nselp.u32 %0, 1, 0, p;\n}"
                 : "=r"(ok) : "r"(bar), "r"(parity) : "memory");
    return ok;
}
__device__ __forceinline__ void mbar_wait(uint32_t bar, uint32_t parity) {
    if (cfg::BOUNDED_MBAR) {
        uint32_t n = 0;
        while (!mbar_try(bar, parity)) if (++n > SPIN_LIMIT) __trap();
    } else {
        asm volatile("{\n.reg .pred p;\nW_%=:\nmbarrier.try_wait.parity.shared::cta.b64 p, [%0], %1;\n@!p bra W_%=;\n}" ::"r"(bar), "r"(parity) : "memory");
    }
}
__device__ __forceinline__ void tma_tile(uint32_t dst, const CUtensorMap* tm, int c1, uint32_t bar, uint64_t pol) {
    asm volatile("cp.async.bulk.tensor.5d.shared::cluster.global.mbarrier::complete_tx::bytes.L2::cache_hint [%0], [%1, {%4, %3, %4, %4, %4}], [%2], %5;"
                 ::"r"(dst), "l"(reinterpret_cast<uint64_t>(tm)), "r"(bar), "r"(c1), "r"(0), "l"(pol) : "memory");
}
__device__ __forceinline__ void tma_5d(uint32_t dst, const CUtensorMap* tm, int c0, int c1, int c2, int c4, uint32_t bar) {
    asm volatile("cp.async.bulk.tensor.5d.shared::cluster.global.mbarrier::complete_tx::bytes [%0], [%1, {%3, %4, %5, %7, %6}], [%2];"
                 ::"r"(dst), "l"(reinterpret_cast<uint64_t>(tm)), "r"(bar), "r"(c0), "r"(c1), "r"(c2), "r"(c4), "r"(0) : "memory");
}
__device__ __forceinline__ uint32_t bits(uint32_t v) { return v; }
__device__ __forceinline__ uint32_t bits(float v) { return __float_as_uint(v); }
__device__ __forceinline__ uint32_t bits(const void* v) { return (uint32_t)(uintptr_t)v ^ (uint32_t)((uintptr_t)v >> 32); }
template <class... T> __device__ __forceinline__ uint32_t after(uint32_t zero, uint32_t bar, T... v) { return bar | ((bits(v) ^ ...) & zero); }
__device__ __forceinline__ void sts32(uint32_t a, float v) { asm volatile("st.shared.f32 [%0], %1;" ::"r"(a), "f"(v) : "memory"); }
__device__ __forceinline__ void sts64(uint32_t a, uint32_t x, uint32_t y) { asm volatile("st.shared.v2.u32 [%0], {%1, %2};" ::"r"(a), "r"(x), "r"(y) : "memory"); }
__device__ __forceinline__ void cons_sync() { asm volatile("bar.sync 1, 256;" ::: "memory"); }

__device__ __forceinline__ uint4 lds128(uint32_t a) {
    uint4 v;
    asm volatile("ld.shared.v4.u32 {%0,%1,%2,%3}, [%4];" : "=r"(v.x), "=r"(v.y), "=r"(v.z), "=r"(v.w) : "r"(a));
    return v;
}
__device__ __forceinline__ float4 lds128f(uint32_t a) {
    float4 v;
    asm volatile("ld.shared.v4.f32 {%0,%1,%2,%3}, [%4];" : "=f"(v.x), "=f"(v.y), "=f"(v.z), "=f"(v.w) : "r"(a) : "memory");
    return v;
}
__device__ __forceinline__ float2 lds64f(uint32_t a) {
    float2 v;
    asm volatile("ld.shared.v2.f32 {%0,%1}, [%2];" : "=f"(v.x), "=f"(v.y) : "r"(a) : "memory");
    return v;
}
__device__ __forceinline__ uint32_t lds32(uint32_t a) {
    uint32_t v;
    asm volatile("ld.shared.u32 %0, [%1];" : "=r"(v) : "r"(a));
    return v;
}
__device__ __forceinline__ void ldsm_x4(uint32_t* r, uint32_t a) {
    asm volatile("ldmatrix.sync.aligned.m8n8.x4.shared.b16 {%0,%1,%2,%3}, [%4];"
                 : "=r"(r[0]), "=r"(r[1]), "=r"(r[2]), "=r"(r[3]) : "r"(a));
}
__device__ __forceinline__ void ldsm_x4_t(uint32_t* r, uint32_t a) {
    asm volatile("ldmatrix.sync.aligned.m8n8.x4.trans.shared.b16 {%0,%1,%2,%3}, [%4];"
                 : "=r"(r[0]), "=r"(r[1]), "=r"(r[2]), "=r"(r[3]) : "r"(a));
}
__device__ __forceinline__ void mma_bf16(float* c, const uint32_t* a, uint32_t b0, uint32_t b1) {
    asm volatile("mma.sync.aligned.m16n8k16.row.col.f32.bf16.bf16.f32 {%0,%1,%2,%3}, {%4,%5,%6,%7}, {%8,%9}, {%0,%1,%2,%3};"
                 : "+f"(c[0]), "+f"(c[1]), "+f"(c[2]), "+f"(c[3]) : "r"(a[0]), "r"(a[1]), "r"(a[2]), "r"(a[3]), "r"(b0), "r"(b1));
}
__device__ __forceinline__ float bf_lo(uint32_t u) { return __uint_as_float(u << 16); }
__device__ __forceinline__ float bf_hi(uint32_t u) { return __uint_as_float(u & 0xffff0000u); }
__device__ __forceinline__ uint32_t pack_bf(float hi, float lo) { uint32_t r; asm("cvt.rn.bf16x2.f32 %0, %1, %2;" : "=r"(r) : "f"(hi), "f"(lo)); return r; }
__device__ __forceinline__ float bfr(float x) { return __uint_as_float(pack_bf(x, 0.f)); }

__device__ __forceinline__ uint64_t pk(float v, uint32_t tag) { return ((uint64_t)tag << 32) | (uint64_t)__float_as_uint(v); }
__device__ __forceinline__ void ll_st1(uint64_t* p, float a, uint32_t tag) {
    asm volatile("st.relaxed.gpu.global.b64 [%0], %1;" ::"l"(p), "l"(pk(a, tag)) : "memory");
}
__device__ __forceinline__ uint4 ll_ld2(const uint4* p) {
    uint4 v;
    asm volatile("{\n.reg .b64 a, b;\nld.relaxed.gpu.global.v2.b64 {a, b}, [%4];\nmov.b64 {%0, %1}, a;\nmov.b64 {%2, %3}, b;\n}"
                 : "=r"(v.x), "=r"(v.y), "=r"(v.z), "=r"(v.w) : "l"(p) : "memory");
    return v;
}
__device__ __forceinline__ uint32_t in_word(float v) {
    uint32_t r;
    asm("min.u32 %0, %1, 0xfffffffe;" : "=r"(r) : "r"(__float_as_uint(v)));
    return r;
}
__device__ __forceinline__ void in_st1(void* p, float v) {
    asm volatile("st.relaxed.gpu.global.u32 [%0], %1;" ::"l"(p), "r"(in_word(v)) : "memory");
}
__device__ __forceinline__ void in_st4(void* p, uint32_t a, uint32_t b, uint32_t c, uint32_t d) {
    asm volatile("st.relaxed.gpu.global.v4.u32 [%0], {%1, %2, %3, %4};" ::"l"(p), "r"(a), "r"(b), "r"(c), "r"(d) : "memory");
}
__device__ __forceinline__ uint32_t in_ld1(const void* p) {
    uint32_t v;
    asm volatile("ld.relaxed.gpu.global.u32 %0, [%1];" : "=r"(v) : "l"(p) : "memory");
    return v;
}
__device__ __forceinline__ uint4 in_ld4(const void* p) {
    uint4 v;
    asm volatile("ld.relaxed.gpu.global.v4.u32 {%0, %1, %2, %3}, [%4];" : "=r"(v.x), "=r"(v.y), "=r"(v.z), "=r"(v.w) : "l"(p) : "memory");
    return v;
}
__device__ __forceinline__ void in_ld2p(const void* p, uint2& v, bool on) {
    asm volatile("{\n.reg .pred q;\nsetp.ne.u32 q, %3, 0;\n@q ld.relaxed.gpu.global.v2.u32 {%0, %1}, [%2];\n}"
                 : "+r"(v.x), "+r"(v.y) : "l"(p), "r"((uint32_t)on) : "memory");
}
__device__ __forceinline__ bool in_ok(const uint2& v) { return max(v.x, v.y) != SENT; }
__device__ __forceinline__ void in_ld4p(const void* p, uint4& v, bool on) {
    asm volatile("{\n.reg .pred q;\nsetp.ne.u32 q, %5, 0;\n@q ld.relaxed.gpu.global.v4.u32 {%0, %1, %2, %3}, [%4];\n}"
                 : "+r"(v.x), "+r"(v.y), "+r"(v.z), "+r"(v.w) : "l"(p), "r"((uint32_t)on) : "memory");
}
__device__ __forceinline__ void pkt_st(uint4* p, uint32_t x, uint32_t y, uint32_t z, uint32_t w) {
    asm volatile("{\n.reg .b128 t;\n.reg .b64 a, b;\nmov.b64 a, {%1, %2};\nmov.b64 b, {%3, %4};\nmov.b128 t, {a, b};\nst.relaxed.gpu.global.b128 [%0], t;\n}"
                 ::"l"(p), "r"(x), "r"(y), "r"(z), "r"(w) : "memory");
}
__device__ __forceinline__ void pkt_ldp(const uint4* p, uint4& v, bool on) {
    asm volatile("{\n.reg .pred q;\n.reg .b128 t;\n.reg .b64 a, b;\nsetp.ne.u32 q, %5, 0;\nmov.b64 a, {%0, %1};\nmov.b64 b, {%2, %3};\nmov.b128 t, {a, b};\n"
                 "@q ld.relaxed.gpu.global.b128 t, [%4];\nmov.b128 {a, b}, t;\nmov.b64 {%0, %1}, a;\nmov.b64 {%2, %3}, b;\n}"
                 : "+r"(v.x), "+r"(v.y), "+r"(v.z), "+r"(v.w) : "l"(p), "r"((uint32_t)on) : "memory");
}

__device__ __forceinline__ float sqrt_fast(float x) { float r; asm("sqrt.approx.ftz.f32 %0, %1;" : "=f"(r) : "f"(x)); return r; }
__device__ __forceinline__ float rcp_fast(float x) { float r; asm("rcp.approx.ftz.f32 %0, %1;" : "=f"(r) : "f"(x)); return r; }
__device__ __forceinline__ float ex2(float x) { float r; asm("ex2.approx.ftz.f32 %0, %1;" : "=f"(r) : "f"(x)); return r; }
constexpr float L2E = 1.4426950408889634f;
__device__ __forceinline__ void ln_sums(const uint2* v, float& t1, float& t2) {
    float s1[5], s2[5];
#pragma unroll
    for (int i = 0; i < 5; i++) {
        const float a0 = bf_lo(v[i].x), a1 = bf_hi(v[i].x), a2 = bf_lo(v[i].y), a3 = bf_hi(v[i].y);
        s1[i] = (a0 + a1) + (a2 + a3);
        s2[i] = fmaf(a0, a0, a1 * a1) + fmaf(a2, a2, a3 * a3);
    }
    t1 = ((s1[0] + s1[1]) + (s1[2] + s1[3])) + s1[4]; t2 = ((s2[0] + s2[1]) + (s2[2] + s2[3])) + s2[4];
#pragma unroll
    for (int o = 16; o > 0; o >>= 1) { t1 += __shfl_xor_sync(0xffffffffu, t1, o); t2 += __shfl_xor_sync(0xffffffffu, t2, o); }
}
__device__ __forceinline__ void ln_finish(float t1, float t2, float& mean_b, float& inv_den) {
    const float mean = t1 * (1.0f / D_MODEL);
    const float var = fmaxf(fmaf(-mean, mean, t2 * (1.0f / D_MODEL)), 0.f);
    mean_b = bfr(mean);
    inv_den = rcp_fast(bfr(sqrt_fast(bfr(bfr(var) + 1e-5f))));
}

struct KParams {
    const __nv_bfloat16* wq;
    uint32_t t_first;
    uint32_t t_step;
    const __nv_bfloat16* x;
    Scratch* sc;
    unsigned char* xa;
    __nv_bfloat16* out;
    uint32_t t_smax;
    uint32_t t_lat;
    uint32_t zero;
};
struct TMaps { CUtensorMap k, v, wo, w1, w3, w2; };

__global__ void __launch_bounds__(NTHREADS, 1)
fused_decode_kernel(const KParams p, const __grid_constant__ TMaps tm) {
    extern __shared__ __align__(1024) unsigned char smem[];
    const uint32_t sbase = smem_u32(smem);
    const int tid = threadIdx.x;
    const int b = blockIdx.x;
    const int head = b >> 2, sp = b & 3;
    {
        if (tid < 192) {
            const uint32_t rg = tid * 2731 >> 16, ch = tid - rg * 24;
            const char* src = reinterpret_cast<const char*>(p.wq) + (uint32_t)(sp * 160 * (NHEAD * DH * 2) + head * ROW_BYTES + rg * (NHEAD * DH * 2) + ch * 16);
            uint32_t dst = SBASE + SM_RING + QSLOT * TILE_BYTES + ((tid ^ (tid >> 3 & 7)) << 4);
#pragma unroll 4
            for (int i = 0; i < 20; i++) {
                asm volatile("cp.async.cg.shared.global [%0], [%1], 16;" ::"r"(dst), "l"(src) : "memory");
                dst += 8 * ROW_BYTES;
                src += (size_t)8 * (NHEAD * DH * 2);
            }
        }
    }
    const int warp = __shfl_sync(0xffffffffu, tid >> 5, 0), lane = tid & 31;
    const int rr = !(b & 1) ? b >> 1 : (b & 15) < 12 ? (b >> 4) * 6 + (b >> 1 & 7) : NFFN + (b >> 4) * 2 + (b >> 1 & 1);
    const bool is_wo = !(b & 1) && rr < NWO, is_ffn = (b & 1) && rr < NFFN, is_out = !is_ffn;
    const int og = (rr >> 2) + (b & 1) * 4, oh = og >= 10, oq = (og - 10 * oh) * 4 + (rr & 3);
    const int kg = min(rr / 10, NG - 1), ng = rr % 10;
    const uint32_t bar_full = sbase + SM_BAR;
    const uint32_t bar_empty = sbase + SM_BAR + 128;
    const uint32_t bar_tail = sbase + SM_BAR + 256;
    const uint32_t bar_set = bar_tail + 8 * NTAIL;
    const uint32_t bar_pace = bar_set + 8;
    const uint32_t bar_q = bar_set + 16;
    const uint32_t bar_part = bar_set + 24;
    volatile uint32_t* s_pace = reinterpret_cast<volatile uint32_t*>(smem + SM_MISC + 64);
    auto tail_time = [&](int t) { return s_pace[0] + (s_pace[1] * (((N_TAIL0 - cfg::ADAPT) * 478 + NWP * cfg::T_WO + t) * 256 / 478) >> 8); };

    if (warp == 8) {
        const uint32_t c_start = now_q();
        if (lane >= 1 && lane <= 6) asm volatile("prefetch.tensormap [%0];" ::"l"(reinterpret_cast<uint64_t>(&tm.k + (lane - 1))) : "memory");
        uint64_t pol_stream;
        asm volatile("createpolicy.fractional.L2::evict_first.b64 %0, 1.0;" : "=l"(pol_stream));
        if (lane == 0) {
#pragma unroll 1
            for (int i = 0; i < NSLOT; i++) { mbar_init(bar_full + 8 * i, 1); mbar_init(bar_empty + 8 * i, 1); }
#pragma unroll 1
            for (int i = 0; i < NTAIL + 4; i++) mbar_init(bar_tail + 8 * i, i == NTAIL + 2 ? 4 : 1);
            asm volatile("fence.mbarrier_init.release.cluster;" ::: "memory");
        }
        __syncwarp();
        asm volatile("bar.arrive 2, 288;" ::: "memory");
        asm volatile("bar.arrive 3, 64;" ::: "memory");
        asm volatile("bar.arrive 4, 64;" ::: "memory");
        if (is_ffn) asm volatile("bar.arrive 10, 192;" ::: "memory");
        if (lane == 0) {
            uint32_t due = c_start + p.t_first, step = p.t_step;
#pragma unroll 1
            for (int n = 0; n < N_TAIL0; n++) {
                const int slot = n & (NSLOT - 1);
                const int use = (n >> 4) + (slot >= QSLOT);
                if (n >= cfg::CAP) mbar_wait(bar_full + 8 * ((n - cfg::CAP) & (NSLOT - 1)), ((n - cfg::CAP) >> 4) & 1);
                if (use >= 1) mbar_wait(bar_empty + 8 * slot, (use - 1) & 1);
                if (n == cfg::ADAPT) { mbar_wait(bar_pace, 0); due = s_pace[0]; step = s_pace[1]; }
                const uint32_t full = bar_full + 8 * slot;
                mbar_expect_tx(full, TILE_BYTES);
                wait_until(due);
                LST(128 + n);
                tma_tile(sbase + SM_RING + slot * TILE_BYTES, &tm.k + (n & 1), ((n >> 1) * SK + (SK - WIN) + b * 32) * 3, full, pol_stream);
                due += step;
            }
            int rel = 0;
            auto released = [&](int end) {
#pragma unroll 1
                for (; rel * TILE_BYTES < end; rel++) mbar_wait(bar_empty + 8 * rel, rel < QSLOT);
            };
            const uint32_t t_wo = step * (cfg::T_WO * 4096 / 478) >> 12;
            if (is_wo) {
#pragma unroll 1
                for (int j = 0; j < NWP; j++) {
                    released((j + 1) * WPIECE);
                    mbar_expect_tx(bar_tail + 8 * j, WPIECE);
                    wait_until(due);
                    LST(128 + N_TAIL0 + j);
                    tma_5d(sbase + j * WPIECE, &tm.wo, ng * 64, j * (NG * 128) + kg * 128, 0, 0, bar_tail + 8 * j);
                    due += t_wo;
                }
            } else {
                due += NWP * t_wo;
            }
            due += 4 * cfg::T_GAP;
            if (is_out) {
                due += step * (cfg::T_W2AT * 4096 / 478) >> 12;
                released(SM_W2 + NDP * PIECE);
#pragma unroll
                for (int j = 0; j < NDP; j++) mbar_expect_tx(bar_tail + 8 * (NWP + j), PIECE);
                sleep_until(due - 4 * 400);
#pragma unroll
                for (int j = 0; j < NDP; j++) {
                    wait_until(due);
                    tma_5d(sbase + SM_W2 + j * PIECE, &tm.w2, oq * 16, (oh * NDP + j) * 256, 0, 0, bar_tail + 8 * (NWP + j));
                    LST(128 + N_TAIL0 + NWP + j);
                    due += step * (cfg::T_W2 * 4096 / 478) >> 12;
                }
            } else if (is_ffn) {
                released(NUP * WPIECE);
#pragma unroll
                for (int j = 0; j <= NUP; j++) mbar_expect_tx(bar_tail + 8 * j, j < NUP - 1 ? WPIECE : WPIECE / 2);
                sleep_until(due - 4 * 400);
#pragma unroll
                for (int j = 0; j <= NUP; j++) {
                    const uint32_t full = bar_tail + 8 * j;
                    wait_until(due);
#pragma unroll
                    for (int e = min(2 * j, j + NUP - 1); e < min(2 * j + 2, j + NUP); e++)
                        tma_5d(sbase + e * (WPIECE / 2), e < NUP ? &tm.w1 : &tm.w3, rr * 32, 0, 0, e % NUP * 8, full);
                    LST(128 + N_TAIL0 + j);
                    due += step * ((j < NUP - 1 ? cfg::T_UP : cfg::T_UP2) * 4096 / 478) >> 12;
                }
            }
        }
    } else if (warp == 10) {
        if (sbase != SBASE) __trap();
        asm volatile("bar.sync 4, 64;" ::: "memory");
        if (lane == 0) {
            uint32_t epoch0;
            asm volatile("ld.relaxed.gpu.global.u32 %0, [%1];" : "=r"(epoch0) : "l"(&p.sc->epoch) : "memory");
            constexpr int MN = cfg::MN;
            const uint32_t t0 = now_q();
            uint32_t sa = 0, sb = 0;
#pragma unroll 1
            for (int n = 0; n < cfg::MB + MN; n++) {
#pragma unroll 1
                for (int k = 0; k < 256 && !mbar_try(bar_full + 8 * (n & (NSLOT - 1)), (n >> 4) & 1); k++) { }
                const uint32_t t = now_q() - t0;
                LST(n);
                if ((uint32_t)(n - cfg::MA) < MN) sa += t;
                if (n >= cfg::MB) sb += t;
            }
            const uint32_t mb = t0 + sb / MN;
            unsigned long long* pace = p.sc->pace + ((epoch0 + 1) & 1);
            mbar_wait(bar_set, 0);
            asm volatile("red.relaxed.gpu.global.add.u64 [%0], %1;" ::"l"(pace), "l"((unsigned long long)mb << 32 | min((sb - sa) / (4 * MN), 0xffffu) << 8 | 1) : "memory");
            if (b == 0) p.sc->pace[epoch0 & 1] = 0;
            unsigned long long v;
            uint32_t n = 0, cnt;
#pragma unroll 1
            do {
                __nanosleep(n ? 200 : 1000);
                asm volatile("ld.relaxed.gpu.global.u64 %0, [%1];" : "=l"(v) : "l"(pace) : "memory");
                cnt = (uint32_t)v & 0xff;
                if (++n > SPIN_LIMIT) __trap();
            } while (cnt < NCTA);
            const uint32_t step = min(max(((uint32_t)v >> 8) / (NCTA / 4 * (cfg::MB - cfg::MA)), p.t_step), p.t_smax);
            s_pace[0] = mb + (int)((uint32_t)(v >> 32) - NCTA * mb) / NCTA + step * (2 * (cfg::ADAPT - cfg::MB) - (MN - 1)) / 2 - p.t_lat;
            s_pace[1] = step;
            mbar_arrive(bar_pace);
            LST(89);
        }
    } else if (warp == 9) {
        const uint32_t c_start = now_q();
        uint32_t epoch0;
        asm volatile("ld.relaxed.gpu.global.u32 %0, [%1];" : "=r"(epoch0) : "l"(&p.sc->epoch) : "memory");
        sleep_until(c_start + p.t_first);
        unsigned char* slot[2];
        slot[0] = p.xa + xa_off(o_off(b * 48 + (lane % 6) * 8), lane / 6 & 1);
        slot[1] = p.xa + (is_wo ? xa_off(L_GATHER + (lane >> 4) * HCOPY_BYTES + (kg * D_MODEL + ng * 64 + (lane & 7) * 8) * 2, lane >> 3 & 1)
                                : xa_off(L_ACT + rr * 64 + (lane & 3) * 16, lane >> 2 & 1));
        const int n2 = is_wo ? 16 * cfg::HCOPY : is_ffn ? 8 : 0;
#pragma unroll
        for (int i = 0; i < 2; i++) if (lane < (i ? n2 : 12)) in_st4(slot[i], SENT, SENT, SENT, SENT);
#pragma unroll
        for (int i = 2; i <= cfg::PREPART; i++) pkt_st(p.sc->part + (((NHEAD - i) * 4 + (lane & 3)) * NCTA + b) * 8 + (lane >> 2), 0, 0, 0, epoch0 & 3);
#pragma unroll
        for (int i = 0; i < 2; i++) pkt_st(reinterpret_cast<uint4*>(p.xa + xa_off(L_PART + (((lane & 3) * NCTA + b) * 8 + (lane >> 2)) * 16, i)), 0, 0, 0, epoch0 & 3);
        unsigned char* probe = p.xa + xa_off(L_PROBE + b * 1024 + (lane >> 1 & 7) * 128 + (lane & 1) * 16, lane >> 4);
        in_st4(probe, SENT, SENT, SENT, SENT);
        const bool clr = is_out && !oh && lane < 2;
        if (clr) in_st4(p.out + oq * 16 + lane * 8, 0, 0, 0, 0);
        sleep_until(now_q() + 4 * cfg::RBDELAY + b * 60);
        uint32_t acc = SENT;
#pragma unroll
        for (int i = 0; i < 2; i++) if (lane < (i ? n2 : 12)) acc &= in_ld1(slot[i]);
        if (clr) acc &= ~in_ld1(p.out + oq * 16 + lane * 8);
        if (__any_sync(0xffffffffu, acc != SENT)) __trap();
        int vote = 0;
        uint32_t lat[2] = {0, 0};
#pragma unroll 1
        for (int r = 0; r <= cfg::NPROBE && abs(vote) < cfg::VOTES; r++) {
            __nanosleep(300);
            uint32_t d[2];
#pragma unroll
            for (int i = 0; i < 2; i++) {
                const uint32_t c0 = (uint32_t)clock();
                if (__any_sync(0xffffffffu, in_ld1(p.xa + xa_off(L_PROBE + b * 1024 + (lane & 7) * 128, i)) != SENT)) __trap();
                d[i] = (uint32_t)clock() - c0;
                if (r) lat[i] += min(d[i], 1500u);
            }
            if (r) vote = __shfl_sync(0xffffffffu, vote + (d[1] < d[0]) - (d[0] < d[1]), 0);
        }
        const uint32_t sel = vote ? vote > 0 : lat[1] < lat[0];
        const uint32_t tag = epoch0 + 1;
        asm volatile("bar.sync 3, 64;" ::: "memory");
        if (lane == 0) { s_pace[2] = sel; mbar_arrive(bar_set); }
        {
            mbar_wait(bar_pace, 0);
            sleep_until(s_pace[0] + (cfg::KEEP_AT - cfg::ADAPT) * s_pace[1]);
            const uint32_t t_res = tail_time(cfg::T_RESAT);
            float c[4] = {0.f, 0.f, 0.f, 0.f};
            const uint32_t z[4] = {p.zero, p.zero, p.zero, p.zero};
            uint32_t n = 0;
#pragma unroll 1
            do {
                mma_bf16(c, z, p.zero, p.zero);
                __nanosleep(cfg::KEEP);
                n += 1 + __float_as_uint(c[0]);
            } while (!__all_sync(0xffffffffu, is_ffn ? mbar_test(bar_tail, 0) : (int)(now_q() - t_res) >= 0) && n < SPIN_LIMIT);
            if (is_ffn) {
                unsigned char* adst = p.xa + xa_off(L_ACT + rr * 64 + (lane >> 3) * 16 + (lane & 3) * 4, lane >> 2 & 1);
                uint32_t src = sbase + SM_RED + lane * 8;
                asm volatile("bar.sync %0, 192;" ::"r"(after(p.zero, 11, adst, src)) : "memory");
                float t1, t2, mean_b, inv_den;
                {
                    float q1[5], q2[5];
#pragma unroll
                    for (int i = 0; i < 5; i++) {
                        const float4 a = lds128f(sbase + SM_STAT + i * 48), c = lds128f(sbase + SM_STAT + i * 48 + 16), d = lds128f(sbase + SM_STAT + i * 48 + 32);
                        q2[i] = ((a.x + a.y) + (a.z + a.w)) + ((c.x + c.y) + (c.z + c.w));
                        q1[i] = (d.x + d.y) + (d.z + d.w);
                    }
                    t1 = ((q1[0] + q1[1]) + (q1[2] + q1[3])) + q1[4]; t2 = ((q2[0] + q2[1]) + (q2[2] + q2[3])) + q2[4];
                }
                ln_finish(t1, t2, mean_b, inv_den);
                float2 r[8];
#define S_(c) (((r[0].c + r[1].c) + (r[2].c + r[3].c)) + ((r[4].c + r[5].c) + (r[6].c + r[7].c)))
                asm volatile("bar.sync %0, 288;" ::"r"(after(p.zero, 8, mean_b, inv_den)) : "memory");
#pragma unroll
                for (int i = 0; i < 8; i++) r[i] = lds64f(src + i * 256);
                const float gate = bfr(fmaf(-mean_b, S_(y), S_(x)) * inv_den);
                const float silu = bfr(__fdividef(gate, 1.0f + ex2(-gate * L2E)));
                asm volatile("bar.sync %0, 288;" ::"r"(after(p.zero, 5, silu)) : "memory");
#pragma unroll
                for (int i = 0; i < 8; i++) r[i] = lds64f(src + 2048 + i * 256);
                const float act = silu * bfr(fmaf(-mean_b, S_(y), S_(x)) * inv_den);
#undef S_
                const float oth = __shfl_xor_sync(0xffffffffu, act, 4);
                in_st1(adst, __uint_as_float((lane & 4) ? pack_bf(act, oth) : pack_bf(oth, act)));
                if (lane == 0) LST(110);
            }
            if (is_out) {
                const int col = oq * 16 + (lane & 15);
                float res = 0.f;
                if (!oh) {
                    uint32_t u[NG], xv;
                    asm volatile("ld.global.nc.u16 %0, [%1];" : "=r"(xv) : "l"(p.x + col));
                    n = 0;
#pragma unroll 1
                    do {
#pragma unroll
                        for (int i = 0; i < NG; i++) u[i] = in_ld1(p.xa + xa_off(L_GATHER + rr % cfg::HCOPY * HCOPY_BYTES + (i * D_MODEL + (col & ~1)) * 2, sel));
                        if (++n > SPIN_LIMIT) __trap();
                    } while (__any_sync(0xffffffffu, max(max(max(u[0], u[1]), max(u[2], u[3])), max(u[4], u[5])) == SENT));
                    if (b == 0 && lane == 0) p.sc->epoch = tag;
#define F_(i) ((lane & 1) ? bf_hi(u[i]) : bf_lo(u[i]))
                    res = bfr(bf_lo(xv) + bfr(((F_(0) + F_(1)) + (F_(2) + F_(3))) + (F_(4) + F_(5))));
#undef F_
                }
                mma_bf16(c, z, p.zero, p.zero);
                mbar_wait(after(p.zero, bar_tail + 8 * NWP, c[0]), 0);
                mma_bf16(c, z, p.zero, p.zero);
                res += c[0];
                __nv_bfloat16* dst = p.out + (col & ~1);
                uint32_t src = sbase + SM_HN + (lane & 15) * 48;
                asm volatile("bar.sync %0, 288;" ::"r"(after(p.zero, 5, src, dst, res)) : "memory");
                const float4 ra = lds128f(src), rb = lds128f(src + 16);
                const float e = ((ra.x + ra.y) + (ra.z + ra.w)) + (((rb.x + rb.y) + (rb.z + rb.w)) + res);
                if (lane < 16) asm volatile("red.relaxed.gpu.global.add.noftz.bf16x2 [%0], %1;" ::"l"(dst), "r"((lane & 1) ? pack_bf(e, 0.f) : pack_bf(0.f, e)) : "memory");
                if (lane == 0) LST(96);
            }
        }
    } else if (warp > 10) {
        if (is_ffn) {
            const int col = (tid - 352) * 4;
            uint2 xres;
            asm volatile("bar.sync 10, 192;" ::: "memory");
            mbar_wait(bar_pace, 0);
            asm volatile("ld.global.nc.v2.u32 {%0, %1}, [%2];" : "=r"(xres.x), "=r"(xres.y) : "l"(p.x + col) : "memory");
            const unsigned char* gsrc[NG];
            uint2 u[NG];
#pragma unroll
            for (int i = 0; i < NG; i++) gsrc[i] = p.xa + xa_off(L_GATHER + rr % cfg::HCOPY * HCOPY_BYTES + (i * D_MODEL + col) * 2, s_pace[2]);
            const uint32_t hdst = sbase + SM_HN + col * 2;
            const bool diag = (lane & 3) == (lane >> 3);
            const uint32_t sdst = sbase + SM_STAT + (warp - 11) * 48 + (diag ? (lane >> 2) : 8 + (lane & 3)) * 4;
            const uint32_t at = after(p.zero, tail_time(cfg::T_HAT), gsrc[0], gsrc[1], gsrc[2], gsrc[3], gsrc[4], gsrc[5], hdst, sdst, xres.x);
            sleep_until(at - 4 * 300);
            wait_until(at);
#pragma unroll
            for (int i = 0; i < NG; i++) { u[i] = make_uint2(0, 0); in_ld2p(gsrc[i], u[i], true); }
            uint32_t n = 0;
#pragma unroll 1
            while (__any_sync(0xffffffffu, max(max(max(u[0].x, u[0].y), max(u[1].x, u[1].y)), max(max(max(u[2].x, u[2].y), max(u[3].x, u[3].y)),
                                                                                                max(max(u[4].x, u[4].y), max(u[5].x, u[5].y)))) == SENT)) {
#pragma unroll
                for (int i = 0; i < NG; i++) in_ld2p(gsrc[i], u[i], !in_ok(u[i]));
                if (++n > SPIN_LIMIT) __trap();
            }
#define F_(f, c) (f(xres.c) + bfr(((f(u[0].c) + f(u[1].c)) + (f(u[2].c) + f(u[3].c))) + (f(u[4].c) + f(u[5].c))))
            const uint32_t hp0 = pack_bf(F_(bf_hi, x), F_(bf_lo, x)), hp1 = pack_bf(F_(bf_hi, y), F_(bf_lo, y));
#undef F_
            sts64(hdst, hp0, hp1);
            asm volatile("bar.arrive 9, 416;" ::: "memory");
            float cs[4] = {0.f, 0.f, 0.f, 0.f};
            const uint32_t sa[4] = {hp0, 0x3f803f80u, hp1, 0x3f803f80u};
            mma_bf16(cs, sa, hp0, hp1);
            if (diag || (!(lane & 4) && (lane & 3) == (lane >> 3 ^ 1))) sts32(sdst, !diag ? cs[2] + cs[3] : (lane & 4) ? cs[1] : cs[0]);
            asm volatile("bar.arrive 11, 192;" ::: "memory");
            if (lane == 0) LST(100);
        }
    } else {
        const int t = lane & 3, g = lane >> 2;
        const int arow = (lane & 7) + ((lane >> 4) << 3), ahalf = (lane >> 3) & 1;
        uint32_t epoch0;
        const char* xb = reinterpret_cast<const char*>(p.x);
        asm volatile("ld.relaxed.gpu.global.u32 %0, [%1];" : "=r"(epoch0) : "l"(&p.sc->epoch) : "memory");
        uint64_t* q1dst = p.sc->q1 + ((head * 4 + (warp & 3)) * 4 + sp) * 48 + min(t, 2) * 16 + g;
        uint4* q2dst = p.sc->q2 + (head * 8 + sp * 2 + lane / 12) * 4 + t;
        if (warp == 7) {
            uint2 xu[5];
#pragma unroll
            for (int i = 0; i < 5; i++) asm volatile("ld.global.nc.v2.u32 {%0, %1}, [%2];" : "=r"(xu[i].x), "=r"(xu[i].y) : "l"(xb + i * 256 + lane * 8));
            float t1, t2, mean_b, inv_den;
            ln_sums(xu, t1, t2);
            ln_finish(t1, t2, mean_b, inv_den);
#define N_(v) (bfr((v) - mean_b) * inv_den)
#pragma unroll
            for (int i = 0; i < 5; i++)
                sts64(sbase + SM_HN + i * 256 + lane * 8, pack_bf(N_(bf_hi(xu[i].x)), N_(bf_lo(xu[i].x))), pack_bf(N_(bf_hi(xu[i].y)), N_(bf_lo(xu[i].y))));
#undef N_
        } else {
            if (warp < 4 && t < 3) { ll_st1(q1dst, 0.f, 0); ll_st1(q1dst + 8, 0.f, 0); }
            if (warp == 4 && lane < 24 && lane % 12 < 4) pkt_st(q2dst, 0, 0, 0, 0);
        }
        asm volatile("cp.async.wait_all;" ::: "memory");
        if (lane == 0) LST(80 + warp);
        asm volatile("bar.sync 2, 288;" ::: "memory");
        const uint32_t tag = epoch0 + 1;
        auto block = [&](int i) { const int unit = arow * 3 + (i >> 2); return sbase + SM_RING + unit * 128 + ((((i & 3) * 2 + ahalf) ^ (unit & 7)) << 4); };

        if (warp < 4) {
            {
                float c[3][4];
                uint32_t wa[3];
#pragma unroll
                for (int k = 0; k < 3; k++) { c[k][0] = c[k][1] = c[k][2] = c[k][3] = 0.f; wa[k] = block(warp * 3 + k) + QSLOT * TILE_BYTES; }
                const uint32_t xa = sbase + SM_HN + sp * 320 + t * 4;
#pragma unroll 2
                for (int ks = 0; ks < 2 * NQT; ks++) {
                    const uint32_t b0 = lds32(xa + ks * 32), b1 = lds32(xa + ks * 32 + 16);
#pragma unroll
                    for (int k = 0; k < 3; k++) { uint32_t a[4]; ldsm_x4_t(a, wa[k] + ks * (TILE_BYTES / 2)); mma_bf16(c[k], a, b0, b1); }
                }
                if (t < 3) {
                    ll_st1(q1dst, t == 0 ? c[0][0] : t == 1 ? c[1][0] : c[2][0], tag);
                    ll_st1(q1dst + 8, t == 0 ? c[0][2] : t == 1 ? c[1][2] : c[2][2], tag);
                }
                asm volatile("bar.sync 6, 128;" ::: "memory");
                if (tid < NQT) mbar_arrive(bar_empty + 8 * (QSLOT + tid));
                if (tid == 0) LST(90);
            }
            const uint32_t ta[3] = {block(0), block(4), block(8)};
            mbar_wait(bar_q, 0);
            if (tid == 0) LST(92);
#pragma unroll 1
            for (int h = warp; h < NHEAD; h += 4) {
                const int slot = (2 * h) & (NSLOT - 1);
                const uint32_t par = (h >> 3) & 1;
                if (h >= NHEAD - cfg::PREPART) mbar_wait(bar_set, 0);
                uint32_t qf[24];
#pragma unroll
                for (int i = 0; i < 6; i++) { const uint4 v = lds128(sbase + SM_Q + h * ROW_BYTES + t * 96 + i * 16); qf[4 * i] = v.x; qf[4 * i + 1] = v.y; qf[4 * i + 2] = v.z; qf[4 * i + 3] = v.w; }
                uint32_t ad[12];
#pragma unroll
                for (int i = 0; i < 12; i++) ad[i] = (ta[i >> 2] + slot * TILE_BYTES) ^ ((i & 3) << 5);
                float sc[4][4];
#pragma unroll
                for (int j = 0; j < 4; j++) sc[j][0] = sc[j][1] = sc[j][2] = sc[j][3] = 0.f;
                mbar_wait(bar_full + 8 * slot, par);
#pragma unroll
                for (int i = 0; i < 12; i++) {
                    const uint32_t a[4] = {qf[2 * i], qf[2 * i], qf[2 * i + 1], qf[2 * i + 1]};
                    uint32_t k0[4], k1[4];
                    ldsm_x4(k0, ad[i]); ldsm_x4(k1, ad[i] + TILE_BYTES / 2);
                    mma_bf16(sc[0], a, k0[0], k0[1]); mma_bf16(sc[1], a, k0[2], k0[3]);
                    mma_bf16(sc[2], a, k1[0], k1[1]); mma_bf16(sc[3], a, k1[2], k1[3]);
                }
                const float scale = 0.07216878364870322f;
                float m = -INFINITY;
#pragma unroll
                for (int j = 0; j < 4; j++) { sc[j][0] = bfr(bfr(sc[j][0]) * scale); sc[j][1] = bfr(bfr(sc[j][1]) * scale); m = fmaxf(m, fmaxf(sc[j][0], sc[j][1])); }
                if (lane == 0) mbar_arrive(after(p.zero, bar_empty + 8 * slot, m));
                m = fmaxf(m, __shfl_xor_sync(0xffffffffu, m, 1));
                m = fmaxf(m, __shfl_xor_sync(0xffffffffu, m, 2));
                float l = 0.f;
                uint32_t pf[4];
#pragma unroll
                for (int j = 0; j < 4; j++) {
                    const float p0 = ex2((sc[j][0] - m) * L2E), p1 = ex2((sc[j][1] - m) * L2E);
                    l += p0 + p1;
                    const uint32_t hi = pack_bf(p1, p0);
                    pf[j] = (g & 1) ? pack_bf(p1 - bf_hi(hi), p0 - bf_lo(hi)) : hi;
                }
                l += __shfl_xor_sync(0xffffffffu, l, 1);
                l += __shfl_xor_sync(0xffffffffu, l, 2);
                const uint32_t meta = (__float_as_uint(m) & 0xffff0000u) | ((__float_as_uint(l) - 0x3f800000u + 0x800u) >> 10 & 0xfffcu) | (tag & 3);
                uint32_t pq[4][4];
#pragma unroll
                for (int q = 0; q < 4; q++)
#pragma unroll
                    for (int j = 0; j < 4; j++) pq[q][j] = (g >> 1) == q ? pf[j] : 0;
                float o[6][4];
#pragma unroll
                for (int k = 0; k < 6; k++) o[k][0] = o[k][1] = o[k][2] = o[k][3] = 0.f;
                uint4* dst = p.sc->part + ((h * 4 + t) * NCTA + b) * 8 + g;
                uint4* dst2 = reinterpret_cast<uint4*>(p.xa + xa_off(L_PART + ((t * NCTA + b) * 8 + g) * 16, 1));
                if (h == NHEAD - 1) dst = reinterpret_cast<uint4*>(p.xa + xa_off(L_PART + ((t * NCTA + b) * 8 + g) * 16, 0));
                mbar_wait(after(p.zero, bar_full + 8 * slot + 8, meta, dst, dst2, pq[0][0], pq[1][1], pq[2][2], pq[3][3]), par);
#pragma unroll
                for (int i = 0; i < 12; i++) {
                    uint32_t v0[4], v1[4];
                    ldsm_x4_t(v0, ad[i] + TILE_BYTES); ldsm_x4_t(v1, ad[i] + TILE_BYTES + TILE_BYTES / 2);
                    mma_bf16(o[i % 3], v0, pq[i / 3][0], pq[i / 3][1]);
                    mma_bf16(o[3 + i % 3], v1, pq[i / 3][2], pq[i / 3][3]);
                }
                uint32_t w[3];
#pragma unroll
                for (int k = 0; k < 3; k++) w[k] = pack_bf((o[k][2] + o[k][3]) + (o[k + 3][2] + o[k + 3][3]), (o[k][0] + o[k][1]) + (o[k + 3][0] + o[k + 3][1]));
                pkt_st(dst, w[0], w[1], w[2], meta);
                if (h == NHEAD - 1) pkt_st(dst2, w[0], w[1], w[2], meta);
                if (lane == 0) {
                    mbar_arrive(after(p.zero, bar_empty + 8 * slot + 8, w[0], w[1], w[2]));
                    if (h == head) mbar_arrive(bar_part);
                }
            }
            if (tid == 96) LST(91);
        } else {
            const int u = tid - 128;
            uint32_t n = 0;
            if (warp == 4) {
                const uint4* src = reinterpret_cast<const uint4*>(p.sc->q1 + (head * 4 + sp) * 4 * 48) + min(lane, 23);
                uint4 v[4];
                sleep_until(now_q() + 4 * cfg::QDELAY);
#pragma unroll 1
                do {
                    if (n) __nanosleep(cfg::QSLEEP);
#pragma unroll
                    for (int i = 0; i < 4; i++) v[i] = ll_ld2(src + i * 24);
                    if (++n > SPIN_LIMIT) __trap();
                } while (__any_sync(0xffffffffu, ((v[0].y ^ tag) | (v[0].w ^ tag) | (v[1].y ^ tag) | (v[1].w ^ tag) | (v[2].y ^ tag) | (v[2].w ^ tag) | (v[3].y ^ tag) | (v[3].w ^ tag)) != 0));
#define F_(c) ((__uint_as_float(v[0].c) + __uint_as_float(v[1].c)) + (__uint_as_float(v[2].c) + __uint_as_float(v[3].c)))
                const uint32_t w0 = pack_bf(F_(z), F_(x));
#undef F_
                const uint32_t w1 = __shfl_down_sync(0xffffffffu, w0, 4), w2 = __shfl_down_sync(0xffffffffu, w0, 8);
                if (lane < 24 && lane % 12 < 4) pkt_st(q2dst, w0, w1, w2, tag);
            }
            asm volatile("bar.sync 7, 128;" ::: "memory");
            uint4 v[8];
            {
#pragma unroll
                for (int i = 0; i < 8; i++) v[i] = make_uint4(0, 0, 0, ~tag);
                sleep_until(now_q() + 4 * cfg::QDELAY2);
                n = 0;
                bool ok;
#pragma unroll 1
                do {
                    if (n) __nanosleep(cfg::QSLEEP);
#pragma unroll
                    for (int i = 0; i < 8; i++) pkt_ldp(p.sc->q2 + u + i * 128, v[i], v[i].w != tag);
                    ok = true;
#pragma unroll
                    for (int i = 0; i < 8; i++) ok &= v[i].w == tag;
                    if (++n > SPIN_LIMIT) __trap();
                } while (!__all_sync(0xffffffffu, ok));
                const uint32_t qd = sbase + SM_Q + (u >> 5) * ROW_BYTES + t * 96 + g * 12;
#pragma unroll
                for (int i = 0; i < 8; i++) {
                    sts32(qd + i * 4 * ROW_BYTES, __uint_as_float(v[i].x)); sts32(qd + i * 4 * ROW_BYTES + 4, __uint_as_float(v[i].y)); sts32(qd + i * 4 * ROW_BYTES + 8, __uint_as_float(v[i].z));
                }
                __syncwarp();
                if (lane == 0) mbar_arrive(bar_q);
            }
            {
                const uint4* src = p.sc->part + b * NCTA * 8 + u;
                const uint32_t rdst = sbase + SM_RED + (warp - 4) * 256 + min(lane >> 3, 2) * 64 + (lane & 7) * 4;
                const uint32_t lo = o_off(b * 48 + (min(lane, 23) >> 3) * 16) + (lane & 3) * 8 + (lane & 4);
                unsigned char *od0 = p.xa + xa_off(lo, 0), *od1 = p.xa + xa_off(lo, 1);
#pragma unroll
                for (int i = 0; i < 8; i++) v[i].w = ~tag;
                mbar_wait(bar_set, 0);
                const uint4* sr[4];
#pragma unroll
                for (int i = 0; i < 4; i++) sr[i] = head == NHEAD - 1 ? reinterpret_cast<const uint4*>(p.xa + xa_off(L_PART + (sp * 4 + i) * 4096, s_pace[2])) + u : src + i * 256;
                mbar_wait(after(p.zero, bar_part, sr[0], sr[1], sr[2], sr[3], rdst, od0, od1), 0);
                {
                    const uint32_t at = now_q() + 4 * min(cfg::PDELAY, cfg::PDELAY_LAST + (NHEAD - 1 - head) * cfg::PDELAY_STEP);
                    sleep_until(at - 4 * 300);
                    wait_until(at);
                }
                n = 0;
                uint32_t bad;
#pragma unroll 1
                do {
                    if (n && head != NHEAD - 1) __nanosleep(cfg::QSLEEP);
#pragma unroll
                    for (int i = 0; i < 8; i++) pkt_ldp(sr[i >> 1] + (i & 1) * 128, v[i], ((v[i].w ^ tag) & 3) != 0);
                    bad = 0;
#pragma unroll
                    for (int i = 0; i < 8; i++) bad |= v[i].w ^ tag;
                    if (++n > SPIN_LIMIT) __trap();
                } while (__any_sync(0xffffffffu, (bad & 3) != 0));
                if (u == 0) LST(119);
                float m = -INFINITY;
#pragma unroll
                for (int i = 0; i < 8; i++) m = fmaxf(m, bf_hi(v[i].w));
                m = fmaxf(m, __shfl_xor_sync(0xffffffffu, m, 8));
                m = fmaxf(m, __shfl_xor_sync(0xffffffffu, m, 16));
                float a[7] = {0.f, 0.f, 0.f, 0.f, 0.f, 0.f, 0.f};
#pragma unroll
                for (int i = 0; i < 8; i++) {
                    const float f = ex2((bf_hi(v[i].w) - m) * L2E);
                    a[0] = fmaf(f, bf_lo(v[i].x), a[0]); a[1] = fmaf(f, bf_hi(v[i].x), a[1]);
                    a[2] = fmaf(f, bf_lo(v[i].y), a[2]); a[3] = fmaf(f, bf_hi(v[i].y), a[3]);
                    a[4] = fmaf(f, bf_lo(v[i].z), a[4]); a[5] = fmaf(f, bf_hi(v[i].z), a[5]);
                    a[6] = fmaf(f, __uint_as_float(((v[i].w & 0xfffcu) << 10) + 0x3f800000u), a[6]);
                }
#pragma unroll
                for (int o = 8; o < 32; o <<= 1)
#pragma unroll
                    for (int i = 0; i < 7; i++) a[i] += __shfl_xor_sync(0xffffffffu, a[i], o);
                if (lane < 24) { sts32(rdst, lane < 8 ? a[0] : lane < 16 ? a[2] : a[4]); sts32(rdst + 32, lane < 8 ? a[1] : lane < 16 ? a[3] : a[5]); }
                if (lane == 24) sts64(rdst + 64, __float_as_uint(a[6]), __float_as_uint(m));
                asm volatile("bar.sync 7, 128;" ::: "memory");
                if (warp == 4) {
                    float2 st[4], r[4];
#pragma unroll
                    for (int i = 0; i < 4; i++) { st[i] = lds64f(sbase + SM_RED + i * 256 + 192); r[i] = lds64f(sbase + SM_RED + i * 256 + lane * 8); }
                    const float mm = fmaxf(fmaxf(st[0].y, st[1].y), fmaxf(st[2].y, st[3].y));
                    float den = 0.f, x0 = 0.f, x1 = 0.f;
#pragma unroll
                    for (int i = 0; i < 4; i++) { const float f = ex2((st[i].y - mm) * L2E); den = fmaf(f, st[i].x, den); x0 = fmaf(f, r[i].x, x0); x1 = fmaf(f, r[i].y, x1); }
                    const float inv = rcp_fast(den);
                    const float ow = __uint_as_float(pack_bf(x1 * inv, x0 * inv));
                    if (lane < 24) { in_st1(od0, ow); in_st1(od1, ow); }
                    if (lane == 0) LST(120);
                }
            }
        }
        mbar_wait(bar_pace, 0);
        const uint32_t msel = s_pace[2];
        cons_sync();
        if (is_wo) {
            uint32_t wa = sbase + (warp * 16 + arow) * 128 + ((ahalf ^ (lane & 7)) << 4);
            uint32_t pw = sbase + SM_RED + (warp * 64 + t * 16 + (lane >> 2)) * 4, pr = sbase + SM_RED + lane * 8;
            unsigned char* gdst = p.xa + xa_off(L_GATHER + (warp >> 1) % cfg::HCOPY * HCOPY_BYTES + (kg * D_MODEL + ng * 64 + lane * 2) * 2, warp & 1);
            const unsigned char* osrc = p.xa + xa_off(L_O + kg * 2048, msel) + warp * 32 + t * 8;
            uint2 ov[NWP];
#pragma unroll
            for (int j = 0; j < NWP; j++) ov[j] = make_uint2(SENT, SENT);
            auto gather = [&](int j0, int j1) {
                uint32_t n = 0;
#pragma unroll 1
                while (true) {
                    uint32_t mx = 0;
#pragma unroll
                    for (int j = j0; j < j1; j++) mx = max(mx, max(ov[j].x, ov[j].y));
                    if (!__any_sync(0xffffffffu, mx == SENT)) break;
#pragma unroll
                    for (int j = j0; j < j1; j++) in_ld2p(osrc + j * 256, ov[j], !in_ok(ov[j]));
                    if (++n > SPIN_LIMIT) __trap();
                }
            };
            float cw[4][4];
#pragma unroll
            for (int i = 0; i < 4; i++) cw[i][0] = cw[i][1] = cw[i][2] = cw[i][3] = 0.f;
            mbar_wait(after(p.zero, bar_tail + 8, osrc, wa, pw, pr, gdst), 0);
#pragma unroll
            for (int j = 0; j < NWP; j++) in_ld2p(osrc + j * 256, ov[j], true);
            gather(0, NWP - 1);
#pragma unroll
            for (int j = 0; j < NWP; j++) {
                if (j == NWP - 2) { gather(NWP - 1, NWP); if (tid == 224) LST(93); }
                mbar_wait(bar_tail + 8 * j, 0);
                if (j == NWP - 4) in_ld2p(osrc + (NWP - 1) * 256, ov[NWP - 1], !in_ok(ov[NWP - 1]));
                uint32_t a[4][4];
#pragma unroll
                for (int i = 0; i < 4; i++) ldsm_x4_t(a[i], (wa ^ (i << 5)) + j * WPIECE);
#pragma unroll
                for (int i = 0; i < 4; i++) mma_bf16(cw[i], a[i], ov[j].x, ov[j].y);
            }
#define SEL_(e) ((t & 2) ? ((t & 1) ? cw[3][e] : cw[2][e]) : ((t & 1) ? cw[1][e] : cw[0][e]))
            sts32(pw, SEL_(0)); sts32(pw + 32, SEL_(2));
#undef SEL_
            cons_sync();
            if (warp < 2 * cfg::HCOPY) {
                float2 r[8];
#pragma unroll
                for (int i = 0; i < 8; i++) r[i] = lds64f(pr + i * 256);
#define S_(c) (((r[0].c + r[1].c) + (r[2].c + r[3].c)) + ((r[4].c + r[5].c) + (r[6].c + r[7].c)))
                in_st1(gdst, __uint_as_float(pack_bf(S_(y), S_(x))));
#undef S_
            }
            if (tid == 0) LST(94);
        } else if (is_ffn) {
            uint32_t w13a = sbase + (warp * 16 + arow) * 64 + ((ahalf ^ (lane >> 1 & 3)) << 4);
            uint32_t red_dst = sbase + SM_RED + tid * 8;
            const uint32_t ha = sbase + SM_HN + warp * 32 + t * 8;
            uint32_t aw[2][NUP][2][4];
            auto load = [&](int m, int i) {
#pragma unroll
                for (int k = 0; k < 2; k++) ldsm_x4_t(aw[m][i][k], (w13a ^ (k << 5)) + (m * NUP + i) * (WPIECE / 2));
            };
#pragma unroll
            for (int j = 0; j < 3; j++) {
                mbar_wait(j ? bar_tail + 8 * j : after(p.zero, bar_tail, w13a, red_dst, ha), 0);
                load(2 * j / NUP, 2 * j % NUP); load((2 * j + 1) / NUP, (2 * j + 1) % NUP);
            }
            LSC(0);
            asm volatile("bar.sync 9, 416;" ::: "memory");
            uint32_t b0[NUP], b1[NUP];
#pragma unroll
            for (int i = 0; i < NUP; i++) {
                b0[i] = b1[i] = 0x3f803f80u;
                asm volatile("{\n.reg .pred q;\nsetp.eq.u32 q, %3, 0;\n@q ld.shared.v2.u32 {%0, %1}, [%2];\n}" : "+r"(b0[i]), "+r"(b1[i]) : "r"(ha + i * 256), "r"(lane & 4) : "memory");
            }
#pragma unroll
            for (int m = 0; m < 2; m++) {
                if (m) { mbar_wait(bar_tail + 8 * 3, 0); load(1, 1); load(1, 2); }
                float cf[2][2][4];
#pragma unroll
                for (int e = 0; e < 4; e++) cf[0][0][e] = cf[0][1][e] = cf[1][0][e] = cf[1][1][e] = 0.f;
#pragma unroll
                for (int i = 0; i < NUP; i++) {
                    if (m && i >= NUP - 2) { mbar_wait(bar_tail + 8 * (i + 1), 0); load(1, i); }
#pragma unroll
                    for (int k = 0; k < 2; k++) mma_bf16(cf[m ? 0 : i & 1][k], aw[m][i][k], b0[i], b1[i]);
                }
#define SEL_(c, e) ((t & 2) ? ((t & 1) ? cf[c][1][e + 2] : cf[c][1][e]) : ((t & 1) ? cf[c][0][e + 2] : cf[c][0][e]))
                if (m == 0) {
                    sts64(red_dst, __float_as_uint(SEL_(0, 0) + SEL_(1, 0)), __float_as_uint(SEL_(0, 1) + SEL_(1, 1)));
                    asm volatile("bar.arrive 8, 288;" ::: "memory");
                } else {
                    sts64(red_dst + 2048, __float_as_uint(SEL_(0, 0)), __float_as_uint(SEL_(0, 1)));
                }
#undef SEL_
            }
            LSC(7);
            asm volatile("bar.arrive 5, 288;" ::: "memory");
        }
        if (is_out) {
            uint32_t w2a = sbase + SM_W2 + (warp * 32 + arow) * 32 + ((ahalf ^ (lane >> 2 & 1)) << 4);
            uint32_t ydst = sbase + SM_HN + ((t & 1) * 8 + (lane >> 2)) * 48 + warp * 4;
            const unsigned char* asrc = p.xa + xa_off(L_ACT, msel) + oh * (NDP * 512) + warp * 64 + t * 16;
            const uint32_t at = tail_time(cfg::T_AAT);
            uint32_t a[NDP][2][4];
            auto load_w2 = [&](int i) {
                mbar_wait(i ? bar_tail + 8 * (NWP + i) : after(p.zero, bar_tail + 8 * NWP, w2a, ydst, asrc, at), 0);
                ldsm_x4_t(a[i][0], w2a + i * PIECE); ldsm_x4_t(a[i][1], w2a + i * PIECE + 512);
            };
            load_w2(0);
            uint4 u[NDP];
            wait_until(at);
            LSC(0);
#pragma unroll
            for (int i = 0; i < NDP; i++) u[i] = in_ld4(asrc + i * 512);
            load_w2(1);
            uint32_t n = 0;
#pragma unroll 1
            while (true) {
                uint32_t m[NDP];
#pragma unroll
                for (int i = 0; i < NDP; i++) m[i] = max(max(u[i].x, u[i].y), max(u[i].z, u[i].w));
                if (!__any_sync(0xffffffffu, max(max(m[0], m[1]), m[2]) == SENT)) break;
#pragma unroll
                for (int i = 0; i < NDP; i++) in_ld4p(asrc + i * 512, u[i], m[i] == SENT);
                if (++n > SPIN_LIMIT) __trap();
            }
            LSC(12);
            if (tid == 96) LST(118);
            float cy[2 * NDP][4];
#pragma unroll
            for (int i = 0; i < NDP; i++) {
#pragma unroll
                for (int e = 0; e < 4; e++) cy[2 * i][e] = cy[2 * i + 1][e] = 0.f;
                if (i == NDP - 1) load_w2(i);
                mma_bf16(cy[2 * i], a[i][0], u[i].x, u[i].y);
                mma_bf16(cy[2 * i + 1], a[i][1], u[i].z, u[i].w);
            }
#define Y_(e) (((cy[0][e] + cy[1][e]) + (cy[2][e] + cy[3][e])) + (cy[4][e] + cy[5][e]))
            const float y = (t & 1) ? Y_(2) : Y_(0);
#undef Y_
            if (t < 2) sts32(ydst, y);
            LSC(13);
            asm volatile("bar.arrive 5, 288;" ::: "memory");
        }
    }
}

typedef CUresult (*EncodeTiledFn)(CUtensorMap*, CUtensorMapDataType, cuuint32_t, void*, const cuuint64_t*, const cuuint64_t*,
                                  const cuuint32_t*, const cuuint32_t*, CUtensorMapInterleave, CUtensorMapSwizzle,
                                  CUtensorMapL2promotion, CUtensorMapFloatOOBfill);

void make_map(EncodeTiledFn fn, CUtensorMap* tm, const void* w, const int (&d)[5], const int (&st)[4], const int (&bx)[5],
              CUtensorMapSwizzle sw, int promo) {
    cuuint64_t dims[5], strides[4];
    cuuint32_t box[5], estr[5];
    for (int i = 0; i < 5; i++) { dims[i] = (cuuint64_t)d[i]; box[i] = (cuuint32_t)bx[i]; estr[i] = 1; }
    for (int i = 0; i < 4; i++) strides[i] = (cuuint64_t)st[i];
    fn(tm, CU_TENSOR_MAP_DATA_TYPE_BFLOAT16, 5, const_cast<void*>(w), dims, strides, box, estr, CU_TENSOR_MAP_INTERLEAVE_NONE, sw,
       (CUtensorMapL2promotion)promo, CU_TENSOR_MAP_FLOAT_OOB_FILL_NONE);
}

}

extern "C" void kernel_launch(void* const* d_in, const int* in_sizes, int n_in, void* d_out, int out_size) {
    (void)in_sizes; (void)n_in; (void)out_size;
    static EncodeTiledFn encode = nullptr;
    static Scratch* scratch = nullptr;
    static unsigned char* xarea = nullptr;
    static double tscale = 1.0;
    if (!encode) {
        void* sp = nullptr;
        cudaGetSymbolAddress(&sp, g_scratch);
        scratch = reinterpret_cast<Scratch*>(sp);
        cudaGetSymbolAddress(&sp, g_xarea);
        xarea = reinterpret_cast<unsigned char*>((reinterpret_cast<uintptr_t>(sp) + XA_ALIGN - 1) / XA_ALIGN * XA_ALIGN);
        void* fn = nullptr;
        cudaDriverEntryPointQueryResult st;
        cudaGetDriverEntryPoint("cuTensorMapEncodeTiled", &fn, cudaEnableDefault, &st);
        encode = reinterpret_cast<EncodeTiledFn>(fn);
        int dev = 0, khz = 0, bits = 0;
        cudaGetDevice(&dev);
        cudaDeviceGetAttribute(&khz, cudaDevAttrMemoryClockRate, dev);
        cudaDeviceGetAttribute(&bits, cudaDevAttrGlobalMemoryBusWidth, dev);
        if (khz > 0 && bits > 0) tscale = (2619000.0 * 5120.0) / ((double)khz * bits);
        cudaFuncSetAttribute(fused_decode_kernel, cudaFuncAttributeMaxDynamicSharedMemorySize, SM_TOTAL);
    }
    KParams p;
    p.x = (const __nv_bfloat16*)d_in[0];
    p.wq = (const __nv_bfloat16*)d_in[3];
    p.out = (__nv_bfloat16*)d_out;
    p.sc = scratch;
    p.xa = xarea;
    p.zero = 0;
    p.t_first = (uint32_t)(4 * cfg::T_FIRST * tscale);
    p.t_step = (uint32_t)(cfg::T_STEP * tscale);
    p.t_smax = (uint32_t)(cfg::T_SMAX * tscale);
    p.t_lat = (uint32_t)(4 * (450 + (cfg::T_LAT - 450) * tscale));
    TMaps tm;
    constexpr int R1 = FF * 2, R2 = D_MODEL * 2;
    make_map(encode, &tm.k, d_in[1], {64, NHEAD * SK * 3, 1, 1, 1}, {128, 128, 128, 128}, {64, 96, 1, 1, 1}, CU_TENSOR_MAP_SWIZZLE_128B, cfg::PROMO_KV);
    make_map(encode, &tm.v, d_in[2], {64, NHEAD * SK * 3, 1, 1, 1}, {128, 128, 128, 128}, {64, 96, 1, 1, 1}, CU_TENSOR_MAP_SWIZZLE_128B, cfg::PROMO_KV);
    make_map(encode, &tm.wo, d_in[4], {D_MODEL, NHEAD * DH, 1, 1, 1}, {R2, R2, R2, R2}, {64, 128, 1, 1, 1}, CU_TENSOR_MAP_SWIZZLE_128B, cfg::PROMO_WO);
    make_map(encode, &tm.w1, d_in[6], {FF, 2, 4, 2, 40}, {R1, 4 * R1, 2 * R1, 16 * R1}, {32, 2, 4, 2, 8}, CU_TENSOR_MAP_SWIZZLE_64B, cfg::PROMO_W13);
    make_map(encode, &tm.w3, d_in[7], {FF, 2, 4, 2, 40}, {R1, 4 * R1, 2 * R1, 16 * R1}, {32, 2, 4, 2, 8}, CU_TENSOR_MAP_SWIZZLE_64B, cfg::PROMO_W13);
    make_map(encode, &tm.w2, d_in[8], {D_MODEL, FF, 1, 1, 1}, {R2, R2, R2, R2}, {16, 256, 1, 1, 1}, CU_TENSOR_MAP_SWIZZLE_32B, cfg::PROMO_W2);
    fused_decode_kernel<<<NCTA, NTHREADS, SM_TOTAL, cudaStreamPerThread>>>(p, tm);
}
```

```cpp
#include <cuda_runtime.h>
#include <cuda_bf16.h>
#include <cuda.h>
#include <stdint.h>
#include <math.h>

namespace {

constexpr int D_MODEL = 640;
constexpr int NHEAD = 32;
constexpr int DH = 192;
constexpr int SK = 32768;
constexpr int WIN = 4096;
constexpr int FF = 1536;

constexpr int NCTA = 128;
constexpr int NCONS = 256;
constexpr int NTHREADS = NCONS + 256;
constexpr int ROW_BYTES = DH * 2;
constexpr int TILE_BYTES = 32 * ROW_BYTES;
constexpr int NSLOT = 16;
constexpr int NQT = 5;
constexpr int QSLOT = NSLOT - NQT;
constexpr int NWO = 60;
constexpr int NG = 6;
constexpr int NFFN = 48;
constexpr int NWP = 8;
constexpr int NUP = 5;
constexpr int WPIECE = 16384;
constexpr int NDP = 3;
constexpr int PIECE = 8192;
constexpr int NTAIL = NWP + NDP;
constexpr int N_TAIL0 = 2 * NHEAD;

#define CFG(name, value) constexpr int name = value
#define CFG_OVERRIDE
namespace cfg_default {
CFG(T_FIRST, 1850);
CFG(T_STEP, 1906);
CFG(T_SMAX, 1940);
CFG(CAP, 4);
CFG(MN, 12);
CFG(MA, 4);
CFG(MB, 40);
CFG(PAUSE, 1300);
CFG(KBIAS, 5);
CFG(ADAPT, 60);
CFG(T_LAT, 1230);
CFG(T_WO, 296);
CFG(T_GAP, 95);
CFG(T_UP, 240);
CFG(T_UP2, 120);
CFG(T_W2AT, 1320);
CFG(T_W2, 200);
CFG(T_HAT, 1130);
CFG(T_RESAT, 1750);
CFG(T_AAT, 2420);
CFG(KEEP_AT, 65);
CFG(KEEP, 150);
CFG(HCOPY, 1);
CFG(QDELAY, 1200);
CFG(QDELAY2, 900);
CFG(QSLEEP, 400);
CFG(PDELAY, 2500);
CFG(PDELAY_LAST, 250);
CFG(PDELAY_STEP, 650);
CFG(PREPART, 3);
CFG(RBDELAY, 5000);
CFG(NPROBE, 10);
CFG(VOTES, 3);
CFG(PROMO_KV, 2);
CFG(PROMO_WO, 2);
CFG(PROMO_W13, 2);
CFG(PROMO_W2, 2);
CFG(BOUNDED_MBAR, 0);
}
namespace cfg { using namespace cfg_default; CFG_OVERRIDE }

constexpr uint32_t SBASE = 1024;
constexpr int SM_RING = 0;
constexpr int SM_W2 = NWP * WPIECE;
constexpr int SM_Q = SM_RING + NSLOT * TILE_BYTES;
constexpr int SM_RED = SM_Q + NHEAD * ROW_BYTES;
constexpr int SM_HN = SM_RED + 4096;
constexpr int SM_STAT = SM_HN + D_MODEL * 2;
constexpr int SM_MISC = SM_STAT + 256;
constexpr int SM_BAR = SM_MISC + 128;
constexpr int SM_TOTAL = SM_BAR + 512;
static_assert(SM_TOTAL <= 232448, "shared memory");

struct __align__(128) Scratch {
    uint4 part[NHEAD * 4 * NCTA * 8];
    uint64_t q1[NHEAD * 4 * DH];
    uint4 q2[NHEAD * 32];
    uint32_t epoch;
    uint32_t pad;
    unsigned long long pace[2];
};
__device__ Scratch g_scratch;
constexpr int XA_ALIGN = 1 << 20;
constexpr uint32_t SENT = 0xffffffffu;
constexpr int L_GATHER = 0;
constexpr int HCOPY_BYTES = NG * D_MODEL * 2;
constexpr int L_O = 9 * 4096;
constexpr int L_ACT = 30 * 4096;
constexpr int L_PROBE = 32 * 4096;
constexpr int L_PART = 64 * 4096;
static_assert(2 * (L_PART + 65536) <= XA_ALIGN, "");
__device__ unsigned char g_xarea[2 * XA_ALIGN];
__device__ __forceinline__ uint32_t xa_off(uint32_t l, uint32_t side) {
    const uint32_t k = l >> 12;
    return (2 * k + ((side ^ k ^ (k >> 3) ^ (k >> 4) ^ (k >> 6)) & 1)) * 4096 + (l & 4095);
}

__device__ __forceinline__ uint32_t o_off(uint32_t r) { return L_O + (r >> 7) % NG * 2048 + (r >> 7) / NG * 256 + (r & 127) * 2; }

#define LST(i) do { } while (0)
#define LSC(i) do { } while (0)
#define LSCD(i, v) do { } while (0)
constexpr uint32_t SPIN_LIMIT = cfg::BOUNDED_MBAR ? 1u << 14 : 1u << 22;

__device__ __forceinline__ uint32_t now_q() { uint32_t t; asm volatile("mov.u32 %0, %globaltimer_lo;" : "=r"(t)); return t * 4; }
__device__ __forceinline__ void wait_until(uint32_t due) {
#pragma unroll 1
    for (int n = 0; n < 4096 && (int)(now_q() - due) < 0; n++) { }
}
__device__ __forceinline__ void sleep_until(uint32_t due) {
#pragma unroll 1
    for (int n = 0; n < 4096 && (int)(now_q() - due) < 0; n++) __nanosleep(200);
}
__device__ __forceinline__ uint32_t smem_u32(const void* p) { return (uint32_t)__cvta_generic_to_shared(p); }
__device__ __forceinline__ void mbar_init(uint32_t bar, uint32_t cnt) {
    asm volatile("mbarrier.init.shared::cta.b64 [%0], %1;" ::"r"(bar), "r"(cnt) : "memory");
}
__device__ __forceinline__ void mbar_expect_tx(uint32_t bar, uint32_t bytes) {
    asm volatile("mbarrier.arrive.expect_tx.shared::cta.b64 _, [%0], %1;" ::"r"(bar), "r"(bytes) : "memory");
}
__device__ __forceinline__ void mbar_arrive(uint32_t bar) {
    asm volatile("mbarrier.arrive.shared::cta.b64 _, [%0];" ::"r"(bar) : "memory");
}
__device__ __forceinline__ bool mbar_test(uint32_t bar, uint32_t parity) {
    uint32_t ok;
    asm volatile("{\n.reg .pred p;\nmbarrier.test_wait.parity.shared::cta.b64 p, [%1], %2;\nselp.u32 %0, 1, 0, p;\n}"
                 : "=r"(ok) : "r"(bar), "r"(parity) : "memory");
    return ok;
}
__device__ __forceinline__ bool mbar_try(uint32_t bar, uint32_t parity) {
    uint32_t ok;
    asm volatile("{\n.reg .pred p;\nmbarrier.try_wait.parity.shared::cta.b64 p, [%1], %2;\nselp.u32 %0, 1, 0, p;\n}"
                 : "=r"(ok) : "r"(bar), "r"(parity) : "memory");
    return ok;
}
__device__ __forceinline__ void mbar_wait(uint32_t bar, uint32_t parity) {
    if (cfg::BOUNDED_MBAR) {
        uint32_t n = 0;
        while (!mbar_try(bar, parity)) if (++n > SPIN_LIMIT) __trap();
    } else {
        asm volatile("{\n.reg .pred p;\nW_%=:\nmbarrier.try_wait.parity.shared::cta.b64 p, [%0], %1;\n@!p bra W_%=;\n}" ::"r"(bar), "r"(parity) : "memory");
    }
}
__device__ __forceinline__ void tma_tile(uint32_t dst, const CUtensorMap* tm, int c1, uint32_t bar, uint64_t pol) {
    asm volatile("cp.async.bulk.tensor.5d.shared::cluster.global.mbarrier::complete_tx::bytes.L2::cache_hint [%0], [%1, {%4, %3, %4, %4, %4}], [%2], %5;"
                 ::"r"(dst), "l"(reinterpret_cast<uint64_t>(tm)), "r"(bar), "r"(c1), "r"(0), "l"(pol) : "memory");
}
__device__ __forceinline__ void tma_5d(uint32_t dst, const CUtensorMap* tm, int c0, int c1, int c2, int c4, uint32_t bar) {
    asm volatile("cp.async.bulk.tensor.5d.shared::cluster.global.mbarrier::complete_tx::bytes [%0], [%1, {%3, %4, %5, %7, %6}], [%2];"
                 ::"r"(dst), "l"(reinterpret_cast<uint64_t>(tm)), "r"(bar), "r"(c0), "r"(c1), "r"(c2), "r"(c4), "r"(0) : "memory");
}
__device__ __forceinline__ uint32_t bits(uint32_t v) { return v; }
__device__ __forceinline__ uint32_t bits(float v) { return __float_as_uint(v); }
__device__ __forceinline__ uint32_t bits(const void* v) { return (uint32_t)(uintptr_t)v ^ (uint32_t)((uintptr_t)v >> 32); }
template <class... T> __device__ __forceinline__ uint32_t after(uint32_t zero, uint32_t bar, T... v) { return bar | ((bits(v) ^ ...) & zero); }
__device__ __forceinline__ void sts32(uint32_t a, float v) { asm volatile("st.shared.f32 [%0], %1;" ::"r"(a), "f"(v) : "memory"); }
__device__ __forceinline__ void sts64(uint32_t a, uint32_t x, uint32_t y) { asm volatile("st.shared.v2.u32 [%0], {%1, %2};" ::"r"(a), "r"(x), "r"(y) : "memory"); }
__device__ __forceinline__ void cons_sync() { asm volatile("bar.sync 1, 256;" ::: "memory"); }

__device__ __forceinline__ uint4 lds128(uint32_t a) {
    uint4 v;
    asm volatile("ld.shared.v4.u32 {%0,%1,%2,%3}, [%4];" : "=r"(v.x), "=r"(v.y), "=r"(v.z), "=r"(v.w) : "r"(a));
    return v;
}
__device__ __forceinline__ float4 lds128f(uint32_t a) {
    float4 v;
    asm volatile("ld.shared.v4.f32 {%0,%1,%2,%3}, [%4];" : "=f"(v.x), "=f"(v.y), "=f"(v.z), "=f"(v.w) : "r"(a) : "memory");
    return v;
}
__device__ __forceinline__ float2 lds64f(uint32_t a) {
    float2 v;
    asm volatile("ld.shared.v2.f32 {%0,%1}, [%2];" : "=f"(v.x), "=f"(v.y) : "r"(a) : "memory");
    return v;
}
__device__ __forceinline__ uint32_t lds32(uint32_t a) {
    uint32_t v;
    asm volatile("ld.shared.u32 %0, [%1];" : "=r"(v) : "r"(a));
    return v;
}
__device__ __forceinline__ void ldsm_x4(uint32_t* r, uint32_t a) {
    asm volatile("ldmatrix.sync.aligned.m8n8.x4.shared.b16 {%0,%1,%2,%3}, [%4];"
                 : "=r"(r[0]), "=r"(r[1]), "=r"(r[2]), "=r"(r[3]) : "r"(a));
}
__device__ __forceinline__ void ldsm_x4_t(uint32_t* r, uint32_t a) {
    asm volatile("ldmatrix.sync.aligned.m8n8.x4.trans.shared.b16 {%0,%1,%2,%3}, [%4];"
                 : "=r"(r[0]), "=r"(r[1]), "=r"(r[2]), "=r"(r[3]) : "r"(a));
}
__device__ __forceinline__ void mma_bf16(float* c, const uint32_t* a, uint32_t b0, uint32_t b1) {
    asm volatile("mma.sync.aligned.m16n8k16.row.col.f32.bf16.bf16.f32 {%0,%1,%2,%3}, {%4,%5,%6,%7}, {%8,%9}, {%0,%1,%2,%3};"
                 : "+f"(c[0]), "+f"(c[1]), "+f"(c[2]), "+f"(c[3]) : "r"(a[0]), "r"(a[1]), "r"(a[2]), "r"(a[3]), "r"(b0), "r"(b1));
}
__device__ __forceinline__ float bf_lo(uint32_t u) { return __uint_as_float(u << 16); }
__device__ __forceinline__ float bf_hi(uint32_t u) { return __uint_as_float(u & 0xffff0000u); }
__device__ __forceinline__ uint32_t pack_bf(float hi, float lo) { uint32_t r; asm("cvt.rn.bf16x2.f32 %0, %1, %2;" : "=r"(r) : "f"(hi), "f"(lo)); return r; }
__device__ __forceinline__ float bfr(float x) { return __uint_as_float(pack_bf(x, 0.f)); }

__device__ __forceinline__ uint64_t pk(float v, uint32_t tag) { return ((uint64_t)tag << 32) | (uint64_t)__float_as_uint(v); }
__device__ __forceinline__ void ll_st1(uint64_t* p, float a, uint32_t tag) {
    asm volatile("st.relaxed.gpu.global.b64 [%0], %1;" ::"l"(p), "l"(pk(a, tag)) : "memory");
}
__device__ __forceinline__ uint4 ll_ld2(const uint4* p) {
    uint4 v;
    asm volatile("{\n.reg .b64 a, b;\nld.relaxed.gpu.global.v2.b64 {a, b}, [%4];\nmov.b64 {%0, %1}, a;\nmov.b64 {%2, %3}, b;\n}"
                 : "=r"(v.x), "=r"(v.y), "=r"(v.z), "=r"(v.w) : "l"(p) : "memory");
    return v;
}
__device__ __forceinline__ uint32_t in_word(float v) {
    uint32_t r;
    asm("min.u32 %0, %1, 0xfffffffe;" : "=r"(r) : "r"(__float_as_uint(v)));
    return r;
}
__device__ __forceinline__ void in_st1(void* p, float v) {
    asm volatile("st.relaxed.gpu.global.u32 [%0], %1;" ::"l"(p), "r"(in_word(v)) : "memory");
}
__device__ __forceinline__ void in_st4(void* p, uint32_t a, uint32_t b, uint32_t c, uint32_t d) {
    asm volatile("st.relaxed.gpu.global.v4.u32 [%0], {%1, %2, %3, %4};" ::"l"(p), "r"(a), "r"(b), "r"(c), "r"(d) : "memory");
}
__device__ __forceinline__ uint32_t in_ld1(const void* p) {
    uint32_t v;
    asm volatile("ld.relaxed.gpu.global.u32 %0, [%1];" : "=r"(v) : "l"(p) : "memory");
    return v;
}
__device__ __forceinline__ uint4 in_ld4(const void* p) {
    uint4 v;
    asm volatile("ld.relaxed.gpu.global.v4.u32 {%0, %1, %2, %3}, [%4];" : "=r"(v.x), "=r"(v.y), "=r"(v.z), "=r"(v.w) : "l"(p) : "memory");
    return v;
}
__device__ __forceinline__ void in_ld2p(const void* p, uint2& v, bool on) {
    asm volatile("{\n.reg .pred q;\nsetp.ne.u32 q, %3, 0;\n@q ld.relaxed.gpu.global.v2.u32 {%0, %1}, [%2];\n}"
                 : "+r"(v.x), "+r"(v.y) : "l"(p), "r"((uint32_t)on) : "memory");
}
__device__ __forceinline__ bool in_ok(const uint2& v) { return max(v.x, v.y) != SENT; }
__device__ __forceinline__ void in_ld4p(const void* p, uint4& v, bool on) {
    asm volatile("{\n.reg .pred q;\nsetp.ne.u32 q, %5, 0;\n@q ld.relaxed.gpu.global.v4.u32 {%0, %1, %2, %3}, [%4];\n}"
                 : "+r"(v.x), "+r"(v.y), "+r"(v.z), "+r"(v.w) : "l"(p), "r"((uint32_t)on) : "memory");
}
__device__ __forceinline__ void pkt_st(uint4* p, uint32_t x, uint32_t y, uint32_t z, uint32_t w) {
    asm volatile("{\n.reg .b128 t;\n.reg .b64 a, b;\nmov.b64 a, {%1, %2};\nmov.b64 b, {%3, %4};\nmov.b128 t, {a, b};\nst.relaxed.gpu.global.b128 [%0], t;\n}"
                 ::"l"(p), "r"(x), "r"(y), "r"(z), "r"(w) : "memory");
}
__device__ __forceinline__ void pkt_ldp(const uint4* p, uint4& v, bool on) {
    asm volatile("{\n.reg .pred q;\n.reg .b128 t;\n.reg .b64 a, b;\nsetp.ne.u32 q, %5, 0;\nmov.b64 a, {%0, %1};\nmov.b64 b, {%2, %3};\nmov.b128 t, {a, b};\n"
                 "@q ld.relaxed.gpu.global.b128 t, [%4];\nmov.b128 {a, b}, t;\nmov.b64 {%0, %1}, a;\nmov.b64 {%2, %3}, b;\n}"
                 : "+r"(v.x), "+r"(v.y), "+r"(v.z), "+r"(v.w) : "l"(p), "r"((uint32_t)on) : "memory");
}

__device__ __forceinline__ float sqrt_fast(float x) { float r; asm("sqrt.approx.ftz.f32 %0, %1;" : "=f"(r) : "f"(x)); return r; }
__device__ __forceinline__ float rcp_fast(float x) { float r; asm("rcp.approx.ftz.f32 %0, %1;" : "=f"(r) : "f"(x)); return r; }
__device__ __forceinline__ float ex2(float x) { float r; asm("ex2.approx.ftz.f32 %0, %1;" : "=f"(r) : "f"(x)); return r; }
constexpr float L2E = 1.4426950408889634f;
__device__ __forceinline__ void ln_sums(const uint2* v, float& t1, float& t2) {
    float s1[5], s2[5];
#pragma unroll
    for (int i = 0; i < 5; i++) {
        const float a0 = bf_lo(v[i].x), a1 = bf_hi(v[i].x), a2 = bf_lo(v[i].y), a3 = bf_hi(v[i].y);
        s1[i] = (a0 + a1) + (a2 + a3);
        s2[i] = fmaf(a0, a0, a1 * a1) + fmaf(a2, a2, a3 * a3);
    }
    t1 = ((s1[0] + s1[1]) + (s1[2] + s1[3])) + s1[4]; t2 = ((s2[0] + s2[1]) + (s2[2] + s2[3])) + s2[4];
#pragma unroll
    for (int o = 16; o > 0; o >>= 1) { t1 += __shfl_xor_sync(0xffffffffu, t1, o); t2 += __shfl_xor_sync(0xffffffffu, t2, o); }
}
__device__ __forceinline__ void ln_finish(float t1, float t2, float& mean_b, float& inv_den) {
    const float mean = t1 * (1.0f / D_MODEL);
    const float var = fmaxf(fmaf(-mean, mean, t2 * (1.0f / D_MODEL)), 0.f);
    mean_b = bfr(mean);
    inv_den = rcp_fast(bfr(sqrt_fast(bfr(bfr(var) + 1e-5f))));
}

struct KParams {
    const __nv_bfloat16* wq;
    uint32_t t_first;
    uint32_t t_step;
    const __nv_bfloat16* x;
    Scratch* sc;
    unsigned char* xa;
    __nv_bfloat16* out;
    uint32_t t_smax;
    uint32_t t_lat;
    uint32_t zero;
};
struct TMaps { CUtensorMap k, v, wo, w1, w3, w2; };

__global__ void __launch_bounds__(NTHREADS, 1)
fused_decode_kernel(const KParams p, const __grid_constant__ TMaps tm) {
    extern __shared__ __align__(1024) unsigned char smem[];
    const uint32_t sbase = smem_u32(smem);
    const int tid = threadIdx.x;
    const int b = blockIdx.x;
    const int head = b >> 2, sp = b & 3;
    {
        if (tid < 192) {
            const uint32_t rg = tid * 2731 >> 16, ch = tid - rg * 24;
            const char* src = reinterpret_cast<const char*>(p.wq) + (uint32_t)(sp * 160 * (NHEAD * DH * 2) + head * ROW_BYTES + rg * (NHEAD * DH * 2) + ch * 16);
            uint32_t dst = SBASE + SM_RING + QSLOT * TILE_BYTES + ((tid ^ (tid >> 3 & 7)) << 4);
#pragma unroll 4
            for (int i = 0; i < 20; i++) {
                asm volatile("cp.async.cg.shared.global [%0], [%1], 16;" ::"r"(dst), "l"(src) : "memory");
                dst += 8 * ROW_BYTES;
                src += (size_t)8 * (NHEAD * DH * 2);
            }
        }
    }
    const int warp = __shfl_sync(0xffffffffu, tid >> 5, 0), lane = tid & 31;
    const int rr = !(b & 1) ? b >> 1 : (b & 15) < 12 ? (b >> 4) * 6 + (b >> 1 & 7) : NFFN + (b >> 4) * 2 + (b >> 1 & 1);
    const bool is_wo = !(b & 1) && rr < NWO, is_ffn = (b & 1) && rr < NFFN, is_out = !is_ffn;
    const int og = (rr >> 2) + (b & 1) * 4, oh = og >= 10, oq = (og - 10 * oh) * 4 + (rr & 3);
    const int kg = min(rr / 10, NG - 1), ng = rr % 10;
    const uint32_t bar_full = sbase + SM_BAR;
    const uint32_t bar_empty = sbase + SM_BAR + 128;
    const uint32_t bar_tail = sbase + SM_BAR + 256;
    const uint32_t bar_set = bar_tail + 8 * NTAIL;
    const uint32_t bar_pace = bar_set + 8;
    const uint32_t bar_q = bar_set + 16;
    const uint32_t bar_part = bar_set + 24;
    volatile uint32_t* s_pace = reinterpret_cast<volatile uint32_t*>(smem + SM_MISC + 64);
    auto tail_time = [&](int t) { return s_pace[0] + (s_pace[1] * (((N_TAIL0 - cfg::ADAPT) * 478 + NWP * cfg::T_WO + t) * 256 / 478) >> 8); };

    if (warp == 8) {
        const uint32_t c_start = now_q();
        if (lane >= 1 && lane <= 6) asm volatile("prefetch.tensormap [%0];" ::"l"(reinterpret_cast<uint64_t>(&tm.k + (lane - 1))) : "memory");
        uint64_t pol_stream;
        asm volatile("createpolicy.fractional.L2::evict_first.b64 %0, 1.0;" : "=l"(pol_stream));
        if (lane == 0) {
#pragma unroll 1
            for (int i = 0; i < NSLOT; i++) { mbar_init(bar_full + 8 * i, 1); mbar_init(bar_empty + 8 * i, 1); }
#pragma unroll 1
            for (int i = 0; i < NTAIL + 4; i++) mbar_init(bar_tail + 8 * i, i == NTAIL + 2 ? 4 : 1);
            asm volatile("fence.mbarrier_init.release.cluster;" ::: "memory");
        }
        __syncwarp();
        asm volatile("bar.arrive 2, 288;" ::: "memory");
        asm volatile("bar.arrive 3, 64;" ::: "memory");
        asm volatile("bar.arrive 4, 64;" ::: "memory");
        if (is_ffn) asm volatile("bar.arrive 10, 192;" ::: "memory");
        if (lane == 0) {
            uint32_t due = c_start + p.t_first, step = p.t_step;
#pragma unroll 1
            for (int n = 0; n < N_TAIL0; n++) {
                const int slot = n & (NSLOT - 1);
                const int use = (n >> 4) + (slot >= QSLOT);
                if (n >= cfg::CAP) mbar_wait(bar_full + 8 * ((n - cfg::CAP) & (NSLOT - 1)), ((n - cfg::CAP) >> 4) & 1);
                if (use >= 1) mbar_wait(bar_empty + 8 * slot, (use - 1) & 1);
                if (n == cfg::ADAPT) { mbar_wait(bar_pace, 0); due = s_pace[0]; step = s_pace[1]; }
                const uint32_t full = bar_full + 8 * slot;
                mbar_expect_tx(full, TILE_BYTES);
                wait_until(due);
                LST(128 + n);
                tma_tile(sbase + SM_RING + slot * TILE_BYTES, &tm.k + (n & 1), ((n >> 1) * SK + (SK - WIN) + b * 32) * 3, full, pol_stream);
                due += step;
            }
            int rel = 0;
            auto released = [&](int end) {
#pragma unroll 1
                for (; rel * TILE_BYTES < end; rel++) mbar_wait(bar_empty + 8 * rel, rel < QSLOT);
            };
            const uint32_t t_wo = step * (cfg::T_WO * 4096 / 478) >> 12;
            if (is_wo) {
#pragma unroll 1
                for (int j = 0; j < NWP; j++) {
                    released((j + 1) * WPIECE);
                    mbar_expect_tx(bar_tail + 8 * j, WPIECE);
                    wait_until(due);
                    LST(128 + N_TAIL0 + j);
                    tma_5d(sbase + j * WPIECE, &tm.wo, ng * 64, j * (NG * 128) + kg * 128, 0, 0, bar_tail + 8 * j);
                    due += t_wo;
                }
            } else {
                due += NWP * t_wo;
            }
            due += 4 * cfg::T_GAP;
            if (is_out) {
                due += step * (cfg::T_W2AT * 4096 / 478) >> 12;
                released(SM_W2 + NDP * PIECE);
#pragma unroll
                for (int j = 0; j < NDP; j++) mbar_expect_tx(bar_tail + 8 * (NWP + j), PIECE);
                sleep_until(due - 4 * 400);
#pragma unroll
                for (int j = 0; j < NDP; j++) {
                    wait_until(due);
                    tma_5d(sbase + SM_W2 + j * PIECE, &tm.w2, oq * 16, (oh * NDP + j) * 256, 0, 0, bar_tail + 8 * (NWP + j));
                    LST(128 + N_TAIL0 + NWP + j);
                    due += step * (cfg::T_W2 * 4096 / 478) >> 12;
                }
            } else if (is_ffn) {
                released(NUP * WPIECE);
#pragma unroll
                for (int j = 0; j <= NUP; j++) mbar_expect_tx(bar_tail + 8 * j, j < NUP - 1 ? WPIECE : WPIECE / 2);
                sleep_until(due - 4 * 400);
#pragma unroll
                for (int j = 0; j <= NUP; j++) {
                    const uint32_t full = bar_tail + 8 * j;
                    wait_until(due);
#pragma unroll
                    for (int e = min(2 * j, j + NUP - 1); e < min(2 * j + 2, j + NUP); e++)
                        tma_5d(sbase + e * (WPIECE / 2), e < NUP ? &tm.w1 : &tm.w3, rr * 32, 0, 0, e % NUP * 8, full);
                    LST(128 + N_TAIL0 + j);
                    due += step * ((j < NUP - 1 ? cfg::T_UP : cfg::T_UP2) * 4096 / 478) >> 12;
                }
            }
        }
    } else if (warp == 10) {
        if (sbase != SBASE) __trap();
        asm volatile("bar.sync 4, 64;" ::: "memory");
        if (lane == 0) {
            uint32_t epoch0;
            asm volatile("ld.relaxed.gpu.global.u32 %0, [%1];" : "=r"(epoch0) : "l"(&p.sc->epoch) : "memory");
            constexpr int MN = cfg::MN;
            const uint32_t t0 = now_q();
            uint32_t sa = 0, sb = 0;
#pragma unroll 1
            for (int n = 0; n < cfg::MB + MN; n++) {
#pragma unroll 1
                for (int k = 0; k < 256 && !mbar_try(bar_full + 8 * (n & (NSLOT - 1)), (n >> 4) & 1); k++) { }
                const uint32_t t = now_q() - t0;
                LST(n);
                if ((uint32_t)(n - cfg::MA) < MN) sa += t;
                if (n >= cfg::MB) sb += t;
            }
            const uint32_t mb = t0 + sb / MN;
            unsigned long long* pace = p.sc->pace + ((epoch0 + 1) & 1);
            mbar_wait(bar_set, 0);
            asm volatile("red.relaxed.gpu.global.add.u64 [%0], %1;" ::"l"(pace), "l"((unsigned long long)mb << 32 | min((sb - sa) / (4 * MN), 0xffffu) << 8 | 1) : "memory");
            if (b == 0) p.sc->pace[epoch0 & 1] = 0;
            unsigned long long v;
            uint32_t n = 0, cnt;
#pragma unroll 1
            do {
                __nanosleep(n ? 200 : 1000);
                asm volatile("ld.relaxed.gpu.global.u64 %0, [%1];" : "=l"(v) : "l"(pace) : "memory");
                cnt = (uint32_t)v & 0xff;
                if (++n > SPIN_LIMIT) __trap();
            } while (cnt < NCTA);
            uint32_t step = ((uint32_t)v >> 8) / (NCTA / 4 * (cfg::MB - cfg::MA));
            const uint32_t pause = step > 2 * p.t_smax - p.t_step ? cfg::PAUSE : 0;
            step = min(max(step - pause * 4 / (cfg::MB - cfg::MA), p.t_step), p.t_smax);
            s_pace[0] = mb + (int)((uint32_t)(v >> 32) - NCTA * mb) / NCTA + step * (2 * (cfg::ADAPT - cfg::MB) - (MN - 1)) / 2 - p.t_lat
                        - (step - p.t_step) * cfg::KBIAS;
            s_pace[1] = step;
            mbar_arrive(bar_pace);
            LST(89);
        }
    } else if (warp == 9) {
        const uint32_t c_start = now_q();
        uint32_t epoch0;
        asm volatile("ld.relaxed.gpu.global.u32 %0, [%1];" : "=r"(epoch0) : "l"(&p.sc->epoch) : "memory");
        sleep_until(c_start + p.t_first);
        unsigned char* slot[2];
        slot[0] = p.xa + xa_off(o_off(b * 48 + (lane % 6) * 8), lane / 6 & 1);
        slot[1] = p.xa + (is_wo ? xa_off(L_GATHER + (lane >> 4) * HCOPY_BYTES + (kg * D_MODEL + ng * 64 + (lane & 7) * 8) * 2, lane >> 3 & 1)
                                : xa_off(L_ACT + rr * 64 + (lane & 3) * 16, lane >> 2 & 1));
        const int n2 = is_wo ? 16 * cfg::HCOPY : is_ffn ? 8 : 0;
#pragma unroll
        for (int i = 0; i < 2; i++) if (lane < (i ? n2 : 12)) in_st4(slot[i], SENT, SENT, SENT, SENT);
#pragma unroll
        for (int i = 2; i <= cfg::PREPART; i++) pkt_st(p.sc->part + (((NHEAD - i) * 4 + (lane & 3)) * NCTA + b) * 8 + (lane >> 2), 0, 0, 0, epoch0 & 3);
#pragma unroll
        for (int i = 0; i < 2; i++) pkt_st(reinterpret_cast<uint4*>(p.xa + xa_off(L_PART + (((lane & 3) * NCTA + b) * 8 + (lane >> 2)) * 16, i)), 0, 0, 0, epoch0 & 3);
        unsigned char* probe = p.xa + xa_off(L_PROBE + b * 1024 + (lane >> 1 & 7) * 128 + (lane & 1) * 16, lane >> 4);
        in_st4(probe, SENT, SENT, SENT, SENT);
        const bool clr = is_out && !oh && lane < 2;
        if (clr) in_st4(p.out + oq * 16 + lane * 8, 0, 0, 0, 0);
        sleep_until(now_q() + 4 * cfg::RBDELAY + b * 60);
        uint32_t acc = SENT;
#pragma unroll
        for (int i = 0; i < 2; i++) if (lane < (i ? n2 : 12)) acc &= in_ld1(slot[i]);
        if (clr) acc &= ~in_ld1(p.out + oq * 16 + lane * 8);
        if (__any_sync(0xffffffffu, acc != SENT)) __trap();
        int vote = 0;
        uint32_t lat[2] = {0, 0};
#pragma unroll 1
        for (int r = 0; r <= cfg::NPROBE && abs(vote) < cfg::VOTES; r++) {
            __nanosleep(300);
            uint32_t d[2];
#pragma unroll
            for (int i = 0; i < 2; i++) {
                const uint32_t c0 = (uint32_t)clock();
                if (__any_sync(0xffffffffu, in_ld1(p.xa + xa_off(L_PROBE + b * 1024 + (lane & 7) * 128, i)) != SENT)) __trap();
                d[i] = (uint32_t)clock() - c0;
                if (r) lat[i] += min(d[i], 1500u);
            }
            if (r) vote = __shfl_sync(0xffffffffu, vote + (d[1] < d[0]) - (d[0] < d[1]), 0);
        }
        const uint32_t sel = vote ? vote > 0 : lat[1] < lat[0];
        const uint32_t tag = epoch0 + 1;
        asm volatile("bar.sync 3, 64;" ::: "memory");
        if (lane == 0) { s_pace[2] = sel; mbar_arrive(bar_set); }
        {
            mbar_wait(bar_pace, 0);
            sleep_until(s_pace[0] + (cfg::KEEP_AT - cfg::ADAPT) * s_pace[1]);
            const uint32_t t_res = tail_time(cfg::T_RESAT);
            float c[4] = {0.f, 0.f, 0.f, 0.f};
            const uint32_t z[4] = {p.zero, p.zero, p.zero, p.zero};
            uint32_t n = 0;
#pragma unroll 1
            do {
                mma_bf16(c, z, p.zero, p.zero);
                __nanosleep(cfg::KEEP);
                n += 1 + __float_as_uint(c[0]);
            } while (!__all_sync(0xffffffffu, is_ffn ? mbar_test(bar_tail, 0) : (int)(now_q() - t_res) >= 0) && n < SPIN_LIMIT);
            if (is_ffn) {
                unsigned char* adst = p.xa + xa_off(L_ACT + rr * 64 + (lane >> 3) * 16 + (lane & 3) * 4, lane >> 2 & 1);
                uint32_t src = sbase + SM_RED + lane * 8;
                asm volatile("bar.sync %0, 192;" ::"r"(after(p.zero, 11, adst, src)) : "memory");
                float t1, t2, mean_b, inv_den;
                {
                    float q1[5], q2[5];
#pragma unroll
                    for (int i = 0; i < 5; i++) {
                        const float4 a = lds128f(sbase + SM_STAT + i * 48), c = lds128f(sbase + SM_STAT + i * 48 + 16), d = lds128f(sbase + SM_STAT + i * 48 + 32);
                        q2[i] = ((a.x + a.y) + (a.z + a.w)) + ((c.x + c.y) + (c.z + c.w));
                        q1[i] = (d.x + d.y) + (d.z + d.w);
                    }
                    t1 = ((q1[0] + q1[1]) + (q1[2] + q1[3])) + q1[4]; t2 = ((q2[0] + q2[1]) + (q2[2] + q2[3])) + q2[4];
                }
                ln_finish(t1, t2, mean_b, inv_den);
                float2 r[8];
#define S_(c) (((r[0].c + r[1].c) + (r[2].c + r[3].c)) + ((r[4].c + r[5].c) + (r[6].c + r[7].c)))
                asm volatile("bar.sync %0, 288;" ::"r"(after(p.zero, 8, mean_b, inv_den)) : "memory");
#pragma unroll
                for (int i = 0; i < 8; i++) r[i] = lds64f(src + i * 256);
                const float gate = bfr(fmaf(-mean_b, S_(y), S_(x)) * inv_den);
                const float silu = bfr(__fdividef(gate, 1.0f + ex2(-gate * L2E)));
                asm volatile("bar.sync %0, 288;" ::"r"(after(p.zero, 5, silu)) : "memory");
#pragma unroll
                for (int i = 0; i < 8; i++) r[i] = lds64f(src + 2048 + i * 256);
                const float act = silu * bfr(fmaf(-mean_b, S_(y), S_(x)) * inv_den);
#undef S_
                const float oth = __shfl_xor_sync(0xffffffffu, act, 4);
                in_st1(adst, __uint_as_float((lane & 4) ? pack_bf(act, oth) : pack_bf(oth, act)));
                if (lane == 0) LST(110);
            }
            if (is_out) {
                const int col = oq * 16 + (lane & 15);
                float res = 0.f;
                if (!oh) {
                    uint32_t u[NG], xv;
                    asm volatile("ld.global.nc.u16 %0, [%1];" : "=r"(xv) : "l"(p.x + col));
                    n = 0;
#pragma unroll 1
                    do {
#pragma unroll
                        for (int i = 0; i < NG; i++) u[i] = in_ld1(p.xa + xa_off(L_GATHER + rr % cfg::HCOPY * HCOPY_BYTES + (i * D_MODEL + (col & ~1)) * 2, sel));
                        if (++n > SPIN_LIMIT) __trap();
                    } while (__any_sync(0xffffffffu, max(max(max(u[0], u[1]), max(u[2], u[3])), max(u[4], u[5])) == SENT));
                    if (b == 0 && lane == 0) p.sc->epoch = tag;
#define F_(i) ((lane & 1) ? bf_hi(u[i]) : bf_lo(u[i]))
                    res = bfr(bf_lo(xv) + bfr(((F_(0) + F_(1)) + (F_(2) + F_(3))) + (F_(4) + F_(5))));
#undef F_
                }
                mma_bf16(c, z, p.zero, p.zero);
                mbar_wait(after(p.zero, bar_tail + 8 * NWP, c[0]), 0);
                mma_bf16(c, z, p.zero, p.zero);
                res += c[0];
                __nv_bfloat16* dst = p.out + (col & ~1);
                uint32_t src = sbase + SM_HN + (lane & 15) * 48;
                asm volatile("bar.sync %0, 288;" ::"r"(after(p.zero, 5, src, dst, res)) : "memory");
                const float4 ra = lds128f(src), rb = lds128f(src + 16);
                const float e = ((ra.x + ra.y) + (ra.z + ra.w)) + (((rb.x + rb.y) + (rb.z + rb.w)) + res);
                if (lane < 16) asm volatile("red.relaxed.gpu.global.add.noftz.bf16x2 [%0], %1;" ::"l"(dst), "r"((lane & 1) ? pack_bf(e, 0.f) : pack_bf(0.f, e)) : "memory");
                if (lane == 0) LST(96);
            }
        }
    } else if (warp > 10) {
        if (is_ffn) {
            const int col = (tid - 352) * 4;
            uint2 xres;
            asm volatile("bar.sync 10, 192;" ::: "memory");
            mbar_wait(bar_pace, 0);
            asm volatile("ld.global.nc.v2.u32 {%0, %1}, [%2];" : "=r"(xres.x), "=r"(xres.y) : "l"(p.x + col) : "memory");
            const unsigned char* gsrc[NG];
            uint2 u[NG];
#pragma unroll
            for (int i = 0; i < NG; i++) gsrc[i] = p.xa + xa_off(L_GATHER + rr % cfg::HCOPY * HCOPY_BYTES + (i * D_MODEL + col) * 2, s_pace[2]);
            const uint32_t hdst = sbase + SM_HN + col * 2;
            const bool diag = (lane & 3) == (lane >> 3);
            const uint32_t sdst = sbase + SM_STAT + (warp - 11) * 48 + (diag ? (lane >> 2) : 8 + (lane & 3)) * 4;
            const uint32_t at = after(p.zero, tail_time(cfg::T_HAT), gsrc[0], gsrc[1], gsrc[2], gsrc[3], gsrc[4], gsrc[5], hdst, sdst, xres.x);
            sleep_until(at - 4 * 300);
            wait_until(at);
#pragma unroll
            for (int i = 0; i < NG; i++) { u[i] = make_uint2(0, 0); in_ld2p(gsrc[i], u[i], true); }
            uint32_t n = 0;
#pragma unroll 1
            while (__any_sync(0xffffffffu, max(max(max(u[0].x, u[0].y), max(u[1].x, u[1].y)), max(max(max(u[2].x, u[2].y), max(u[3].x, u[3].y)),
                                                                                                max(max(u[4].x, u[4].y), max(u[5].x, u[5].y)))) == SENT)) {
#pragma unroll
                for (int i = 0; i < NG; i++) in_ld2p(gsrc[i], u[i], !in_ok(u[i]));
                if (++n > SPIN_LIMIT) __trap();
            }
#define F_(f, c) (f(xres.c) + bfr(((f(u[0].c) + f(u[1].c)) + (f(u[2].c) + f(u[3].c))) + (f(u[4].c) + f(u[5].c))))
            const uint32_t hp0 = pack_bf(F_(bf_hi, x), F_(bf_lo, x)), hp1 = pack_bf(F_(bf_hi, y), F_(bf_lo, y));
#undef F_
            sts64(hdst, hp0, hp1);
            asm volatile("bar.arrive 9, 416;" ::: "memory");
            float cs[4] = {0.f, 0.f, 0.f, 0.f};
            const uint32_t sa[4] = {hp0, 0x3f803f80u, hp1, 0x3f803f80u};
            mma_bf16(cs, sa, hp0, hp1);
            if (diag || (!(lane & 4) && (lane & 3) == (lane >> 3 ^ 1))) sts32(sdst, !diag ? cs[2] + cs[3] : (lane & 4) ? cs[1] : cs[0]);
            asm volatile("bar.arrive 11, 192;" ::: "memory");
            if (lane == 0) LST(100);
        }
    } else {
        const int t = lane & 3, g = lane >> 2;
        const int arow = (lane & 7) + ((lane >> 4) << 3), ahalf = (lane >> 3) & 1;
        uint32_t epoch0;
        const char* xb = reinterpret_cast<const char*>(p.x);
        asm volatile("ld.relaxed.gpu.global.u32 %0, [%1];" : "=r"(epoch0) : "l"(&p.sc->epoch) : "memory");
        uint64_t* q1dst = p.sc->q1 + ((head * 4 + (warp & 3)) * 4 + sp) * 48 + min(t, 2) * 16 + g;
        uint4* q2dst = p.sc->q2 + (head * 8 + sp * 2 + lane / 12) * 4 + t;
        if (warp == 7) {
            uint2 xu[5];
#pragma unroll
            for (int i = 0; i < 5; i++) asm volatile("ld.global.nc.v2.u32 {%0, %1}, [%2];" : "=r"(xu[i].x), "=r"(xu[i].y) : "l"(xb + i * 256 + lane * 8));
            float t1, t2, mean_b, inv_den;
            ln_sums(xu, t1, t2);
            ln_finish(t1, t2, mean_b, inv_den);
#define N_(v) (bfr((v) - mean_b) * inv_den)
#pragma unroll
            for (int i = 0; i < 5; i++)
                sts64(sbase + SM_HN + i * 256 + lane * 8, pack_bf(N_(bf_hi(xu[i].x)), N_(bf_lo(xu[i].x))), pack_bf(N_(bf_hi(xu[i].y)), N_(bf_lo(xu[i].y))));
#undef N_
        } else {
            if (warp < 4 && t < 3) { ll_st1(q1dst, 0.f, 0); ll_st1(q1dst + 8, 0.f, 0); }
            if (warp == 4 && lane < 24 && lane % 12 < 4) pkt_st(q2dst, 0, 0, 0, 0);
        }
        asm volatile("cp.async.wait_all;" ::: "memory");
        if (lane == 0) LST(80 + warp);
        asm volatile("bar.sync 2, 288;" ::: "memory");
        const uint32_t tag = epoch0 + 1;
        auto block = [&](int i) { const int unit = arow * 3 + (i >> 2); return sbase + SM_RING + unit * 128 + ((((i & 3) * 2 + ahalf) ^ (unit & 7)) << 4); };

        if (warp < 4) {
            {
                float c[3][4];
                uint32_t wa[3];
#pragma unroll
                for (int k = 0; k < 3; k++) { c[k][0] = c[k][1] = c[k][2] = c[k][3] = 0.f; wa[k] = block(warp * 3 + k) + QSLOT * TILE_BYTES; }
                const uint32_t xa = sbase + SM_HN + sp * 320 + t * 4;
#pragma unroll 2
                for (int ks = 0; ks < 2 * NQT; ks++) {
                    const uint32_t b0 = lds32(xa + ks * 32), b1 = lds32(xa + ks * 32 + 16);
#pragma unroll
                    for (int k = 0; k < 3; k++) { uint32_t a[4]; ldsm_x4_t(a, wa[k] + ks * (TILE_BYTES / 2)); mma_bf16(c[k], a, b0, b1); }
                }
                if (t < 3) {
                    ll_st1(q1dst, t == 0 ? c[0][0] : t == 1 ? c[1][0] : c[2][0], tag);
                    ll_st1(q1dst + 8, t == 0 ? c[0][2] : t == 1 ? c[1][2] : c[2][2], tag);
                }
                asm volatile("bar.sync 6, 128;" ::: "memory");
                if (tid < NQT) mbar_arrive(bar_empty + 8 * (QSLOT + tid));
                if (tid == 0) LST(90);
            }
            const uint32_t ta[3] = {block(0), block(4), block(8)};
            mbar_wait(bar_q, 0);
            if (tid == 0) LST(92);
#pragma unroll 1
            for (int h = warp; h < NHEAD; h += 4) {
                const int slot = (2 * h) & (NSLOT - 1);
                const uint32_t par = (h >> 3) & 1;
                if (h >= NHEAD - cfg::PREPART) mbar_wait(bar_set, 0);
                uint32_t qf[24];
#pragma unroll
                for (int i = 0; i < 6; i++) { const uint4 v = lds128(sbase + SM_Q + h * ROW_BYTES + t * 96 + i * 16); qf[4 * i] = v.x; qf[4 * i + 1] = v.y; qf[4 * i + 2] = v.z; qf[4 * i + 3] = v.w; }
                uint32_t ad[12];
#pragma unroll
                for (int i = 0; i < 12; i++) ad[i] = (ta[i >> 2] + slot * TILE_BYTES) ^ ((i & 3) << 5);
                float sc[4][4];
#pragma unroll
                for (int j = 0; j < 4; j++) sc[j][0] = sc[j][1] = sc[j][2] = sc[j][3] = 0.f;
                mbar_wait(bar_full + 8 * slot, par);
#pragma unroll
                for (int i = 0; i < 12; i++) {
                    const uint32_t a[4] = {qf[2 * i], qf[2 * i], qf[2 * i + 1], qf[2 * i + 1]};
                    uint32_t k0[4], k1[4];
                    ldsm_x4(k0, ad[i]); ldsm_x4(k1, ad[i] + TILE_BYTES / 2);
                    mma_bf16(sc[0], a, k0[0], k0[1]); mma_bf16(sc[1], a, k0[2], k0[3]);
                    mma_bf16(sc[2], a, k1[0], k1[1]); mma_bf16(sc[3], a, k1[2], k1[3]);
                }
                const float scale = 0.07216878364870322f;
                float m = -INFINITY;
#pragma unroll
                for (int j = 0; j < 4; j++) { sc[j][0] = bfr(bfr(sc[j][0]) * scale); sc[j][1] = bfr(bfr(sc[j][1]) * scale); m = fmaxf(m, fmaxf(sc[j][0], sc[j][1])); }
                if (lane == 0) mbar_arrive(after(p.zero, bar_empty + 8 * slot, m));
                m = fmaxf(m, __shfl_xor_sync(0xffffffffu, m, 1));
                m = fmaxf(m, __shfl_xor_sync(0xffffffffu, m, 2));
                float l = 0.f;
                uint32_t pf[4];
#pragma unroll
                for (int j = 0; j < 4; j++) {
                    const float p0 = ex2((sc[j][0] - m) * L2E), p1 = ex2((sc[j][1] - m) * L2E);
                    l += p0 + p1;
                    const uint32_t hi = pack_bf(p1, p0);
                    pf[j] = (g & 1) ? pack_bf(p1 - bf_hi(hi), p0 - bf_lo(hi)) : hi;
                }
                l += __shfl_xor_sync(0xffffffffu, l, 1);
                l += __shfl_xor_sync(0xffffffffu, l, 2);
                const uint32_t meta = (__float_as_uint(m) & 0xffff0000u) | ((__float_as_uint(l) - 0x3f800000u + 0x800u) >> 10 & 0xfffcu) | (tag & 3);
                uint32_t pq[4][4];
#pragma unroll
                for (int q = 0; q < 4; q++)
#pragma unroll
                    for (int j = 0; j < 4; j++) pq[q][j] = (g >> 1) == q ? pf[j] : 0;
                float o[6][4];
#pragma unroll
                for (int k = 0; k < 6; k++) o[k][0] = o[k][1] = o[k][2] = o[k][3] = 0.f;
                uint4* dst = p.sc->part + ((h * 4 + t) * NCTA + b) * 8 + g;
                uint4* dst2 = reinterpret_cast<uint4*>(p.xa + xa_off(L_PART + ((t * NCTA + b) * 8 + g) * 16, 1));
                if (h == NHEAD - 1) dst = reinterpret_cast<uint4*>(p.xa + xa_off(L_PART + ((t * NCTA + b) * 8 + g) * 16, 0));
                mbar_wait(after(p.zero, bar_full + 8 * slot + 8, meta, dst, dst2, pq[0][0], pq[1][1], pq[2][2], pq[3][3]), par);
#pragma unroll
                for (int i = 0; i < 12; i++) {
                    uint32_t v0[4], v1[4];
                    ldsm_x4_t(v0, ad[i] + TILE_BYTES); ldsm_x4_t(v1, ad[i] + TILE_BYTES + TILE_BYTES / 2);
                    mma_bf16(o[i % 3], v0, pq[i / 3][0], pq[i / 3][1]);
                    mma_bf16(o[3 + i % 3], v1, pq[i / 3][2], pq[i / 3][3]);
                }
                uint32_t w[3];
#pragma unroll
                for (int k = 0; k < 3; k++) w[k] = pack_bf((o[k][2] + o[k][3]) + (o[k + 3][2] + o[k + 3][3]), (o[k][0] + o[k][1]) + (o[k + 3][0] + o[k + 3][1]));
                pkt_st(dst, w[0], w[1], w[2], meta);
                if (h == NHEAD - 1) pkt_st(dst2, w[0], w[1], w[2], meta);
                if (lane == 0) {
                    mbar_arrive(after(p.zero, bar_empty + 8 * slot + 8, w[0], w[1], w[2]));
                    if (h == head) mbar_arrive(bar_part);
                }
            }
            if (tid == 96) LST(91);
        } else {
            const int u = tid - 128;
            uint32_t n = 0;
            if (warp == 4) {
                const uint4* src = reinterpret_cast<const uint4*>(p.sc->q1 + (head * 4 + sp) * 4 * 48) + min(lane, 23);
                uint4 v[4];
                sleep_until(now_q() + 4 * cfg::QDELAY);
#pragma unroll 1
                do {
                    if (n) __nanosleep(cfg::QSLEEP);
#pragma unroll
                    for (int i = 0; i < 4; i++) v[i] = ll_ld2(src + i * 24);
                    if (++n > SPIN_LIMIT) __trap();
                } while (__any_sync(0xffffffffu, ((v[0].y ^ tag) | (v[0].w ^ tag) | (v[1].y ^ tag) | (v[1].w ^ tag) | (v[2].y ^ tag) | (v[2].w ^ tag) | (v[3].y ^ tag) | (v[3].w ^ tag)) != 0));
#define F_(c) ((__uint_as_float(v[0].c) + __uint_as_float(v[1].c)) + (__uint_as_float(v[2].c) + __uint_as_float(v[3].c)))
                const uint32_t w0 = pack_bf(F_(z), F_(x));
#undef F_
                const uint32_t w1 = __shfl_down_sync(0xffffffffu, w0, 4), w2 = __shfl_down_sync(0xffffffffu, w0, 8);
                if (lane < 24 && lane % 12 < 4) pkt_st(q2dst, w0, w1, w2, tag);
            }
            asm volatile("bar.sync 7, 128;" ::: "memory");
            uint4 v[8];
            {
#pragma unroll
                for (int i = 0; i < 8; i++) v[i] = make_uint4(0, 0, 0, ~tag);
                sleep_until(now_q() + 4 * cfg::QDELAY2);
                n = 0;
                bool ok;
#pragma unroll 1
                do {
                    if (n) __nanosleep(cfg::QSLEEP);
#pragma unroll
                    for (int i = 0; i < 8; i++) pkt_ldp(p.sc->q2 + u + i * 128, v[i], v[i].w != tag);
                    ok = true;
#pragma unroll
                    for (int i = 0; i < 8; i++) ok &= v[i].w == tag;
                    if (++n > SPIN_LIMIT) __trap();
                } while (!__all_sync(0xffffffffu, ok));
                const uint32_t qd = sbase + SM_Q + (u >> 5) * ROW_BYTES + t * 96 + g * 12;
#pragma unroll
                for (int i = 0; i < 8; i++) {
                    sts32(qd + i * 4 * ROW_BYTES, __uint_as_float(v[i].x)); sts32(qd + i * 4 * ROW_BYTES + 4, __uint_as_float(v[i].y)); sts32(qd + i * 4 * ROW_BYTES + 8, __uint_as_float(v[i].z));
                }
                __syncwarp();
                if (lane == 0) mbar_arrive(bar_q);
            }
            {
                const uint4* src = p.sc->part + b * NCTA * 8 + u;
                const uint32_t rdst = sbase + SM_RED + (warp - 4) * 256 + min(lane >> 3, 2) * 64 + (lane & 7) * 4;
                const uint32_t lo = o_off(b * 48 + (min(lane, 23) >> 3) * 16) + (lane & 3) * 8 + (lane & 4);
                unsigned char *od0 = p.xa + xa_off(lo, 0), *od1 = p.xa + xa_off(lo, 1);
#pragma unroll
                for (int i = 0; i < 8; i++) v[i].w = ~tag;
                mbar_wait(bar_set, 0);
                const uint4* sr[4];
#pragma unroll
                for (int i = 0; i < 4; i++) sr[i] = head == NHEAD - 1 ? reinterpret_cast<const uint4*>(p.xa + xa_off(L_PART + (sp * 4 + i) * 4096, s_pace[2])) + u : src + i * 256;
                mbar_wait(after(p.zero, bar_part, sr[0], sr[1], sr[2], sr[3], rdst, od0, od1), 0);
                {
                    const uint32_t at = now_q() + 4 * min(cfg::PDELAY, cfg::PDELAY_LAST + (NHEAD - 1 - head) * cfg::PDELAY_STEP);
                    sleep_until(at - 4 * 300);
                    wait_until(at);
                }
                n = 0;
                uint32_t bad;
#pragma unroll 1
                do {
                    if (n && head != NHEAD - 1) __nanosleep(cfg::QSLEEP);
#pragma unroll
                    for (int i = 0; i < 8; i++) pkt_ldp(sr[i >> 1] + (i & 1) * 128, v[i], ((v[i].w ^ tag) & 3) != 0);
                    bad = 0;
#pragma unroll
                    for (int i = 0; i < 8; i++) bad |= v[i].w ^ tag;
                    if (++n > SPIN_LIMIT) __trap();
                } while (__any_sync(0xffffffffu, (bad & 3) != 0));
                if (u == 0) LST(119);
                float m = -INFINITY;
#pragma unroll
                for (int i = 0; i < 8; i++) m = fmaxf(m, bf_hi(v[i].w));
                m = fmaxf(m, __shfl_xor_sync(0xffffffffu, m, 8));
                m = fmaxf(m, __shfl_xor_sync(0xffffffffu, m, 16));
                float a[7] = {0.f, 0.f, 0.f, 0.f, 0.f, 0.f, 0.f};
#pragma unroll
                for (int i = 0; i < 8; i++) {
                    const float f = ex2((bf_hi(v[i].w) - m) * L2E);
                    a[0] = fmaf(f, bf_lo(v[i].x), a[0]); a[1] = fmaf(f, bf_hi(v[i].x), a[1]);
                    a[2] = fmaf(f, bf_lo(v[i].y), a[2]); a[3] = fmaf(f, bf_hi(v[i].y), a[3]);
                    a[4] = fmaf(f, bf_lo(v[i].z), a[4]); a[5] = fmaf(f, bf_hi(v[i].z), a[5]);
                    a[6] = fmaf(f, __uint_as_float(((v[i].w & 0xfffcu) << 10) + 0x3f800000u), a[6]);
                }
#pragma unroll
                for (int o = 8; o < 32; o <<= 1)
#pragma unroll
                    for (int i = 0; i < 7; i++) a[i] += __shfl_xor_sync(0xffffffffu, a[i], o);
                if (lane < 24) { sts32(rdst, lane < 8 ? a[0] : lane < 16 ? a[2] : a[4]); sts32(rdst + 32, lane < 8 ? a[1] : lane < 16 ? a[3] : a[5]); }
                if (lane == 24) sts64(rdst + 64, __float_as_uint(a[6]), __float_as_uint(m));
                asm volatile("bar.sync 7, 128;" ::: "memory");
                if (warp == 4) {
                    float2 st[4], r[4];
#pragma unroll
                    for (int i = 0; i < 4; i++) { st[i] = lds64f(sbase + SM_RED + i * 256 + 192); r[i] = lds64f(sbase + SM_RED + i * 256 + lane * 8); }
                    const float mm = fmaxf(fmaxf(st[0].y, st[1].y), fmaxf(st[2].y, st[3].y));
                    float den = 0.f, x0 = 0.f, x1 = 0.f;
#pragma unroll
                    for (int i = 0; i < 4; i++) { const float f = ex2((st[i].y - mm) * L2E); den = fmaf(f, st[i].x, den); x0 = fmaf(f, r[i].x, x0); x1 = fmaf(f, r[i].y, x1); }
                    const float inv = rcp_fast(den);
                    const float ow = __uint_as_float(pack_bf(x1 * inv, x0 * inv));
                    if (lane < 24) { in_st1(od0, ow); in_st1(od1, ow); }
                    if (lane == 0) LST(120);
                }
            }
        }
        mbar_wait(bar_pace, 0);
        const uint32_t msel = s_pace[2];
        cons_sync();
        if (is_wo) {
            uint32_t wa = sbase + (warp * 16 + arow) * 128 + ((ahalf ^ (lane & 7)) << 4);
            uint32_t pw = sbase + SM_RED + (warp * 64 + t * 16 + (lane >> 2)) * 4, pr = sbase + SM_RED + lane * 8;
            unsigned char* gdst = p.xa + xa_off(L_GATHER + (warp >> 1) % cfg::HCOPY * HCOPY_BYTES + (kg * D_MODEL + ng * 64 + lane * 2) * 2, warp & 1);
            const unsigned char* osrc = p.xa + xa_off(L_O + kg * 2048, msel) + warp * 32 + t * 8;
            uint2 ov[NWP];
#pragma unroll
            for (int j = 0; j < NWP; j++) ov[j] = make_uint2(SENT, SENT);
            auto gather = [&](int j0, int j1) {
                uint32_t n = 0;
#pragma unroll 1
                while (true) {
                    uint32_t mx = 0;
#pragma unroll
                    for (int j = j0; j < j1; j++) mx = max(mx, max(ov[j].x, ov[j].y));
                    if (!__any_sync(0xffffffffu, mx == SENT)) break;
#pragma unroll
                    for (int j = j0; j < j1; j++) in_ld2p(osrc + j * 256, ov[j], !in_ok(ov[j]));
                    if (++n > SPIN_LIMIT) __trap();
                }
            };
            float cw[4][4];
#pragma unroll
            for (int i = 0; i < 4; i++) cw[i][0] = cw[i][1] = cw[i][2] = cw[i][3] = 0.f;
            mbar_wait(after(p.zero, bar_tail + 8, osrc, wa, pw, pr, gdst), 0);
#pragma unroll
            for (int j = 0; j < NWP; j++) in_ld2p(osrc + j * 256, ov[j], true);
            gather(0, NWP - 1);
#pragma unroll
            for (int j = 0; j < NWP; j++) {
                if (j == NWP - 2) { gather(NWP - 1, NWP); if (tid == 224) LST(93); }
                mbar_wait(bar_tail + 8 * j, 0);
                if (j == NWP - 4) in_ld2p(osrc + (NWP - 1) * 256, ov[NWP - 1], !in_ok(ov[NWP - 1]));
                uint32_t a[4][4];
#pragma unroll
                for (int i = 0; i < 4; i++) ldsm_x4_t(a[i], (wa ^ (i << 5)) + j * WPIECE);
#pragma unroll
                for (int i = 0; i < 4; i++) mma_bf16(cw[i], a[i], ov[j].x, ov[j].y);
            }
#define SEL_(e) ((t & 2) ? ((t & 1) ? cw[3][e] : cw[2][e]) : ((t & 1) ? cw[1][e] : cw[0][e]))
            sts32(pw, SEL_(0)); sts32(pw + 32, SEL_(2));
#undef SEL_
            cons_sync();
            if (warp < 2 * cfg::HCOPY) {
                float2 r[8];
#pragma unroll
                for (int i = 0; i < 8; i++) r[i] = lds64f(pr + i * 256);
#define S_(c) (((r[0].c + r[1].c) + (r[2].c + r[3].c)) + ((r[4].c + r[5].c) + (r[6].c + r[7].c)))
                in_st1(gdst, __uint_as_float(pack_bf(S_(y), S_(x))));
#undef S_
            }
            if (tid == 0) LST(94);
        } else if (is_ffn) {
            uint32_t w13a = sbase + (warp * 16 + arow) * 64 + ((ahalf ^ (lane >> 1 & 3)) << 4);
            uint32_t red_dst = sbase + SM_RED + tid * 8;
            const uint32_t ha = sbase + SM_HN + warp * 32 + t * 8;
            uint32_t aw[2][NUP][2][4];
            auto load = [&](int m, int i) {
#pragma unroll
                for (int k = 0; k < 2; k++) ldsm_x4_t(aw[m][i][k], (w13a ^ (k << 5)) + (m * NUP + i) * (WPIECE / 2));
            };
#pragma unroll
            for (int j = 0; j < 3; j++) {
                mbar_wait(j ? bar_tail + 8 * j : after(p.zero, bar_tail, w13a, red_dst, ha), 0);
                load(2 * j / NUP, 2 * j % NUP); load((2 * j + 1) / NUP, (2 * j + 1) % NUP);
            }
            LSC(0);
            asm volatile("bar.sync 9, 416;" ::: "memory");
            uint32_t b0[NUP], b1[NUP];
#pragma unroll
            for (int i = 0; i < NUP; i++) {
                b0[i] = b1[i] = 0x3f803f80u;
                asm volatile("{\n.reg .pred q;\nsetp.eq.u32 q, %3, 0;\n@q ld.shared.v2.u32 {%0, %1}, [%2];\n}" : "+r"(b0[i]), "+r"(b1[i]) : "r"(ha + i * 256), "r"(lane & 4) : "memory");
            }
#pragma unroll
            for (int m = 0; m < 2; m++) {
                if (m) { mbar_wait(bar_tail + 8 * 3, 0); load(1, 1); load(1, 2); }
                float cf[2][2][4];
#pragma unroll
                for (int e = 0; e < 4; e++) cf[0][0][e] = cf[0][1][e] = cf[1][0][e] = cf[1][1][e] = 0.f;
#pragma unroll
                for (int i = 0; i < NUP; i++) {
                    if (m && i >= NUP - 2) { mbar_wait(bar_tail + 8 * (i + 1), 0); load(1, i); }
#pragma unroll
                    for (int k = 0; k < 2; k++) mma_bf16(cf[m ? 0 : i & 1][k], aw[m][i][k], b0[i], b1[i]);
                }
#define SEL_(c, e) ((t & 2) ? ((t & 1) ? cf[c][1][e + 2] : cf[c][1][e]) : ((t & 1) ? cf[c][0][e + 2] : cf[c][0][e]))
                if (m == 0) {
                    sts64(red_dst, __float_as_uint(SEL_(0, 0) + SEL_(1, 0)), __float_as_uint(SEL_(0, 1) + SEL_(1, 1)));
                    asm volatile("bar.arrive 8, 288;" ::: "memory");
                } else {
                    sts64(red_dst + 2048, __float_as_uint(SEL_(0, 0)), __float_as_uint(SEL_(0, 1)));
                }
#undef SEL_
            }
            LSC(7);
            asm volatile("bar.arrive 5, 288;" ::: "memory");
        }
        if (is_out) {
            uint32_t w2a = sbase + SM_W2 + (warp * 32 + arow) * 32 + ((ahalf ^ (lane >> 2 & 1)) << 4);
            uint32_t ydst = sbase + SM_HN + ((t & 1) * 8 + (lane >> 2)) * 48 + warp * 4;
            const unsigned char* asrc = p.xa + xa_off(L_ACT, msel) + oh * (NDP * 512) + warp * 64 + t * 16;
            const uint32_t at = tail_time(cfg::T_AAT);
            uint32_t a[NDP][2][4];
            auto load_w2 = [&](int i) {
                mbar_wait(i ? bar_tail + 8 * (NWP + i) : after(p.zero, bar_tail + 8 * NWP, w2a, ydst, asrc, at), 0);
                ldsm_x4_t(a[i][0], w2a + i * PIECE); ldsm_x4_t(a[i][1], w2a + i * PIECE + 512);
            };
            load_w2(0);
            uint4 u[NDP];
            wait_until(at);
            LSC(0);
#pragma unroll
            for (int i = 0; i < NDP; i++) u[i] = in_ld4(asrc + i * 512);
            load_w2(1);
            uint32_t n = 0;
#pragma unroll 1
            while (true) {
                uint32_t m[NDP];
#pragma unroll
                for (int i = 0; i < NDP; i++) m[i] = max(max(u[i].x, u[i].y), max(u[i].z, u[i].w));
                if (!__any_sync(0xffffffffu, max(max(m[0], m[1]), m[2]) == SENT)) break;
#pragma unroll
                for (int i = 0; i < NDP; i++) in_ld4p(asrc + i * 512, u[i], m[i] == SENT);
                if (++n > SPIN_LIMIT) __trap();
            }
            LSC(12);
            if (tid == 96) LST(118);
            float cy[2 * NDP][4];
#pragma unroll
            for (int i = 0; i < NDP; i++) {
#pragma unroll
                for (int e = 0; e < 4; e++) cy[2 * i][e] = cy[2 * i + 1][e] = 0.f;
                if (i == NDP - 1) load_w2(i);
                mma_bf16(cy[2 * i], a[i][0], u[i].x, u[i].y);
                mma_bf16(cy[2 * i + 1], a[i][1], u[i].z, u[i].w);
            }
#define Y_(e) (((cy[0][e] + cy[1][e]) + (cy[2][e] + cy[3][e])) + (cy[4][e] + cy[5][e]))
            const float y = (t & 1) ? Y_(2) : Y_(0);
#undef Y_
            if (t < 2) sts32(ydst, y);
            LSC(13);
            asm volatile("bar.arrive 5, 288;" ::: "memory");
        }
    }
}

typedef CUresult (*EncodeTiledFn)(CUtensorMap*, CUtensorMapDataType, cuuint32_t, void*, const cuuint64_t*, const cuuint64_t*,
                                  const cuuint32_t*, const cuuint32_t*, CUtensorMapInterleave, CUtensorMapSwizzle,
                                  CUtensorMapL2promotion, CUtensorMapFloatOOBfill);

void make_map(EncodeTiledFn fn, CUtensorMap* tm, const void* w, const int (&d)[5], const int (&st)[4], const int (&bx)[5],
              CUtensorMapSwizzle sw, int promo) {
    cuuint64_t dims[5], strides[4];
    cuuint32_t box[5], estr[5];
    for (int i = 0; i < 5; i++) { dims[i] = (cuuint64_t)d[i]; box[i] = (cuuint32_t)bx[i]; estr[i] = 1; }
    for (int i = 0; i < 4; i++) strides[i] = (cuuint64_t)st[i];
    fn(tm, CU_TENSOR_MAP_DATA_TYPE_BFLOAT16, 5, const_cast<void*>(w), dims, strides, box, estr, CU_TENSOR_MAP_INTERLEAVE_NONE, sw,
       (CUtensorMapL2promotion)promo, CU_TENSOR_MAP_FLOAT_OOB_FILL_NONE);
}

}

extern "C" void kernel_launch(void* const* d_in, const int* in_sizes, int n_in, void* d_out, int out_size) {
    (void)in_sizes; (void)n_in; (void)out_size;
    static EncodeTiledFn encode = nullptr;
    static Scratch* scratch = nullptr;
    static unsigned char* xarea = nullptr;
    static double tscale = 1.0;
    if (!encode) {
        void* sp = nullptr;
        cudaGetSymbolAddress(&sp, g_scratch);
        scratch = reinterpret_cast<Scratch*>(sp);
        cudaGetSymbolAddress(&sp, g_xarea);
        xarea = reinterpret_cast<unsigned char*>((reinterpret_cast<uintptr_t>(sp) + XA_ALIGN - 1) / XA_ALIGN * XA_ALIGN);
        void* fn = nullptr;
        cudaDriverEntryPointQueryResult st;
        cudaGetDriverEntryPoint("cuTensorMapEncodeTiled", &fn, cudaEnableDefault, &st);
        encode = reinterpret_cast<EncodeTiledFn>(fn);
        int dev = 0, khz = 0, bits = 0;
        cudaGetDevice(&dev);
        cudaDeviceGetAttribute(&khz, cudaDevAttrMemoryClockRate, dev);
        cudaDeviceGetAttribute(&bits, cudaDevAttrGlobalMemoryBusWidth, dev);
        if (khz > 0 && bits > 0) tscale = (2619000.0 * 5120.0) / ((double)khz * bits);
        cudaFuncSetAttribute(fused_decode_kernel, cudaFuncAttributeMaxDynamicSharedMemorySize, SM_TOTAL);
    }
    KParams p;
    p.x = (const __nv_bfloat16*)d_in[0];
    p.wq = (const __nv_bfloat16*)d_in[3];
    p.out = (__nv_bfloat16*)d_out;
    p.sc = scratch;
    p.xa = xarea;
    p.zero = 0;
    p.t_first = (uint32_t)(4 * cfg::T_FIRST * tscale);
    p.t_step = (uint32_t)(cfg::T_STEP * tscale);
    p.t_smax = (uint32_t)(cfg::T_SMAX * tscale);
    p.t_lat = (uint32_t)(4 * (450 + (cfg::T_LAT - 450) * tscale));
    TMaps tm;
    constexpr int R1 = FF * 2, R2 = D_MODEL * 2;
    make_map(encode, &tm.k, d_in[1], {64, NHEAD * SK * 3, 1, 1, 1}, {128, 128, 128, 128}, {64, 96, 1, 1, 1}, CU_TENSOR_MAP_SWIZZLE_128B, cfg::PROMO_KV);
    make_map(encode, &tm.v, d_in[2], {64, NHEAD * SK * 3, 1, 1, 1}, {128, 128, 128, 128}, {64, 96, 1, 1, 1}, CU_TENSOR_MAP_SWIZZLE_128B, cfg::PROMO_KV);
    make_map(encode, &tm.wo, d_in[4], {D_MODEL, NHEAD * DH, 1, 1, 1}, {R2, R2, R2, R2}, {64, 128, 1, 1, 1}, CU_TENSOR_MAP_SWIZZLE_128B, cfg::PROMO_WO);
    make_map(encode, &tm.w1, d_in[6], {FF, 2, 4, 2, 40}, {R1, 4 * R1, 2 * R1, 16 * R1}, {32, 2, 4, 2, 8}, CU_TENSOR_MAP_SWIZZLE_64B, cfg::PROMO_W13);
    make_map(encode, &tm.w3, d_in[7], {FF, 2, 4, 2, 40}, {R1, 4 * R1, 2 * R1, 16 * R1}, {32, 2, 4, 2, 8}, CU_TENSOR_MAP_SWIZZLE_64B, cfg::PROMO_W13);
    make_map(encode, &tm.w2, d_in[8], {D_MODEL, FF, 1, 1, 1}, {R2, R2, R2, R2}, {16, 256, 1, 1, 1}, CU_TENSOR_MAP_SWIZZLE_32B, cfg::PROMO_W2);
    fused_decode_kernel<<<NCTA, NTHREADS, SM_TOTAL, cudaStreamPerThread>>>(p, tm);
}
```

```cpp
#include <cuda_runtime.h>
#include <cuda_bf16.h>
#include <cuda.h>
#include <stdint.h>
#include <math.h>

namespace {

constexpr int D_MODEL = 640;
constexpr int NHEAD = 32;
constexpr int DH = 192;
constexpr int SK = 32768;
constexpr int WIN = 4096;
constexpr int FF = 1536;

constexpr int NCTA = 128;
constexpr int NCONS = 256;
constexpr int NTHREADS = NCONS + 256;
constexpr int ROW_BYTES = DH * 2;
constexpr int TILE_BYTES = 32 * ROW_BYTES;
constexpr int NSLOT = 16;
constexpr int NQT = 5;
constexpr int QSLOT = NSLOT - NQT;
constexpr int NWO = 60;
constexpr int NG = 6;
constexpr int NFFN = 48;
constexpr int NWP = 8;
constexpr int NUP = 5;
constexpr int WPIECE = 16384;
constexpr int NDP = 3;
constexpr int PIECE = 8192;
constexpr int NTAIL = NWP + NDP;
constexpr int N_TAIL0 = 2 * NHEAD;

#define CFG(name, value) constexpr int name = value
#define CFG_OVERRIDE
namespace cfg_default {
CFG(T_FIRST, 1850);
CFG(T_STEP, 1906);
CFG(T_SMAX, 1940);
CFG(CAP, 4);
CFG(MN, 12);
CFG(MA, 4);
CFG(MB, 40);
CFG(PAUSE, 1300);
CFG(ADAPT, 60);
CFG(T_LAT, 1230);
CFG(T_WO, 296);
CFG(T_GAP, 95);
CFG(T_UP, 240);
CFG(T_UP2, 120);
CFG(T_W2AT, 1330);
CFG(T_W2, 200);
CFG(T_HAT, 1110);
CFG(T_RESAT, 1750);
CFG(T_AAT, 2430);
CFG(KEEP_AT, 65);
CFG(KEEP, 150);
CFG(HCOPY, 1);
CFG(QDELAY, 1200);
CFG(QDELAY2, 900);
CFG(QSLEEP, 400);
CFG(PDELAY, 2500);
CFG(PDELAY_LAST, 250);
CFG(PDELAY_STEP, 650);
CFG(PREPART, 3);
CFG(RBDELAY, 5000);
CFG(NPROBE, 10);
CFG(VOTES, 3);
CFG(PROMO_KV, 2);
CFG(PROMO_WO, 2);
CFG(PROMO_W13, 2);
CFG(PROMO_W2, 2);
CFG(BOUNDED_MBAR, 0);
}
namespace cfg { using namespace cfg_default; CFG_OVERRIDE }

constexpr uint32_t SBASE = 1024;
constexpr int SM_RING = 0;
constexpr int SM_W2 = NWP * WPIECE;
constexpr int SM_Q = SM_RING + NSLOT * TILE_BYTES;
constexpr int SM_RED = SM_Q + NHEAD * ROW_BYTES;
constexpr int SM_HN = SM_RED + 4096;
constexpr int SM_STAT = SM_HN + D_MODEL * 2;
constexpr int SM_MISC = SM_STAT + 256;
constexpr int SM_BAR = SM_MISC + 128;
constexpr int SM_TOTAL = SM_BAR + 512;
static_assert(SM_TOTAL <= 232448, "shared memory");

struct __align__(128) Scratch {
    uint4 part[NHEAD * 4 * NCTA * 8];
    uint64_t q1[NHEAD * 4 * DH];
    uint4 q2[NHEAD * 32];
    uint32_t epoch;
    uint32_t pad;
    unsigned long long pace[2];
};
__device__ Scratch g_scratch;
constexpr int XA_ALIGN = 1 << 20;
constexpr uint32_t SENT = 0xffffffffu;
constexpr int L_GATHER = 0;
constexpr int HCOPY_BYTES = NG * D_MODEL * 2;
constexpr int L_O = 9 * 4096;
constexpr int L_ACT = 30 * 4096;
constexpr int L_PROBE = 32 * 4096;
constexpr int L_PART = 64 * 4096;
static_assert(2 * (L_PART + 65536) <= XA_ALIGN, "");
__device__ unsigned char g_xarea[2 * XA_ALIGN];
__device__ __forceinline__ uint32_t xa_off(uint32_t l, uint32_t side) {
    const uint32_t k = l >> 12;
    return (2 * k + ((side ^ k ^ (k >> 3) ^ (k >> 4) ^ (k >> 6)) & 1)) * 4096 + (l & 4095);
}

__device__ __forceinline__ uint32_t o_off(uint32_t r) { return L_O + (r >> 7) % NG * 2048 + (r >> 7) / NG * 256 + (r & 127) * 2; }

#define LST(i) do { } while (0)
#define LSC(i) do { } while (0)
#define LSCD(i, v) do { } while (0)
constexpr uint32_t SPIN_LIMIT = cfg::BOUNDED_MBAR ? 1u << 14 : 1u << 22;

__device__ __forceinline__ uint32_t now_q() { uint32_t t; asm volatile("mov.u32 %0, %globaltimer_lo;" : "=r"(t)); return t * 4; }
__device__ __forceinline__ void wait_until(uint32_t due) {
#pragma unroll 1
    for (int n = 0; n < 4096 && (int)(now_q() - due) < 0; n++) { }
}
__device__ __forceinline__ void sleep_until(uint32_t due) {
#pragma unroll 1
    for (int n = 0; n < 4096 && (int)(now_q() - due) < 0; n++) __nanosleep(200);
}
__device__ __forceinline__ uint32_t smem_u32(const void* p) { return (uint32_t)__cvta_generic_to_shared(p); }
__device__ __forceinline__ void mbar_init(uint32_t bar, uint32_t cnt) {
    asm volatile("mbarrier.init.shared::cta.b64 [%0], %1;" ::"r"(bar), "r"(cnt) : "memory");
}
__device__ __forceinline__ void mbar_expect_tx(uint32_t bar, uint32_t bytes) {
    asm volatile("mbarrier.arrive.expect_tx.shared::cta.b64 _, [%0], %1;" ::"r"(bar), "r"(bytes) : "memory");
}
__device__ __forceinline__ void mbar_arrive(uint32_t bar) {
    asm volatile("mbarrier.arrive.shared::cta.b64 _, [%0];" ::"r"(bar) : "memory");
}
__device__ __forceinline__ bool mbar_test(uint32_t bar, uint32_t parity) {
    uint32_t ok;
    asm volatile("{\n.reg .pred p;\nmbarrier.test_wait.parity.shared::cta.b64 p, [%1], %2;\nselp.u32 %0, 1, 0, p;\n}"
                 : "=r"(ok) : "r"(bar), "r"(parity) : "memory");
    return ok;
}
__device__ __forceinline__ bool mbar_try(uint32_t bar, uint32_t parity) {
    uint32_t ok;
    asm volatile("{\n.reg .pred p;\nmbarrier.try_wait.parity.shared::cta.b64 p, [%1], %2;\nselp.u32 %0, 1, 0, p;\n}"
                 : "=r"(ok) : "r"(bar), "r"(parity) : "memory");
    return ok;
}
__device__ __forceinline__ void mbar_wait(uint32_t bar, uint32_t parity) {
    if (cfg::BOUNDED_MBAR) {
        uint32_t n = 0;
        while (!mbar_try(bar, parity)) if (++n > SPIN_LIMIT) __trap();
    } else {
        asm volatile("{\n.reg .pred p;\nW_%=:\nmbarrier.try_wait.parity.shared::cta.b64 p, [%0], %1;\n@!p bra W_%=;\n}" ::"r"(bar), "r"(parity) : "memory");
    }
}
__device__ __forceinline__ void tma_tile(uint32_t dst, const CUtensorMap* tm, int c1, uint32_t bar, uint64_t pol) {
    asm volatile("cp.async.bulk.tensor.5d.shared::cluster.global.mbarrier::complete_tx::bytes.L2::cache_hint [%0], [%1, {%4, %3, %4, %4, %4}], [%2], %5;"
                 ::"r"(dst), "l"(reinterpret_cast<uint64_t>(tm)), "r"(bar), "r"(c1), "r"(0), "l"(pol) : "memory");
}
__device__ __forceinline__ void tma_5d(uint32_t dst, const CUtensorMap* tm, int c0, int c1, int c2, int c4, uint32_t bar) {
    asm volatile("cp.async.bulk.tensor.5d.shared::cluster.global.mbarrier::complete_tx::bytes [%0], [%1, {%3, %4, %5, %7, %6}], [%2];"
                 ::"r"(dst), "l"(reinterpret_cast<uint64_t>(tm)), "r"(bar), "r"(c0), "r"(c1), "r"(c2), "r"(c4), "r"(0) : "memory");
}
__device__ __forceinline__ uint32_t bits(uint32_t v) { return v; }
__device__ __forceinline__ uint32_t bits(float v) { return __float_as_uint(v); }
__device__ __forceinline__ uint32_t bits(const void* v) { return (uint32_t)(uintptr_t)v ^ (uint32_t)((uintptr_t)v >> 32); }
template <class... T> __device__ __forceinline__ uint32_t after(uint32_t zero, uint32_t bar, T... v) { return bar | ((bits(v) ^ ...) & zero); }
__device__ __forceinline__ void sts32(uint32_t a, float v) { asm volatile("st.shared.f32 [%0], %1;" ::"r"(a), "f"(v) : "memory"); }
__device__ __forceinline__ void sts64(uint32_t a, uint32_t x, uint32_t y) { asm volatile("st.shared.v2.u32 [%0], {%1, %2};" ::"r"(a), "r"(x), "r"(y) : "memory"); }
__device__ __forceinline__ void cons_sync() { asm volatile("bar.sync 1, 256;" ::: "memory"); }

__device__ __forceinline__ uint4 lds128(uint32_t a) {
    uint4 v;
    asm volatile("ld.shared.v4.u32 {%0,%1,%2,%3}, [%4];" : "=r"(v.x), "=r"(v.y), "=r"(v.z), "=r"(v.w) : "r"(a));
    return v;
}
__device__ __forceinline__ float4 lds128f(uint32_t a) {
    float4 v;
    asm volatile("ld.shared.v4.f32 {%0,%1,%2,%3}, [%4];" : "=f"(v.x), "=f"(v.y), "=f"(v.z), "=f"(v.w) : "r"(a) : "memory");
    return v;
}
__device__ __forceinline__ float2 lds64f(uint32_t a) {
    float2 v;
    asm volatile("ld.shared.v2.f32 {%0,%1}, [%2];" : "=f"(v.x), "=f"(v.y) : "r"(a) : "memory");
    return v;
}
__device__ __forceinline__ uint32_t lds32(uint32_t a) {
    uint32_t v;
    asm volatile("ld.shared.u32 %0, [%1];" : "=r"(v) : "r"(a));
    return v;
}
__device__ __forceinline__ void ldsm_x4(uint32_t* r, uint32_t a) {
    asm volatile("ldmatrix.sync.aligned.m8n8.x4.shared.b16 {%0,%1,%2,%3}, [%4];"
                 : "=r"(r[0]), "=r"(r[1]), "=r"(r[2]), "=r"(r[3]) : "r"(a));
}
__device__ __forceinline__ void ldsm_x4_t(uint32_t* r, uint32_t a) {
    asm volatile("ldmatrix.sync.aligned.m8n8.x4.trans.shared.b16 {%0,%1,%2,%3}, [%4];"
                 : "=r"(r[0]), "=r"(r[1]), "=r"(r[2]), "=r"(r[3]) : "r"(a));
}
__device__ __forceinline__ void mma_bf16(float* c, const uint32_t* a, uint32_t b0, uint32_t b1) {
    asm volatile("mma.sync.aligned.m16n8k16.row.col.f32.bf16.bf16.f32 {%0,%1,%2,%3}, {%4,%5,%6,%7}, {%8,%9}, {%0,%1,%2,%3};"
                 : "+f"(c[0]), "+f"(c[1]), "+f"(c[2]), "+f"(c[3]) : "r"(a[0]), "r"(a[1]), "r"(a[2]), "r"(a[3]), "r"(b0), "r"(b1));
}
__device__ __forceinline__ float bf_lo(uint32_t u) { return __uint_as_float(u << 16); }
__device__ __forceinline__ float bf_hi(uint32_t u) { return __uint_as_float(u & 0xffff0000u); }
__device__ __forceinline__ uint32_t pack_bf(float hi, float lo) { uint32_t r; asm("cvt.rn.bf16x2.f32 %0, %1, %2;" : "=r"(r) : "f"(hi), "f"(lo)); return r; }
__device__ __forceinline__ float bfr(float x) { return __uint_as_float(pack_bf(x, 0.f)); }

__device__ __forceinline__ uint64_t pk(float v, uint32_t tag) { return ((uint64_t)tag << 32) | (uint64_t)__float_as_uint(v); }
__device__ __forceinline__ void ll_st1(uint64_t* p, float a, uint32_t tag) {
    asm volatile("st.relaxed.gpu.global.b64 [%0], %1;" ::"l"(p), "l"(pk(a, tag)) : "memory");
}
__device__ __forceinline__ uint4 ll_ld2(const uint4* p) {
    uint4 v;
    asm volatile("{\n.reg .b64 a, b;\nld.relaxed.gpu.global.v2.b64 {a, b}, [%4];\nmov.b64 {%0, %1}, a;\nmov.b64 {%2, %3}, b;\n}"
                 : "=r"(v.x), "=r"(v.y), "=r"(v.z), "=r"(v.w) : "l"(p) : "memory");
    return v;
}
__device__ __forceinline__ uint32_t in_word(float v) {
    uint32_t r;
    asm("min.u32 %0, %1, 0xfffffffe;" : "=r"(r) : "r"(__float_as_uint(v)));
    return r;
}
__device__ __forceinline__ void in_st1(void* p, float v) {
    asm volatile("st.relaxed.gpu.global.u32 [%0], %1;" ::"l"(p), "r"(in_word(v)) : "memory");
}
__device__ __forceinline__ void in_st4(void* p, uint32_t a, uint32_t b, uint32_t c, uint32_t d) {
    asm volatile("st.relaxed.gpu.global.v4.u32 [%0], {%1, %2, %3, %4};" ::"l"(p), "r"(a), "r"(b), "r"(c), "r"(d) : "memory");
}
__device__ __forceinline__ uint32_t in_ld1(const void* p) {
    uint32_t v;
    asm volatile("ld.relaxed.gpu.global.u32 %0, [%1];" : "=r"(v) : "l"(p) : "memory");
    return v;
}
__device__ __forceinline__ uint4 in_ld4(const void* p) {
    uint4 v;
    asm volatile("ld.relaxed.gpu.global.v4.u32 {%0, %1, %2, %3}, [%4];" : "=r"(v.x), "=r"(v.y), "=r"(v.z), "=r"(v.w) : "l"(p) : "memory");
    return v;
}
__device__ __forceinline__ void in_ld2p(const void* p, uint2& v, bool on) {
    asm volatile("{\n.reg .pred q;\nsetp.ne.u32 q, %3, 0;\n@q ld.relaxed.gpu.global.v2.u32 {%0, %1}, [%2];\n}"
                 : "+r"(v.x), "+r"(v.y) : "l"(p), "r"((uint32_t)on) : "memory");
}
__device__ __forceinline__ bool in_ok(const uint2& v) { return max(v.x, v.y) != SENT; }
__device__ __forceinline__ void in_ld4p(const void* p, uint4& v, bool on) {
    asm volatile("{\n.reg .pred q;\nsetp.ne.u32 q, %5, 0;\n@q ld.relaxed.gpu.global.v4.u32 {%0, %1, %2, %3}, [%4];\n}"
                 : "+r"(v.x), "+r"(v.y), "+r"(v.z), "+r"(v.w) : "l"(p), "r"((uint32_t)on) : "memory");
}
__device__ __forceinline__ void pkt_st(uint4* p, uint32_t x, uint32_t y, uint32_t z, uint32_t w) {
    asm volatile("{\n.reg .b128 t;\n.reg .b64 a, b;\nmov.b64 a, {%1, %2};\nmov.b64 b, {%3, %4};\nmov.b128 t, {a, b};\nst.relaxed.gpu.global.b128 [%0], t;\n}"
                 ::"l"(p), "r"(x), "r"(y), "r"(z), "r"(w) : "memory");
}
__device__ __forceinline__ void pkt_ldp(const uint4* p, uint4& v, bool on) {
    asm volatile("{\n.reg .pred q;\n.reg .b128 t;\n.reg .b64 a, b;\nsetp.ne.u32 q, %5, 0;\nmov.b64 a, {%0, %1};\nmov.b64 b, {%2, %3};\nmov.b128 t, {a, b};\n"
                 "@q ld.relaxed.gpu.global.b128 t, [%4];\nmov.b128 {a, b}, t;\nmov.b64 {%0, %1}, a;\nmov.b64 {%2, %3}, b;\n}"
                 : "+r"(v.x), "+r"(v.y), "+r"(v.z), "+r"(v.w) : "l"(p), "r"((uint32_t)on) : "memory");
}

__device__ __forceinline__ float sqrt_fast(float x) { float r; asm("sqrt.approx.ftz.f32 %0, %1;" : "=f"(r) : "f"(x)); return r; }
__device__ __forceinline__ float rcp_fast(float x) { float r; asm("rcp.approx.ftz.f32 %0, %1;" : "=f"(r) : "f"(x)); return r; }
__device__ __forceinline__ float ex2(float x) { float r; asm("ex2.approx.ftz.f32 %0, %1;" : "=f"(r) : "f"(x)); return r; }
constexpr float L2E = 1.4426950408889634f;
__device__ __forceinline__ void ln_sums(const uint2* v, float& t1, float& t2) {
    float s1[5], s2[5];
#pragma unroll
    for (int i = 0; i < 5; i++) {
        const float a0 = bf_lo(v[i].x), a1 = bf_hi(v[i].x), a2 = bf_lo(v[i].y), a3 = bf_hi(v[i].y);
        s1[i] = (a0 + a1) + (a2 + a3);
        s2[i] = fmaf(a0, a0, a1 * a1) + fmaf(a2, a2, a3 * a3);
    }
    t1 = ((s1[0] + s1[1]) + (s1[2] + s1[3])) + s1[4]; t2 = ((s2[0] + s2[1]) + (s2[2] + s2[3])) + s2[4];
#pragma unroll
    for (int o = 16; o > 0; o >>= 1) { t1 += __shfl_xor_sync(0xffffffffu, t1, o); t2 += __shfl_xor_sync(0xffffffffu, t2, o); }
}
__device__ __forceinline__ void ln_finish(float t1, float t2, float& mean_b, float& inv_den) {
    const float mean = t1 * (1.0f / D_MODEL);
    const float var = fmaxf(fmaf(-mean, mean, t2 * (1.0f / D_MODEL)), 0.f);
    mean_b = bfr(mean);
    inv_den = rcp_fast(bfr(sqrt_fast(bfr(bfr(var) + 1e-5f))));
}

struct KParams {
    const __nv_bfloat16* wq;
    uint32_t t_first;
    uint32_t t_step;
    const __nv_bfloat16* x;
    Scratch* sc;
    unsigned char* xa;
    __nv_bfloat16* out;
    uint32_t t_smax;
    uint32_t t_lat;
    uint32_t zero;
};
struct TMaps { CUtensorMap k, v, wo, w1, w3, w2; };

__global__ void __launch_bounds__(NTHREADS, 1)
fused_decode_kernel(const KParams p, const __grid_constant__ TMaps tm) {
    extern __shared__ __align__(1024) unsigned char smem[];
    const uint32_t sbase = smem_u32(smem);
    const int tid = threadIdx.x;
    const int b = blockIdx.x;
    const int head = b >> 2, sp = b & 3;
    {
        if (tid < 192) {
            const uint32_t rg = tid * 2731 >> 16, ch = tid - rg * 24;
            const char* src = reinterpret_cast<const char*>(p.wq) + (uint32_t)(sp * 8 * (NHEAD * DH * 2) + head * ROW_BYTES + rg * (NHEAD * DH * 2) + ch * 16);
            uint32_t dst = SBASE + SM_RING + QSLOT * TILE_BYTES + ((tid ^ (tid >> 3 & 7)) << 4);
#pragma unroll 4
            for (int i = 0; i < 20; i++) {
                asm volatile("cp.async.cg.shared.global [%0], [%1], 16;" ::"r"(dst), "l"(src) : "memory");
                dst += 8 * ROW_BYTES;
                src += (size_t)32 * (NHEAD * DH * 2);
            }
        }
    }
    const int warp = __shfl_sync(0xffffffffu, tid >> 5, 0), lane = tid & 31;
    const int rr = !(b & 1) ? b >> 1 : (b & 15) < 12 ? (b >> 4) * 6 + (b >> 1 & 7) : NFFN + (b >> 4) * 2 + (b >> 1 & 1);
    const bool is_wo = !(b & 1) && rr < NWO, is_ffn = (b & 1) && rr < NFFN, is_out = !is_ffn;
    const int og = (rr >> 2) + (b & 1) * 4, oh = og >= 10, oq = (og - 10 * oh) * 4 + (rr & 3);
    const int kg = min(rr / 10, NG - 1), ng = rr % 10;
    const uint32_t bar_full = sbase + SM_BAR;
    const uint32_t bar_empty = sbase + SM_BAR + 128;
    const uint32_t bar_tail = sbase + SM_BAR + 256;
    const uint32_t bar_set = bar_tail + 8 * NTAIL;
    const uint32_t bar_pace = bar_set + 8;
    const uint32_t bar_q = bar_set + 16;
    const uint32_t bar_part = bar_set + 24;
    volatile uint32_t* s_pace = reinterpret_cast<volatile uint32_t*>(smem + SM_MISC + 64);
    auto tail_time = [&](int t) { return s_pace[0] + (s_pace[1] * (((N_TAIL0 - cfg::ADAPT) * 478 + NWP * cfg::T_WO + t) * 256 / 478) >> 8); };

    if (warp == 8) {
        const uint32_t c_start = now_q();
        if (lane >= 1 && lane <= 6) asm volatile("prefetch.tensormap [%0];" ::"l"(reinterpret_cast<uint64_t>(&tm.k + (lane - 1))) : "memory");
        uint64_t pol_stream;
        asm volatile("createpolicy.fractional.L2::evict_first.b64 %0, 1.0;" : "=l"(pol_stream));
        if (lane == 0) {
#pragma unroll 1
            for (int i = 0; i < NSLOT; i++) { mbar_init(bar_full + 8 * i, 1); mbar_init(bar_empty + 8 * i, 1); }
#pragma unroll 1
            for (int i = 0; i < NTAIL + 4; i++) mbar_init(bar_tail + 8 * i, i == NTAIL + 2 ? 4 : 1);
            asm volatile("fence.mbarrier_init.release.cluster;" ::: "memory");
        }
        __syncwarp();
        asm volatile("bar.arrive 2, 288;" ::: "memory");
        asm volatile("bar.arrive 3, 64;" ::: "memory");
        asm volatile("bar.arrive 4, 64;" ::: "memory");
        if (is_ffn) asm volatile("bar.arrive 10, 192;" ::: "memory");
        if (lane == 0) {
            uint32_t due = c_start + p.t_first, step = p.t_step;
#pragma unroll 1
            for (int n = 0; n < N_TAIL0; n++) {
                const int slot = n & (NSLOT - 1);
                const int use = (n >> 4) + (slot >= QSLOT);
                if (n >= cfg::CAP) mbar_wait(bar_full + 8 * ((n - cfg::CAP) & (NSLOT - 1)), ((n - cfg::CAP) >> 4) & 1);
                if (use >= 1) mbar_wait(bar_empty + 8 * slot, (use - 1) & 1);
                if (n == cfg::ADAPT) { mbar_wait(bar_pace, 0); due = s_pace[0]; step = s_pace[1]; }
                const uint32_t full = bar_full + 8 * slot;
                mbar_expect_tx(full, TILE_BYTES);
                wait_until(due);
                LST(128 + n);
                tma_tile(sbase + SM_RING + slot * TILE_BYTES, &tm.k + (n & 1), ((n >> 1) * SK + (SK - WIN) + b * 32) * 3, full, pol_stream);
                due += step;
            }
            int rel = 0;
            auto released = [&](int end) {
#pragma unroll 1
                for (; rel * TILE_BYTES < end; rel++) mbar_wait(bar_empty + 8 * rel, rel < QSLOT);
            };
            const uint32_t t_wo = step * (cfg::T_WO * 4096 / 478) >> 12;
            if (is_wo) {
#pragma unroll 1
                for (int j = 0; j < NWP; j++) {
                    released((j + 1) * WPIECE);
                    mbar_expect_tx(bar_tail + 8 * j, WPIECE);
                    wait_until(due);
                    LST(128 + N_TAIL0 + j);
                    tma_5d(sbase + j * WPIECE, &tm.wo, ng * 64, j * (NG * 128) + kg * 128, 0, 0, bar_tail + 8 * j);
                    due += t_wo;
                }
            } else {
                due += NWP * t_wo;
            }
            due += 4 * cfg::T_GAP;
            if (is_out) {
                due += step * (cfg::T_W2AT * 4096 / 478) >> 12;
                released(SM_W2 + NDP * PIECE);
#pragma unroll
                for (int j = 0; j < NDP; j++) mbar_expect_tx(bar_tail + 8 * (NWP + j), PIECE);
                sleep_until(due - 4 * 400);
#pragma unroll
                for (int j = 0; j < NDP; j++) {
                    wait_until(due);
                    tma_5d(sbase + SM_W2 + j * PIECE, &tm.w2, oq * 16, (2 * j + oh) * 256, 0, 0, bar_tail + 8 * (NWP + j));
                    LST(128 + N_TAIL0 + NWP + j);
                    due += step * (cfg::T_W2 * 4096 / 478) >> 12;
                }
            } else if (is_ffn) {
                released(NUP * WPIECE);
#pragma unroll
                for (int j = 0; j <= NUP; j++) mbar_expect_tx(bar_tail + 8 * j, j < NUP - 1 ? WPIECE : WPIECE / 2);
                sleep_until(due - 4 * 400);
#pragma unroll
                for (int j = 0; j <= NUP; j++) {
                    const uint32_t full = bar_tail + 8 * j;
                    wait_until(due);
#pragma unroll
                    for (int e = min(2 * j, j + NUP - 1); e < min(2 * j + 2, j + NUP); e++)
                        tma_5d(sbase + e * (WPIECE / 2), e < NUP ? &tm.w1 : &tm.w3, rr * 32, 0, 0, e % NUP * 8, full);
                    LST(128 + N_TAIL0 + j);
                    due += step * ((j < NUP - 1 ? cfg::T_UP : cfg::T_UP2) * 4096 / 478) >> 12;
                }
            }
        }
    } else if (warp == 10) {
        if (sbase != SBASE) __trap();
        asm volatile("bar.sync 4, 64;" ::: "memory");
        if (lane == 0) {
            uint32_t epoch0;
            asm volatile("ld.relaxed.gpu.global.u32 %0, [%1];" : "=r"(epoch0) : "l"(&p.sc->epoch) : "memory");
            constexpr int MN = cfg::MN;
            const uint32_t t0 = now_q();
            uint32_t sa = 0, sb = 0;
#pragma unroll 1
            for (int n = 0; n < cfg::MB + MN; n++) {
#pragma unroll 1
                for (int k = 0; k < 256 && !mbar_try(bar_full + 8 * (n & (NSLOT - 1)), (n >> 4) & 1); k++) { }
                const uint32_t t = now_q() - t0;
                LST(n);
                if ((uint32_t)(n - cfg::MA) < MN) sa += t;
                if (n >= cfg::MB) sb += t;
            }
            const uint32_t mb = t0 + sb / MN;
            unsigned long long* pace = p.sc->pace + ((epoch0 + 1) & 1);
            mbar_wait(bar_set, 0);
            asm volatile("red.relaxed.gpu.global.add.u64 [%0], %1;" ::"l"(pace), "l"((unsigned long long)mb << 32 | min((sb - sa) / (4 * MN), 0xffffu) << 8 | 1) : "memory");
            if (b == 0) p.sc->pace[epoch0 & 1] = 0;
            unsigned long long v;
            uint32_t n = 0, cnt;
#pragma unroll 1
            do {
                __nanosleep(n ? 200 : 1000);
                asm volatile("ld.relaxed.gpu.global.u64 %0, [%1];" : "=l"(v) : "l"(pace) : "memory");
                cnt = (uint32_t)v & 0xff;
                if (++n > SPIN_LIMIT) __trap();
            } while (cnt < NCTA);
            uint32_t step = ((uint32_t)v >> 8) / (NCTA / 4 * (cfg::MB - cfg::MA));
            const uint32_t pause = step > 2 * p.t_smax - p.t_step ? cfg::PAUSE : 0;
            step = min(max(step - pause * 4 / (cfg::MB - cfg::MA), p.t_step), p.t_smax);
            s_pace[0] = mb + (int)((uint32_t)(v >> 32) - NCTA * mb) / NCTA + step * (2 * (cfg::ADAPT - cfg::MB) - (MN - 1)) / 2 - p.t_lat;
            s_pace[1] = step;
            mbar_arrive(bar_pace);
            LST(89);
        }
    } else if (warp == 9) {
        const uint32_t c_start = now_q();
        uint32_t epoch0;
        asm volatile("ld.relaxed.gpu.global.u32 %0, [%1];" : "=r"(epoch0) : "l"(&p.sc->epoch) : "memory");
        sleep_until(c_start + p.t_first);
        unsigned char* slot[2];
        slot[0] = p.xa + xa_off(o_off(b * 48 + (lane % 6) * 8), lane / 6 & 1);
        slot[1] = p.xa + (is_wo ? xa_off(L_GATHER + (lane >> 4) * HCOPY_BYTES + (kg * D_MODEL + ng * 64 + (lane & 7) * 8) * 2, lane >> 3 & 1)
                                : xa_off(L_ACT + rr * 64 + (lane & 3) * 16, lane >> 2 & 1));
        const int n2 = is_wo ? 16 * cfg::HCOPY : is_ffn ? 8 : 0;
#pragma unroll
        for (int i = 0; i < 2; i++) if (lane < (i ? n2 : 12)) in_st4(slot[i], SENT, SENT, SENT, SENT);
#pragma unroll
        for (int i = 2; i <= cfg::PREPART; i++) pkt_st(p.sc->part + (((NHEAD - i) * 4 + (lane & 3)) * NCTA + b) * 8 + (lane >> 2), 0, 0, 0, epoch0 & 3);
#pragma unroll
        for (int i = 0; i < 2; i++) pkt_st(reinterpret_cast<uint4*>(p.xa + xa_off(L_PART + (((lane & 3) * NCTA + b) * 8 + (lane >> 2)) * 16, i)), 0, 0, 0, epoch0 & 3);
        unsigned char* probe = p.xa + xa_off(L_PROBE + b * 1024 + (lane >> 1 & 7) * 128 + (lane & 1) * 16, lane >> 4);
        in_st4(probe, SENT, SENT, SENT, SENT);
        const bool clr = is_out && !oh && lane < 2;
        if (clr) in_st4(p.out + oq * 16 + lane * 8, 0, 0, 0, 0);
        sleep_until(now_q() + 4 * cfg::RBDELAY + b * 60);
        uint32_t acc = SENT;
#pragma unroll
        for (int i = 0; i < 2; i++) if (lane < (i ? n2 : 12)) acc &= in_ld1(slot[i]);
        if (clr) acc &= ~in_ld1(p.out + oq * 16 + lane * 8);
        if (__any_sync(0xffffffffu, acc != SENT)) __trap();
        int vote = 0;
        uint32_t lat[2] = {0, 0};
#pragma unroll 1
        for (int r = 0; r <= cfg::NPROBE && abs(vote) < cfg::VOTES; r++) {
            __nanosleep(300);
            uint32_t d[2];
#pragma unroll
            for (int i = 0; i < 2; i++) {
                const uint32_t c0 = (uint32_t)clock();
                if (__any_sync(0xffffffffu, in_ld1(p.xa + xa_off(L_PROBE + b * 1024 + (lane & 7) * 128, i)) != SENT)) __trap();
                d[i] = (uint32_t)clock() - c0;
                if (r) lat[i] += min(d[i], 1500u);
            }
            if (r) vote = __shfl_sync(0xffffffffu, vote + (d[1] < d[0]) - (d[0] < d[1]), 0);
        }
        const uint32_t sel = vote ? vote > 0 : lat[1] < lat[0];
        const uint32_t tag = epoch0 + 1;
        asm volatile("bar.sync 3, 64;" ::: "memory");
        if (lane == 0) { s_pace[2] = sel; mbar_arrive(bar_set); }
        {
            mbar_wait(bar_pace, 0);
            sleep_until(s_pace[0] + (cfg::KEEP_AT - cfg::ADAPT) * s_pace[1]);
            const uint32_t t_res = tail_time(cfg::T_RESAT);
            float c[4] = {0.f, 0.f, 0.f, 0.f};
            const uint32_t z[4] = {p.zero, p.zero, p.zero, p.zero};
            uint32_t n = 0;
#pragma unroll 1
            do {
                mma_bf16(c, z, p.zero, p.zero);
                __nanosleep(cfg::KEEP);
                n += 1 + __float_as_uint(c[0]);
            } while (!__all_sync(0xffffffffu, is_ffn ? mbar_test(bar_tail, 0) : (int)(now_q() - t_res) >= 0) && n < SPIN_LIMIT);
            if (is_ffn) {
                unsigned char* adst = p.xa + xa_off(L_ACT + rr * 64 + (lane >> 3) * 16 + (lane & 3) * 4, lane >> 2 & 1);
                uint32_t src = sbase + SM_RED + lane * 8;
                asm volatile("bar.sync %0, 192;" ::"r"(after(p.zero, 11, adst, src)) : "memory");
                float t1, t2, mean_b, inv_den;
                {
                    float q1[5], q2[5];
#pragma unroll
                    for (int i = 0; i < 5; i++) {
                        const float4 a = lds128f(sbase + SM_STAT + i * 48), c = lds128f(sbase + SM_STAT + i * 48 + 16), d = lds128f(sbase + SM_STAT + i * 48 + 32);
                        q2[i] = ((a.x + a.y) + (a.z + a.w)) + ((c.x + c.y) + (c.z + c.w));
                        q1[i] = (d.x + d.y) + (d.z + d.w);
                    }
                    t1 = ((q1[0] + q1[1]) + (q1[2] + q1[3])) + q1[4]; t2 = ((q2[0] + q2[1]) + (q2[2] + q2[3])) + q2[4];
                }
                ln_finish(t1, t2, mean_b, inv_den);
                float2 r[8];
#define S_(c) (((r[0].c + r[1].c) + (r[2].c + r[3].c)) + ((r[4].c + r[5].c) + (r[6].c + r[7].c)))
                asm volatile("bar.sync %0, 288;" ::"r"(after(p.zero, 8, mean_b, inv_den)) : "memory");
#pragma unroll
                for (int i = 0; i < 8; i++) r[i] = lds64f(src + i * 256);
                const float gate = bfr(fmaf(-mean_b, S_(y), S_(x)) * inv_den);
                const float silu = bfr(__fdividef(gate, 1.0f + ex2(-gate * L2E)));
                asm volatile("bar.sync %0, 288;" ::"r"(after(p.zero, 5, silu)) : "memory");
#pragma unroll
                for (int i = 0; i < 8; i++) r[i] = lds64f(src + 2048 + i * 256);
                const float act = silu * bfr(fmaf(-mean_b, S_(y), S_(x)) * inv_den);
#undef S_
                const float oth = __shfl_xor_sync(0xffffffffu, act, 4);
                in_st1(adst, __uint_as_float((lane & 4) ? pack_bf(act, oth) : pack_bf(oth, act)));
                if (lane == 0) LST(110);
            }
            if (is_out) {
                const int col = oq * 16 + (lane & 15);
                float res = 0.f;
                if (!oh) {
                    uint32_t u[NG], xv;
                    asm volatile("ld.global.nc.u16 %0, [%1];" : "=r"(xv) : "l"(p.x + col));
                    n = 0;
#pragma unroll 1
                    do {
#pragma unroll
                        for (int i = 0; i < NG; i++) u[i] = in_ld1(p.xa + xa_off(L_GATHER + rr % cfg::HCOPY * HCOPY_BYTES + (i * D_MODEL + (col & ~1)) * 2, sel));
                        if (++n > SPIN_LIMIT) __trap();
                    } while (__any_sync(0xffffffffu, max(max(max(u[0], u[1]), max(u[2], u[3])), max(u[4], u[5])) == SENT));
                    if (b == 0 && lane == 0) p.sc->epoch = tag;
#define F_(i) ((lane & 1) ? bf_hi(u[i]) : bf_lo(u[i]))
                    res = bfr(bf_lo(xv) + bfr(((F_(0) + F_(1)) + (F_(2) + F_(3))) + (F_(4) + F_(5))));
#undef F_
                }
                mma_bf16(c, z, p.zero, p.zero);
                mbar_wait(after(p.zero, bar_tail + 8 * NWP, c[0]), 0);
                mma_bf16(c, z, p.zero, p.zero);
                res += c[0];
                __nv_bfloat16* dst = p.out + (col & ~1);
                uint32_t src = sbase + SM_HN + (lane & 15) * 48;
                asm volatile("bar.sync %0, 288;" ::"r"(after(p.zero, 5, src, dst, res)) : "memory");
                const float4 ra = lds128f(src), rb = lds128f(src + 16);
                const float e = ((ra.x + ra.y) + (ra.z + ra.w)) + (((rb.x + rb.y) + (rb.z + rb.w)) + res);
                if (lane < 16) asm volatile("red.relaxed.gpu.global.add.noftz.bf16x2 [%0], %1;" ::"l"(dst), "r"((lane & 1) ? pack_bf(e, 0.f) : pack_bf(0.f, e)) : "memory");
                if (lane == 0) LST(96);
            }
        }
    } else if (warp > 10) {
        if (is_ffn) {
            const int col = (tid - 352) * 4;
            uint2 xres;
            asm volatile("bar.sync 10, 192;" ::: "memory");
            mbar_wait(bar_pace, 0);
            asm volatile("ld.global.nc.v2.u32 {%0, %1}, [%2];" : "=r"(xres.x), "=r"(xres.y) : "l"(p.x + col) : "memory");
            const unsigned char* gsrc[NG];
            uint2 u[NG];
#pragma unroll
            for (int i = 0; i < NG; i++) gsrc[i] = p.xa + xa_off(L_GATHER + rr % cfg::HCOPY * HCOPY_BYTES + (i * D_MODEL + col) * 2, s_pace[2]);
            const uint32_t hdst = sbase + SM_HN + col * 2;
            const bool diag = (lane & 3) == (lane >> 3);
            const uint32_t sdst = sbase + SM_STAT + (warp - 11) * 48 + (diag ? (lane >> 2) : 8 + (lane & 3)) * 4;
            const uint32_t at = after(p.zero, tail_time(cfg::T_HAT), gsrc[0], gsrc[1], gsrc[2], gsrc[3], gsrc[4], gsrc[5], hdst, sdst, xres.x);
            sleep_until(at - 4 * 300);
            wait_until(at);
#pragma unroll
            for (int i = 0; i < NG; i++) { u[i] = make_uint2(0, 0); in_ld2p(gsrc[i], u[i], true); }
            uint32_t n = 0;
#pragma unroll 1
            while (__any_sync(0xffffffffu, max(max(max(u[0].x, u[0].y), max(u[1].x, u[1].y)), max(max(max(u[2].x, u[2].y), max(u[3].x, u[3].y)),
                                                                                                max(max(u[4].x, u[4].y), max(u[5].x, u[5].y)))) == SENT)) {
#pragma unroll
                for (int i = 0; i < NG; i++) in_ld2p(gsrc[i], u[i], !in_ok(u[i]));
                if (++n > SPIN_LIMIT) __trap();
            }
#define F_(f, c) (f(xres.c) + bfr(((f(u[0].c) + f(u[1].c)) + (f(u[2].c) + f(u[3].c))) + (f(u[4].c) + f(u[5].c))))
            const uint32_t hp0 = pack_bf(F_(bf_hi, x), F_(bf_lo, x)), hp1 = pack_bf(F_(bf_hi, y), F_(bf_lo, y));
#undef F_
            sts64(hdst, hp0, hp1);
            asm volatile("bar.arrive 9, 416;" ::: "memory");
            float cs[4] = {0.f, 0.f, 0.f, 0.f};
            const uint32_t sa[4] = {hp0, 0x3f803f80u, hp1, 0x3f803f80u};
            mma_bf16(cs, sa, hp0, hp1);
            if (diag || (!(lane & 4) && (lane & 3) == (lane >> 3 ^ 1))) sts32(sdst, !diag ? cs[2] + cs[3] : (lane & 4) ? cs[1] : cs[0]);
            asm volatile("bar.arrive 11, 192;" ::: "memory");
            if (lane == 0) LST(100);
        }
    } else {
        const int t = lane & 3, g = lane >> 2;
        const int arow = (lane & 7) + ((lane >> 4) << 3), ahalf = (lane >> 3) & 1;
        uint32_t epoch0;
        const char* xb = reinterpret_cast<const char*>(p.x);
        asm volatile("ld.relaxed.gpu.global.u32 %0, [%1];" : "=r"(epoch0) : "l"(&p.sc->epoch) : "memory");
        uint64_t* q1dst = p.sc->q1 + ((head * 4 + (warp & 3)) * 4 + sp) * 48 + min(t, 2) * 16 + g;
        uint4* q2dst = p.sc->q2 + (head * 8 + sp * 2 + lane / 12) * 4 + t;
        if (warp == 7) {
            uint2 xu[5];
#pragma unroll
            for (int i = 0; i < 5; i++) asm volatile("ld.global.nc.v2.u32 {%0, %1}, [%2];" : "=r"(xu[i].x), "=r"(xu[i].y) : "l"(xb + i * 256 + lane * 8));
            float t1, t2, mean_b, inv_den;
            ln_sums(xu, t1, t2);
            ln_finish(t1, t2, mean_b, inv_den);
#define N_(v) (bfr((v) - mean_b) * inv_den)
#pragma unroll
            for (int i = 0; i < 5; i++)
                sts64(sbase + SM_HN + i * 256 + lane * 8, pack_bf(N_(bf_hi(xu[i].x)), N_(bf_lo(xu[i].x))), pack_bf(N_(bf_hi(xu[i].y)), N_(bf_lo(xu[i].y))));
#undef N_
        } else {
            if (warp < 4 && t < 3) { ll_st1(q1dst, 0.f, 0); ll_st1(q1dst + 8, 0.f, 0); }
            if (warp == 4 && lane < 24 && lane % 12 < 4) pkt_st(q2dst, 0, 0, 0, 0);
        }
        asm volatile("cp.async.wait_all;" ::: "memory");
        if (lane == 0) LST(80 + warp);
        asm volatile("bar.sync 2, 288;" ::: "memory");
        const uint32_t tag = epoch0 + 1;
        auto block = [&](int i) { const int unit = arow * 3 + (i >> 2); return sbase + SM_RING + unit * 128 + ((((i & 3) * 2 + ahalf) ^ (unit & 7)) << 4); };

        if (warp < 4) {
            {
                float c[3][4];
                uint32_t wa[3];
#pragma unroll
                for (int k = 0; k < 3; k++) { c[k][0] = c[k][1] = c[k][2] = c[k][3] = 0.f; wa[k] = block(warp * 3 + k) + QSLOT * TILE_BYTES; }
                const uint32_t xa = sbase + SM_HN + sp * 16 + t * 4;
#pragma unroll 2
                for (int ks = 0; ks < 2 * NQT; ks++) {
                    const uint32_t b0 = lds32(xa + ks * 128), b1 = lds32(xa + ks * 128 + 64);
#pragma unroll
                    for (int k = 0; k < 3; k++) { uint32_t a[4]; ldsm_x4_t(a, wa[k] + ks * (TILE_BYTES / 2)); mma_bf16(c[k], a, b0, b1); }
                }
                if (t < 3) {
                    ll_st1(q1dst, t == 0 ? c[0][0] : t == 1 ? c[1][0] : c[2][0], tag);
                    ll_st1(q1dst + 8, t == 0 ? c[0][2] : t == 1 ? c[1][2] : c[2][2], tag);
                }
                asm volatile("bar.sync 6, 128;" ::: "memory");
                if (tid < NQT) mbar_arrive(bar_empty + 8 * (QSLOT + tid));
                if (tid == 0) LST(90);
            }
            const uint32_t ta[3] = {block(0), block(4), block(8)};
            mbar_wait(bar_q, 0);
            if (tid == 0) LST(92);
#pragma unroll 1
            for (int h = warp; h < NHEAD; h += 4) {
                const int slot = (2 * h) & (NSLOT - 1);
                const uint32_t par = (h >> 3) & 1;
                if (h >= NHEAD - cfg::PREPART) mbar_wait(bar_set, 0);
                uint32_t qf[24];
#pragma unroll
                for (int i = 0; i < 6; i++) { const uint4 v = lds128(sbase + SM_Q + h * ROW_BYTES + t * 96 + i * 16); qf[4 * i] = v.x; qf[4 * i + 1] = v.y; qf[4 * i + 2] = v.z; qf[4 * i + 3] = v.w; }
                uint32_t ad[12];
#pragma unroll
                for (int i = 0; i < 12; i++) ad[i] = (ta[i >> 2] + slot * TILE_BYTES) ^ ((i & 3) << 5);
                float sc[4][4];
#pragma unroll
                for (int j = 0; j < 4; j++) sc[j][0] = sc[j][1] = sc[j][2] = sc[j][3] = 0.f;
                mbar_wait(bar_full + 8 * slot, par);
#pragma unroll
                for (int i = 0; i < 12; i++) {
                    const uint32_t a[4] = {qf[2 * i], qf[2 * i], qf[2 * i + 1], qf[2 * i + 1]};
                    uint32_t k0[4], k1[4];
                    ldsm_x4(k0, ad[i]); ldsm_x4(k1, ad[i] + TILE_BYTES / 2);
                    mma_bf16(sc[0], a, k0[0], k0[1]); mma_bf16(sc[1], a, k0[2], k0[3]);
                    mma_bf16(sc[2], a, k1[0], k1[1]); mma_bf16(sc[3], a, k1[2], k1[3]);
                }
                const float scale = 0.07216878364870322f;
                float m = -INFINITY;
#pragma unroll
                for (int j = 0; j < 4; j++) { sc[j][0] = bfr(bfr(sc[j][0]) * scale); sc[j][1] = bfr(bfr(sc[j][1]) * scale); m = fmaxf(m, fmaxf(sc[j][0], sc[j][1])); }
                if (lane == 0) mbar_arrive(after(p.zero, bar_empty + 8 * slot, m));
                m = fmaxf(m, __shfl_xor_sync(0xffffffffu, m, 1));
                m = fmaxf(m, __shfl_xor_sync(0xffffffffu, m, 2));
                float l = 0.f;
                uint32_t pf[4];
#pragma unroll
                for (int j = 0; j < 4; j++) {
                    const float p0 = ex2((sc[j][0] - m) * L2E), p1 = ex2((sc[j][1] - m) * L2E);
                    l += p0 + p1;
                    const uint32_t hi = pack_bf(p1, p0);
                    pf[j] = (g & 1) ? pack_bf(p1 - bf_hi(hi), p0 - bf_lo(hi)) : hi;
                }
                l += __shfl_xor_sync(0xffffffffu, l, 1);
                l += __shfl_xor_sync(0xffffffffu, l, 2);
                const uint32_t meta = (__float_as_uint(m) & 0xffff0000u) | ((__float_as_uint(l) - 0x3f800000u + 0x800u) >> 10 & 0xfffcu) | (tag & 3);
                uint32_t pq[4][4];
#pragma unroll
                for (int q = 0; q < 4; q++)
#pragma unroll
                    for (int j = 0; j < 4; j++) pq[q][j] = (g >> 1) == q ? pf[j] : 0;
                float o[6][4];
#pragma unroll
                for (int k = 0; k < 6; k++) o[k][0] = o[k][1] = o[k][2] = o[k][3] = 0.f;
                uint4* dst = p.sc->part + ((h * 4 + t) * NCTA + b) * 8 + g;
                uint4* dst2 = reinterpret_cast<uint4*>(p.xa + xa_off(L_PART + ((t * NCTA + b) * 8 + g) * 16, 1));
                if (h == NHEAD - 1) dst = reinterpret_cast<uint4*>(p.xa + xa_off(L_PART + ((t * NCTA + b) * 8 + g) * 16, 0));
                mbar_wait(after(p.zero, bar_full + 8 * slot + 8, meta, dst, dst2, pq[0][0], pq[1][1], pq[2][2], pq[3][3]), par);
#pragma unroll
                for (int i = 0; i < 12; i++) {
                    uint32_t v0[4], v1[4];
                    ldsm_x4_t(v0, ad[i] + TILE_BYTES); ldsm_x4_t(v1, ad[i] + TILE_BYTES + TILE_BYTES / 2);
                    mma_bf16(o[i % 3], v0, pq[i / 3][0], pq[i / 3][1]);
                    mma_bf16(o[3 + i % 3], v1, pq[i / 3][2], pq[i / 3][3]);
                }
                uint32_t w[3];
#pragma unroll
                for (int k = 0; k < 3; k++) w[k] = pack_bf((o[k][2] + o[k][3]) + (o[k + 3][2] + o[k + 3][3]), (o[k][0] + o[k][1]) + (o[k + 3][0] + o[k + 3][1]));
                pkt_st(dst, w[0], w[1], w[2], meta);
                if (h == NHEAD - 1) pkt_st(dst2, w[0], w[1], w[2], meta);
                if (lane == 0) {
                    mbar_arrive(after(p.zero, bar_empty + 8 * slot + 8, w[0], w[1], w[2]));
                    if (h == head) mbar_arrive(bar_part);
                }
            }
            if (tid == 96) LST(91);
        } else {
            const int u = tid - 128;
            uint32_t n = 0;
            if (warp == 4) {
                const uint4* src = reinterpret_cast<const uint4*>(p.sc->q1 + (head * 4 + sp) * 4 * 48) + min(lane, 23);
                uint4 v[4];
                sleep_until(now_q() + 4 * cfg::QDELAY);
#pragma unroll 1
                do {
                    if (n) __nanosleep(cfg::QSLEEP);
#pragma unroll
                    for (int i = 0; i < 4; i++) v[i] = ll_ld2(src + i * 24);
                    if (++n > SPIN_LIMIT) __trap();
                } while (__any_sync(0xffffffffu, ((v[0].y ^ tag) | (v[0].w ^ tag) | (v[1].y ^ tag) | (v[1].w ^ tag) | (v[2].y ^ tag) | (v[2].w ^ tag) | (v[3].y ^ tag) | (v[3].w ^ tag)) != 0));
#define F_(c) ((__uint_as_float(v[0].c) + __uint_as_float(v[1].c)) + (__uint_as_float(v[2].c) + __uint_as_float(v[3].c)))
                const uint32_t w0 = pack_bf(F_(z), F_(x));
#undef F_
                const uint32_t w1 = __shfl_down_sync(0xffffffffu, w0, 4), w2 = __shfl_down_sync(0xffffffffu, w0, 8);
                if (lane < 24 && lane % 12 < 4) pkt_st(q2dst, w0, w1, w2, tag);
            }
            asm volatile("bar.sync 7, 128;" ::: "memory");
            uint4 v[8];
            {
#pragma unroll
                for (int i = 0; i < 8; i++) v[i] = make_uint4(0, 0, 0, ~tag);
                sleep_until(now_q() + 4 * cfg::QDELAY2);
                n = 0;
                bool ok;
#pragma unroll 1
                do {
                    if (n) __nanosleep(cfg::QSLEEP);
#pragma unroll
                    for (int i = 0; i < 8; i++) pkt_ldp(p.sc->q2 + u + i * 128, v[i], v[i].w != tag);
                    ok = true;
#pragma unroll
                    for (int i = 0; i < 8; i++) ok &= v[i].w == tag;
                    if (++n > SPIN_LIMIT) __trap();
                } while (!__all_sync(0xffffffffu, ok));
                const uint32_t qd = sbase + SM_Q + (u >> 5) * ROW_BYTES + t * 96 + g * 12;
#pragma unroll
                for (int i = 0; i < 8; i++) {
                    sts32(qd + i * 4 * ROW_BYTES, __uint_as_float(v[i].x)); sts32(qd + i * 4 * ROW_BYTES + 4, __uint_as_float(v[i].y)); sts32(qd + i * 4 * ROW_BYTES + 8, __uint_as_float(v[i].z));
                }
                __syncwarp();
                if (lane == 0) mbar_arrive(bar_q);
            }
            {
                const uint4* src = p.sc->part + b * NCTA * 8 + u;
                const uint32_t rdst = sbase + SM_RED + (warp - 4) * 256 + min(lane >> 3, 2) * 64 + (lane & 7) * 4;
                const uint32_t lo = o_off(b * 48 + (min(lane, 23) >> 3) * 16) + (lane & 3) * 8 + (lane & 4);
                unsigned char *od0 = p.xa + xa_off(lo, 0), *od1 = p.xa + xa_off(lo, 1);
#pragma unroll
                for (int i = 0; i < 8; i++) v[i].w = ~tag;
                mbar_wait(bar_set, 0);
                const uint4* sr[4];
#pragma unroll
                for (int i = 0; i < 4; i++) sr[i] = head == NHEAD - 1 ? reinterpret_cast<const uint4*>(p.xa + xa_off(L_PART + (sp * 4 + i) * 4096, s_pace[2])) + u : src + i * 256;
                mbar_wait(after(p.zero, bar_part, sr[0], sr[1], sr[2], sr[3], rdst, od0, od1), 0);
                {
                    const uint32_t at = now_q() + 4 * min(cfg::PDELAY, cfg::PDELAY_LAST + (NHEAD - 1 - head) * cfg::PDELAY_STEP);
                    sleep_until(at - 4 * 300);
                    wait_until(at);
                }
                n = 0;
                uint32_t bad;
#pragma unroll 1
                do {
                    if (n && head != NHEAD - 1) __nanosleep(cfg::QSLEEP);
#pragma unroll
                    for (int i = 0; i < 8; i++) pkt_ldp(sr[i >> 1] + (i & 1) * 128, v[i], ((v[i].w ^ tag) & 3) != 0);
                    bad = 0;
#pragma unroll
                    for (int i = 0; i < 8; i++) bad |= v[i].w ^ tag;
                    if (++n > SPIN_LIMIT) __trap();
                } while (__any_sync(0xffffffffu, (bad & 3) != 0));
                if (u == 0) LST(119);
                float m = -INFINITY;
#pragma unroll
                for (int i = 0; i < 8; i++) m = fmaxf(m, bf_hi(v[i].w));
                m = fmaxf(m, __shfl_xor_sync(0xffffffffu, m, 8));
                m = fmaxf(m, __shfl_xor_sync(0xffffffffu, m, 16));
                float a[7] = {0.f, 0.f, 0.f, 0.f, 0.f, 0.f, 0.f};
#pragma unroll
                for (int i = 0; i < 8; i++) {
                    const float f = ex2((bf_hi(v[i].w) - m) * L2E);
                    a[0] = fmaf(f, bf_lo(v[i].x), a[0]); a[1] = fmaf(f, bf_hi(v[i].x), a[1]);
                    a[2] = fmaf(f, bf_lo(v[i].y), a[2]); a[3] = fmaf(f, bf_hi(v[i].y), a[3]);
                    a[4] = fmaf(f, bf_lo(v[i].z), a[4]); a[5] = fmaf(f, bf_hi(v[i].z), a[5]);
                    a[6] = fmaf(f, __uint_as_float(((v[i].w & 0xfffcu) << 10) + 0x3f800000u), a[6]);
                }
#pragma unroll
                for (int o = 8; o < 32; o <<= 1)
#pragma unroll
                    for (int i = 0; i < 7; i++) a[i] += __shfl_xor_sync(0xffffffffu, a[i], o);
                if (lane < 24) { sts32(rdst, lane < 8 ? a[0] : lane < 16 ? a[2] : a[4]); sts32(rdst + 32, lane < 8 ? a[1] : lane < 16 ? a[3] : a[5]); }
                if (lane == 24) sts64(rdst + 64, __float_as_uint(a[6]), __float_as_uint(m));
                asm volatile("bar.sync 7, 128;" ::: "memory");
                if (warp == 4) {
                    float2 st[4], r[4];
#pragma unroll
                    for (int i = 0; i < 4; i++) { st[i] = lds64f(sbase + SM_RED + i * 256 + 192); r[i] = lds64f(sbase + SM_RED + i * 256 + lane * 8); }
                    const float mm = fmaxf(fmaxf(st[0].y, st[1].y), fmaxf(st[2].y, st[3].y));
                    float den = 0.f, x0 = 0.f, x1 = 0.f;
#pragma unroll
                    for (int i = 0; i < 4; i++) { const float f = ex2((st[i].y - mm) * L2E); den = fmaf(f, st[i].x, den); x0 = fmaf(f, r[i].x, x0); x1 = fmaf(f, r[i].y, x1); }
                    const float inv = rcp_fast(den);
                    const float ow = __uint_as_float(pack_bf(x1 * inv, x0 * inv));
                    if (lane < 24) { in_st1(od0, ow); in_st1(od1, ow); }
                    if (lane == 0) LST(120);
                }
            }
        }
        mbar_wait(bar_pace, 0);
        const uint32_t msel = s_pace[2];
        cons_sync();
        if (is_wo) {
            uint32_t wa = sbase + (warp * 16 + arow) * 128 + ((ahalf ^ (lane & 7)) << 4);
            uint32_t pw = sbase + SM_RED + (warp * 64 + t * 16 + (lane >> 2)) * 4, pr = sbase + SM_RED + lane * 8;
            unsigned char* gdst = p.xa + xa_off(L_GATHER + (warp >> 1) % cfg::HCOPY * HCOPY_BYTES + (kg * D_MODEL + ng * 64 + lane * 2) * 2, warp & 1);
            const unsigned char* osrc = p.xa + xa_off(L_O + kg * 2048, msel) + warp * 32 + t * 8;
            uint2 ov[NWP];
#pragma unroll
            for (int j = 0; j < NWP; j++) ov[j] = make_uint2(SENT, SENT);
            auto gather = [&](int j0, int j1) {
                uint32_t n = 0;
#pragma unroll 1
                while (true) {
                    uint32_t mx = 0;
#pragma unroll
                    for (int j = j0; j < j1; j++) mx = max(mx, max(ov[j].x, ov[j].y));
                    if (!__any_sync(0xffffffffu, mx == SENT)) break;
#pragma unroll
                    for (int j = j0; j < j1; j++) in_ld2p(osrc + j * 256, ov[j], !in_ok(ov[j]));
                    if (++n > SPIN_LIMIT) __trap();
                }
            };
            float cw[4][4];
#pragma unroll
            for (int i = 0; i < 4; i++) cw[i][0] = cw[i][1] = cw[i][2] = cw[i][3] = 0.f;
            mbar_wait(after(p.zero, bar_tail + 8, osrc, wa, pw, pr, gdst), 0);
#pragma unroll
            for (int j = 0; j < NWP; j++) in_ld2p(osrc + j * 256, ov[j], true);
            gather(0, NWP - 1);
#pragma unroll
            for (int j = 0; j < NWP; j++) {
                if (j == NWP - 2) { gather(NWP - 1, NWP); if (tid == 224) LST(93); }
                mbar_wait(bar_tail + 8 * j, 0);
                if (j == NWP - 4) in_ld2p(osrc + (NWP - 1) * 256, ov[NWP - 1], !in_ok(ov[NWP - 1]));
                uint32_t a[4][4];
#pragma unroll
                for (int i = 0; i < 4; i++) ldsm_x4_t(a[i], (wa ^ (i << 5)) + j * WPIECE);
#pragma unroll
                for (int i = 0; i < 4; i++) mma_bf16(cw[i], a[i], ov[j].x, ov[j].y);
            }
#define SEL_(e) ((t & 2) ? ((t & 1) ? cw[3][e] : cw[2][e]) : ((t & 1) ? cw[1][e] : cw[0][e]))
            sts32(pw, SEL_(0)); sts32(pw + 32, SEL_(2));
#undef SEL_
            cons_sync();
            if (warp < 2 * cfg::HCOPY) {
                float2 r[8];
#pragma unroll
                for (int i = 0; i < 8; i++) r[i] = lds64f(pr + i * 256);
#define S_(c) (((r[0].c + r[1].c) + (r[2].c + r[3].c)) + ((r[4].c + r[5].c) + (r[6].c + r[7].c)))
                in_st1(gdst, __uint_as_float(pack_bf(S_(y), S_(x))));
#undef S_
            }
            if (tid == 0) LST(94);
        } else if (is_ffn) {
            uint32_t w13a = sbase + (warp * 16 + arow) * 64 + ((ahalf ^ (lane >> 1 & 3)) << 4);
            uint32_t red_dst = sbase + SM_RED + tid * 8;
            const uint32_t ha = sbase + SM_HN + warp * 32 + t * 8;
            uint32_t aw[2][NUP][2][4];
            auto load = [&](int m, int i) {
#pragma unroll
                for (int k = 0; k < 2; k++) ldsm_x4_t(aw[m][i][k], (w13a ^ (k << 5)) + (m * NUP + i) * (WPIECE / 2));
            };
#pragma unroll
            for (int j = 0; j < 3; j++) {
                mbar_wait(j ? bar_tail + 8 * j : after(p.zero, bar_tail, w13a, red_dst, ha), 0);
                load(2 * j / NUP, 2 * j % NUP); load((2 * j + 1) / NUP, (2 * j + 1) % NUP);
            }
            LSC(0);
            asm volatile("bar.sync 9, 416;" ::: "memory");
            uint32_t b0[NUP], b1[NUP];
#pragma unroll
            for (int i = 0; i < NUP; i++) {
                b0[i] = b1[i] = 0x3f803f80u;
                asm volatile("{\n.reg .pred q;\nsetp.eq.u32 q, %3, 0;\n@q ld.shared.v2.u32 {%0, %1}, [%2];\n}" : "+r"(b0[i]), "+r"(b1[i]) : "r"(ha + i * 256), "r"(lane & 4) : "memory");
            }
#pragma unroll
            for (int m = 0; m < 2; m++) {
                if (m) { mbar_wait(bar_tail + 8 * 3, 0); load(1, 1); load(1, 2); }
                float cf[2][2][4];
#pragma unroll
                for (int e = 0; e < 4; e++) cf[0][0][e] = cf[0][1][e] = cf[1][0][e] = cf[1][1][e] = 0.f;
#pragma unroll
                for (int i = 0; i < NUP; i++) {
                    if (m && i >= NUP - 2) { mbar_wait(bar_tail + 8 * (i + 1), 0); load(1, i); }
#pragma unroll
                    for (int k = 0; k < 2; k++) mma_bf16(cf[m ? 0 : i & 1][k], aw[m][i][k], b0[i], b1[i]);
                }
#define SEL_(c, e) ((t & 2) ? ((t & 1) ? cf[c][1][e + 2] : cf[c][1][e]) : ((t & 1) ? cf[c][0][e + 2] : cf[c][0][e]))
                if (m == 0) {
                    sts64(red_dst, __float_as_uint(SEL_(0, 0) + SEL_(1, 0)), __float_as_uint(SEL_(0, 1) + SEL_(1, 1)));
                    asm volatile("bar.arrive 8, 288;" ::: "memory");
                } else {
                    sts64(red_dst + 2048, __float_as_uint(SEL_(0, 0)), __float_as_uint(SEL_(0, 1)));
                }
#undef SEL_
            }
            LSC(7);
            asm volatile("bar.arrive 5, 288;" ::: "memory");
        }
        if (is_out) {
            uint32_t w2a = sbase + SM_W2 + (warp * 32 + arow) * 32 + ((ahalf ^ (lane >> 2 & 1)) << 4);
            uint32_t ydst = sbase + SM_HN + ((t & 1) * 8 + (lane >> 2)) * 48 + warp * 4;
            const unsigned char* asrc = p.xa + xa_off(L_ACT, msel) + oh * 512 + warp * 64 + t * 16;
            const uint32_t at = tail_time(cfg::T_AAT);
            uint32_t a[NDP][2][4];
            auto load_w2 = [&](int i) {
                mbar_wait(i ? bar_tail + 8 * (NWP + i) : after(p.zero, bar_tail + 8 * NWP, w2a, ydst, asrc, at), 0);
                ldsm_x4_t(a[i][0], w2a + i * PIECE); ldsm_x4_t(a[i][1], w2a + i * PIECE + 512);
            };
            load_w2(0);
            uint4 u[NDP];
            wait_until(at);
            LSC(0);
#pragma unroll
            for (int i = 0; i < NDP; i++) u[i] = in_ld4(asrc + i * 1024);
            load_w2(1);
            uint32_t n = 0;
#pragma unroll 1
            while (true) {
                uint32_t m[NDP];
#pragma unroll
                for (int i = 0; i < NDP; i++) m[i] = max(max(u[i].x, u[i].y), max(u[i].z, u[i].w));
                if (!__any_sync(0xffffffffu, max(max(m[0], m[1]), m[2]) == SENT)) break;
#pragma unroll
                for (int i = 0; i < NDP; i++) in_ld4p(asrc + i * 1024, u[i], m[i] == SENT);
                if (++n > SPIN_LIMIT) __trap();
            }
            LSC(12);
            if (tid == 96) LST(118);
            float cy[2 * NDP][4];
#pragma unroll
            for (int i = 0; i < NDP; i++) {
#pragma unroll
                for (int e = 0; e < 4; e++) cy[2 * i][e] = cy[2 * i + 1][e] = 0.f;
                if (i == NDP - 1) load_w2(i);
                mma_bf16(cy[2 * i], a[i][0], u[i].x, u[i].y);
                mma_bf16(cy[2 * i + 1], a[i][1], u[i].z, u[i].w);
            }
#define Y_(e) (((cy[0][e] + cy[1][e]) + (cy[2][e] + cy[3][e])) + (cy[4][e] + cy[5][e]))
            const float y = (t & 1) ? Y_(2) : Y_(0);
#undef Y_
            if (t < 2) sts32(ydst, y);
            LSC(13);
            asm volatile("bar.arrive 5, 288;" ::: "memory");
        }
    }
}

typedef CUresult (*EncodeTiledFn)(CUtensorMap*, CUtensorMapDataType, cuuint32_t, void*, const cuuint64_t*, const cuuint64_t*,
                                  const cuuint32_t*, const cuuint32_t*, CUtensorMapInterleave, CUtensorMapSwizzle,
                                  CUtensorMapL2promotion, CUtensorMapFloatOOBfill);

void make_map(EncodeTiledFn fn, CUtensorMap* tm, const void* w, const int (&d)[5], const int (&st)[4], const int (&bx)[5],
              CUtensorMapSwizzle sw, int promo) {
    cuuint64_t dims[5], strides[4];
    cuuint32_t box[5], estr[5];
    for (int i = 0; i < 5; i++) { dims[i] = (cuuint64_t)d[i]; box[i] = (cuuint32_t)bx[i]; estr[i] = 1; }
    for (int i = 0; i < 4; i++) strides[i] = (cuuint64_t)st[i];
    fn(tm, CU_TENSOR_MAP_DATA_TYPE_BFLOAT16, 5, const_cast<void*>(w), dims, strides, box, estr, CU_TENSOR_MAP_INTERLEAVE_NONE, sw,
       (CUtensorMapL2promotion)promo, CU_TENSOR_MAP_FLOAT_OOB_FILL_NONE);
}

}

extern "C" void kernel_launch(void* const* d_in, const int* in_sizes, int n_in, void* d_out, int out_size) {
    (void)in_sizes; (void)n_in; (void)out_size;
    static EncodeTiledFn encode = nullptr;
    static Scratch* scratch = nullptr;
    static unsigned char* xarea = nullptr;
    static double tscale = 1.0;
    if (!encode) {
        void* sp = nullptr;
        cudaGetSymbolAddress(&sp, g_scratch);
        scratch = reinterpret_cast<Scratch*>(sp);
        cudaGetSymbolAddress(&sp, g_xarea);
        xarea = reinterpret_cast<unsigned char*>((reinterpret_cast<uintptr_t>(sp) + XA_ALIGN - 1) / XA_ALIGN * XA_ALIGN);
        void* fn = nullptr;
        cudaDriverEntryPointQueryResult st;
        cudaGetDriverEntryPoint("cuTensorMapEncodeTiled", &fn, cudaEnableDefault, &st);
        encode = reinterpret_cast<EncodeTiledFn>(fn);
        int dev = 0, khz = 0, bits = 0;
        cudaGetDevice(&dev);
        cudaDeviceGetAttribute(&khz, cudaDevAttrMemoryClockRate, dev);
        cudaDeviceGetAttribute(&bits, cudaDevAttrGlobalMemoryBusWidth, dev);
        if (khz > 0 && bits > 0) tscale = (2619000.0 * 5120.0) / ((double)khz * bits);
        cudaFuncSetAttribute(fused_decode_kernel, cudaFuncAttributeMaxDynamicSharedMemorySize, SM_TOTAL);
    }
    KParams p;
    p.x = (const __nv_bfloat16*)d_in[0];
    p.wq = (const __nv_bfloat16*)d_in[3];
    p.out = (__nv_bfloat16*)d_out;
    p.sc = scratch;
    p.xa = xarea;
    p.zero = 0;
    p.t_first = (uint32_t)(4 * cfg::T_FIRST * tscale);
    p.t_step = (uint32_t)(cfg::T_STEP * tscale);
    p.t_smax = (uint32_t)(cfg::T_SMAX * tscale);
    p.t_lat = (uint32_t)(4 * (450 + (cfg::T_LAT - 450) * tscale));
    TMaps tm;
    constexpr int R1 = FF * 2, R2 = D_MODEL * 2;
    make_map(encode, &tm.k, d_in[1], {64, NHEAD * SK * 3, 1, 1, 1}, {128, 128, 128, 128}, {64, 96, 1, 1, 1}, CU_TENSOR_MAP_SWIZZLE_128B, cfg::PROMO_KV);
    make_map(encode, &tm.v, d_in[2], {64, NHEAD * SK * 3, 1, 1, 1}, {128, 128, 128, 128}, {64, 96, 1, 1, 1}, CU_TENSOR_MAP_SWIZZLE_128B, cfg::PROMO_KV);
    make_map(encode, &tm.wo, d_in[4], {D_MODEL, NHEAD * DH, 1, 1, 1}, {R2, R2, R2, R2}, {64, 128, 1, 1, 1}, CU_TENSOR_MAP_SWIZZLE_128B, cfg::PROMO_WO);
    make_map(encode, &tm.w1, d_in[6], {FF, 2, 4, 2, 40}, {R1, 4 * R1, 2 * R1, 16 * R1}, {32, 2, 4, 2, 8}, CU_TENSOR_MAP_SWIZZLE_64B, cfg::PROMO_W13);
    make_map(encode, &tm.w3, d_in[7], {FF, 2, 4, 2, 40}, {R1, 4 * R1, 2 * R1, 16 * R1}, {32, 2, 4, 2, 8}, CU_TENSOR_MAP_SWIZZLE_64B, cfg::PROMO_W13);
    make_map(encode, &tm.w2, d_in[8], {D_MODEL, FF, 1, 1, 1}, {R2, R2, R2, R2}, {16, 256, 1, 1, 1}, CU_TENSOR_MAP_SWIZZLE_32B, cfg::PROMO_W2);
    fused_decode_kernel<<<NCTA, NTHREADS, SM_TOTAL, cudaStreamPerThread>>>(p, tm);
}
```
